```python
import torch

def _softmax(x, axis=-1):
    return torch.softmax(x, dim=axis)
def _gelu(x):
    return torch.nn.functional.gelu(x, approximate="tanh")
def _silu(x):
    return torch.nn.functional.silu(x)
def _sigmoid(x):
    return torch.sigmoid(x)
def _layernorm(x, axis=-1, eps=1e-5):
    m = x.mean(dim=axis, keepdim=True)
    v = x.var(dim=axis, keepdim=True, unbiased=False)
    return (x - m) / torch.sqrt(v + eps)
def _scatter_add(tgt, idx, src, axis=0):
    return tgt.clone().index_add_(axis, idx, src)
def _segment_sum(src, seg, n):
    out = torch.zeros((n,) + src.shape[1:], dtype=src.dtype)
    return out.index_add_(0, seg, src)
def _pad(x, pw):
    flat = tuple(v for pair in reversed(pw) for v in pair)
    return torch.nn.functional.pad(x, flat)

kernel_name = 'gated_mix__linear_attn_block__moe_arch_mod__prompt'

def setup_inputs():

    _w = (lambda a: (lambda t: t.to(torch.bfloat16) if t.is_floating_point() else t)(torch.as_tensor(a)))
    def _A_setup():
        B, S, D = 1, 2048, 1024
        return {
            "x": _w((lambda *s: torch.randn(*s, dtype=torch.bfloat16) * 0.05)(B, S, D)),
            "wqkv": _w((lambda *s: torch.randn(*s, dtype=torch.bfloat16) * 0.8)(D, 3 * D)),
            "wo": _w((lambda *s: torch.randn(*s, dtype=torch.bfloat16) * 0.1)(D, D)),
        }
    _A_in = _A_setup()

    def _B_setup():
        B, S, D, F, C = 1, 2048, 1024, 3584, 1
        return {
            "x": _w((lambda *s: torch.randn(*s, dtype=torch.bfloat16) * 0.05)(B, S, D)),
            "w_r": _w((lambda *s: torch.randn(*s, dtype=torch.bfloat16) * 1.6)(D)),
            "w_gate": _w((lambda *s: torch.randn(*s, dtype=torch.bfloat16) * 0.1)(D, F)),
            "w_up": _w((lambda *s: torch.randn(*s, dtype=torch.bfloat16) * 0.1)(D, F)),
            "w_down": _w((lambda *s: torch.randn(*s, dtype=torch.bfloat16) * 0.1)(F, D)),
        }
    _B_in = _B_setup()

    return {
        "A_x": _A_in["x"],
        "A_wqkv": _A_in["wqkv"],
        "A_wo": _A_in["wo"],
        "B_x": _B_in["x"],
        "B_w_r": _B_in["w_r"],
        "B_w_gate": _B_in["w_gate"],
        "B_w_up": _B_in["w_up"],
        "B_w_down": _B_in["w_down"],
        "gate_w": _w((lambda *s: torch.randn(*s, dtype=torch.bfloat16) * 0.05)(1024) * 16.0),
    }

def reference(A_x, A_wqkv, A_wo, B_x, B_w_r, B_w_gate, B_w_up, B_w_down, gate_w):
    def _A_ref(x, wqkv, wo):
        B, S, D = x.shape
        H = 32; Dh = D // H
        qkv = (lambda x, *d: x.permute(*d))((x @ wqkv).reshape(B, S, 3, H, Dh), 2, 0, 3, 1, 4)
        q, k, v = qkv[0], qkv[1], qkv[2]
        phi = lambda t: torch.where(t > 0, t + 1, torch.exp(t)) + 1e-6
        pq, pk = phi(q), phi(k)
        kv = torch.einsum("bhsd,bhse->bhde", pk, v)
        z = torch.einsum("bhsd->bhd", pk)
        num = torch.einsum("bhqd,bhde->bhqe", pq, kv)
        den = torch.einsum("bhqd,bhd->bhq", pq, z)[..., None] + 1e-6
        o = num / den
        return (lambda x, *d: x.permute(*d))(o, 0, 2, 1, 3).reshape(B, S, D) @ wo

    def _B_ref(x, w_r, w_gate, w_up, w_down):
        B, S, D = x.shape
        C = 1
        r = x @ w_r
        idx = torch.argsort(-r, axis=-1)[:, :C]
        idx_e = (lambda x, n, axis: torch.repeat_interleave(x, n, dim=axis))(idx.reshape(B, C, 1), D, axis=2)
        x_sel = (lambda x, i, axis: torch.take_along_dim(x, i, dim=axis))(x, idx_e, axis=1)
        g = _silu(x_sel @ w_gate)
        u = x_sel @ w_up
        y = (g * u) @ w_down
        r_sel = _sigmoid((lambda x, i, axis: torch.take_along_dim(x, i, dim=axis))(r, idx, axis=1))
        y = y * r_sel.reshape(B, C, 1)
        b_off = (torch.arange(B) * S).reshape(B, 1)
        flat_idx = (idx + b_off).reshape(B * C)
        zero = (x * 0.0).reshape(B * S, D)
        upd = _scatter_add(zero, flat_idx, y.reshape(B * C, D), axis=0)
        return x + upd.reshape(B, S, D)

    x = A_x
    g = _sigmoid((x * gate_w).sum(-1, keepdims=True))
    a = _A_ref(x, A_wqkv, A_wo)
    b = _B_ref(x, B_w_r, B_w_gate, B_w_up, B_w_down)
    return g * a + (1 - g) * b
```

```cpp
#include <cuda_runtime.h>
#include <cuda.h>
#include <cuda_bf16.h>
#include <stdint.h>
#include <stddef.h>
#include <type_traits>

namespace {

constexpr int S_ = 2048, D_ = 1024, F_ = 3584;
constexpr int NCTA = 128, NGRID = 132, NTHREADS = 512;
#define NOMOD 0
constexpr int MOD_CTAS = NOMOD ? 0 : F_ / 32;

#define PRE 2
#define ST1 700
#define RT_G0 2
#define RT_ROT 1
#define RT_SLEEP 500
#define PF_MOD 7
#define MOD_START 9
#define MM 3
#define PO 2
#define A_SLEEP 128
#define KU 99
#define HS 1
#define GO 0
#define HOLD 5
#define OWN1 0
#define KF 8
#define QA 3
#define R0 1
#define OA 2
#define QD 0
#define MOD_SLEEP 0
#define MOD_S0 8
#define Y_SLEEP 200
#define PD 0
#define TRY_A 9
#define NAP_A 0
#define VK 1
#define G1 1
#define HP 2
#define KL 3
#define RS 2
#define EARLY_O 0
#define RETRY 1
#define KV_SLEEP_A 64
#define KV_SLEEP 50
#define TL 3
#define PAIRED 1
#define BYSM 1

constexpr uint32_t SLOT = 16384, WQKV_BYTES = 24576;
constexpr int MOD_BUFS = 3, MOD_BUFS0 = MOD_BUFS + 2;
static_assert(MOD_START + MOD_BUFS0 <= 16, "first FFN round is requested during W1");
constexpr uint32_t OFF_RING = 0, OFF_W1 = 4 * SLOT;
constexpr uint64_t OA_SLOTS = 0x0AB210AB21098210ull, OW_SLOTS = 0x4376543765437654ull;
constexpr uint32_t OFF_RES = OFF_RING + 8 * SLOT, RES_H = SLOT;
constexpr uint32_t OFF_PK = 10 * SLOT;
constexpr uint32_t OFF_V = 11 * SLOT;
constexpr uint32_t OFF_ONES = OFF_V + 9216 + 8192;
constexpr uint32_t MOD_STEP = 9216, OFF_MOD = OFF_V + 2 * MOD_STEP;
constexpr uint32_t OFF_XSEL = OFF_MOD + 8192;
constexpr uint32_t OFF_KVB = OFF_MOD + 2 * MOD_STEP + 8192;
constexpr uint32_t KVB_N = 1056;
constexpr uint32_t OFF_G = OFF_KVB + 4 * KVB_N + 1024;
constexpr uint32_t OFF_PART = OFF_G + 512;
constexpr uint32_t OFF_MISC = OFF_PART + 576;
constexpr uint32_t OFF_BAR = OFF_MISC + 32;
constexpr uint32_t SMEM_BYTES = OFF_BAR + 480;
constexpr uint32_t BAR_FULL = OFF_BAR, BAR_EMPTY = OFF_BAR + 64, BAR_OEMPTY = BAR_EMPTY + 64, BAR_RTD = BAR_OEMPTY + 40, BAR_DONE = BAR_RTD + 8,
                   BAR_OWN = BAR_DONE + 8, BAR_PA = BAR_OWN + 8, BAR_PUB = BAR_PA + 8, BAR_MEMPTY = BAR_PUB + 16,
                   BAR_IDX = BAR_MEMPTY + 8,
                   BAR_OFULL = BAR_MEMPTY + MOD_BUFS0 * 8, BAR_Y = BAR_OFULL + 40, BAR_X = BAR_Y + 8, BAR_PEER = BAR_X + 8, BAR_GATE = BAR_PEER + 8,
                   BAR_RT = BAR_GATE + 8, BAR_MFULL = BAR_RT + 32, BAR_FIX = BAR_MFULL + MOD_BUFS0 * 8,
                   BAR_END = BAR_FIX + 72, BAR_LAND = BAR_FULL;
static_assert(BAR_END - OFF_BAR <= 480, "warp w initialises barriers 4w .. 4w + 3");
static_assert(SMEM_BYTES <= 232448, "smem");
static_assert(TL == 3 && PRE == 2, "schedule");
constexpr __host__ __device__ uint64_t bar_counts(int first) {
  uint64_t r = 0;
  for (uint32_t i = 0; i < 16; i++) {
    const uint32_t b = OFF_BAR + (first + i) * 8;
    const uint64_t c = b < BAR_EMPTY || b >= BAR_Y ? 1 : b == BAR_IDX ? 5 : b < BAR_OFULL ? 4 : 5;
    r |= c << i * 4;
  }
  return r;
}

constexpr int NB_WG0 = 1, NB_ORDER_12 = 3, NB_ORDER_3O = 4, NB_STG = 5, NB_MODW = 6, NB_KEY = 7, NB_HOLD = 8;

struct Scratch {
  uint4 kv[2][8][3][128];
  float4 y[2][3][128];
  unsigned cnt[32][32];
  unsigned gslot[S_];
  unsigned rslot[8][NCTA];
  unsigned spare[128];
  unsigned block[NCTA];
  uint4 o[16][16][1024];
};
static_assert(offsetof(Scratch, gslot) == NCTA * 56 * 16, "clear size");
__device__ __align__(1024) Scratch g_scratch;

#define PROF(cond, i) do {} while (0)
#define PROF_C(cond, i) do {} while (0)

__device__ __forceinline__ void mbar_init(uint32_t bar, int cnt) { asm volatile("mbarrier.init.shared::cta.b64 [%0], %1;" ::"r"(bar), "r"(cnt)); }
__device__ __forceinline__ void mbar_expect_tx(uint32_t bar, uint32_t bytes) { asm volatile("mbarrier.arrive.expect_tx.shared::cta.b64 _, [%0], %1;" ::"r"(bar), "r"(bytes) : "memory"); }
__device__ __forceinline__ void mbar_arrive(uint32_t bar) { asm volatile("mbarrier.arrive.shared::cta.b64 _, [%0];" ::"r"(bar) : "memory"); }
__device__ __forceinline__ uint32_t peer_addr(uint32_t a) {
  uint32_t r;
  asm volatile("{\n.reg .u32 c;\nmov.u32 c, %%cluster_ctarank;\nxor.b32 c, c, 1;\nmapa.shared::cluster.u32 %0, %1, c;\n}" : "=r"(r) : "r"(a));
  return r;
}
__device__ __forceinline__ void mbar_arrive_peer(uint32_t bar) { asm volatile("mbarrier.arrive.shared::cluster.b64 _, [%0];" ::"r"(bar) : "memory"); }
__device__ __forceinline__ uint32_t mism(uint32_t a, uint32_t b, uint32_t p) {
  uint32_t r; asm("lop3.b32 %0, %1, %2, %3, 0x7E;" : "=r"(r) : "r"(a), "r"(b), "r"(p)); return r;
}
__device__ __forceinline__ bool elect() {
  uint32_t r;
  asm volatile("{\n.reg .pred p;\nelect.sync _|p, 0xffffffff;\nselp.u32 %0, 1, 0, p;\n}" : "=r"(r));
  return r;
}
__device__ __forceinline__ uint32_t fresh_tid() { uint32_t r; asm volatile("mov.u32 %0, %%tid.x;" : "=r"(r)); return r; }
__device__ __forceinline__ void mbar_arrive_warp(uint32_t bar) {
  asm volatile("{\n.reg .pred p;\nelect.sync _|p, 0xffffffff;\n@p mbarrier.arrive.shared::cta.b64 _, [%0];\n}" ::"r"(bar) : "memory");
}
__device__ __forceinline__ void mbar_wait(uint32_t bar, uint32_t parity) {
  asm volatile("{\n.reg .pred p;\nWAIT_L:\nmbarrier.try_wait.parity.shared::cta.b64 p, [%0], %1;\n@p bra DONE_L;\nbra WAIT_L;\nDONE_L:\n}"
               ::"r"(bar), "r"(parity) : "memory");
}
__device__ __forceinline__ uint32_t mbar_try(uint32_t bar, uint32_t parity) {
  uint32_t ok;
  asm volatile("{\n.reg .pred p;\nmbarrier.try_wait.parity.shared::cta.b64 p, [%1], %2;\nselp.u32 %0, 1, 0, p;\n}" : "=r"(ok) : "r"(bar), "r"(parity) : "memory");
  return ok;
}
__device__ __forceinline__ uint32_t mbar_test(uint32_t bar, uint32_t parity) {
  uint32_t ok;
  asm volatile("{\n.reg .pred p;\nmbarrier.test_wait.parity.shared::cta.b64 p, [%1], %2;\nselp.u32 %0, 1, 0, p;\n}" : "=r"(ok) : "r"(bar), "r"(parity) : "memory");
  return ok;
}
constexpr unsigned long long WATCHDOG_NS = 2000000000ull;
__device__ __forceinline__ unsigned long long gtime() { unsigned long long t; asm volatile("mov.u64 %0, %%globaltimer;" : "=l"(t)); return t; }
__device__ __forceinline__ uint32_t clock32() { uint32_t t; asm volatile("mov.u32 %0, %%clock;" : "=r"(t)); return t; }
__device__ __forceinline__ void mbar_wait_bounded(uint32_t bar, uint32_t parity) {
  unsigned long long t0 = 0;
  for (;;) {
    uint32_t ok;
    asm volatile("{\n.reg .pred p;\nmbarrier.try_wait.parity.shared::cta.b64 p, [%1], %2;\nselp.u32 %0, 1, 0, p;\n}" : "=r"(ok) : "r"(bar), "r"(parity) : "memory");
    if (ok) break;
    const unsigned long long t1 = gtime();
    if (t0 == 0) t0 = t1;
    if (t1 - t0 > WATCHDOG_NS) __trap();
  }
}
__device__ __forceinline__ void tma2d(uint32_t dst, const CUtensorMap* m, int c0, int c1, uint32_t bar) {
  asm volatile("cp.async.bulk.tensor.2d.shared::cluster.global.mbarrier::complete_tx::bytes [%0], [%1, {%3, %4}], [%2];"
               ::"r"(dst), "l"(m), "r"(bar), "r"(c0), "r"(c1) : "memory");
}
__device__ __forceinline__ void tma3d(uint32_t dst, const CUtensorMap* m, int c0, int c1, int c2, uint32_t bar) {
  asm volatile("cp.async.bulk.tensor.3d.shared::cluster.global.mbarrier::complete_tx::bytes [%0], [%1, {%3, %4, %5}], [%2];"
               ::"r"(dst), "l"(m), "r"(bar), "r"(c0), "r"(c1), "r"(c2) : "memory");
}
__device__ __forceinline__ void bulk_load(uint32_t dst, const void* src, uint32_t bytes, uint32_t bar) {
  asm volatile("cp.async.bulk.shared::cluster.global.mbarrier::complete_tx::bytes [%0], [%1], %2, [%3];" ::"r"(dst), "l"(src), "r"(bytes), "r"(bar) : "memory");
}
__device__ __forceinline__ void bulk_store(void* dst, uint32_t src, uint32_t bytes) {
  asm volatile("cp.async.bulk.global.shared::cta.bulk_group [%0], [%1], %2;" ::"l"(dst), "r"(src), "r"(bytes) : "memory");
}
__device__ __forceinline__ void st_async4(uint32_t dst, const uint32_t (&v)[4], uint32_t bar) {
  asm volatile("st.async.shared::cluster.mbarrier::complete_tx::bytes.v4.b32 [%0], {%1, %2, %3, %4}, [%5];" ::"r"(dst), "r"(v[0]), "r"(v[1]), "r"(v[2]), "r"(v[3]), "r"(bar) : "memory");
}
__device__ __forceinline__ void bulk_commit() { asm volatile("cp.async.bulk.commit_group;" ::: "memory"); }
__device__ __forceinline__ void bulk_prefetch(const void* p, uint32_t bytes) {
  asm volatile("cp.async.bulk.prefetch.L2.global [%0], %1;" ::"l"(p), "r"(bytes) : "memory");
}
__device__ __forceinline__ void tma2d_store(const CUtensorMap* m, uint32_t src, int c0, int c1) {
  asm volatile("cp.async.bulk.tensor.2d.global.shared::cta.bulk_group [%0, {%2, %3}], [%1];" ::"l"(m), "r"(src), "r"(c0), "r"(c1) : "memory");
}
__device__ __forceinline__ void wg_fence() { asm volatile("wgmma.fence.sync.aligned;" ::: "memory"); }
__device__ __forceinline__ void wg_commit() { asm volatile("wgmma.commit_group.sync.aligned;" ::: "memory"); }
template <int N> __device__ __forceinline__ void wg_wait() { asm volatile("wgmma.wait_group.sync.aligned %0;" ::"n"(N) : "memory"); }
__device__ __forceinline__ void fence_async_smem() { asm volatile("fence.proxy.async.shared::cta;" ::: "memory"); }
__device__ __forceinline__ void fence_async_global() { asm volatile("fence.proxy.async.global;" ::: "memory"); }
__device__ __forceinline__ void fence_release() { asm volatile("fence.release.gpu;" ::: "memory"); }
__device__ __forceinline__ void fence_acquire() { asm volatile("fence.acquire.gpu;" ::: "memory"); }
__device__ __forceinline__ void nb_sync(int id, int n) { asm volatile("bar.sync %0, %1;" ::"r"(id), "r"(n) : "memory"); }
__device__ __forceinline__ void nb_arrive(int id, int n) { asm volatile("bar.arrive %0, %1;" ::"r"(id), "r"(n) : "memory"); }
__device__ __forceinline__ void stsm4(uint32_t addr, uint32_t r0, uint32_t r1, uint32_t r2, uint32_t r3) {
  asm volatile("stmatrix.sync.aligned.m8n8.x4.shared.b16 [%0], {%1, %2, %3, %4};" ::"r"(addr), "r"(r0), "r"(r1), "r"(r2), "r"(r3) : "memory");
}
__device__ __forceinline__ void stsm4t(uint32_t addr, uint32_t r0, uint32_t r1, uint32_t r2, uint32_t r3) {
  asm volatile("stmatrix.sync.aligned.m8n8.x4.trans.shared.b16 [%0], {%1, %2, %3, %4};" ::"r"(addr), "r"(r0), "r"(r1), "r"(r2), "r"(r3) : "memory");
}
__device__ __forceinline__ void st_relaxed4(void* p, const uint32_t (&v)[4]) {
  asm volatile("st.relaxed.gpu.global.v4.u32 [%0], {%1, %2, %3, %4};" ::"l"(p), "r"(v[0]), "r"(v[1]), "r"(v[2]), "r"(v[3]) : "memory");
}
__device__ __forceinline__ void sts128(uint32_t addr, uint32_t a, uint32_t b, uint32_t c, uint32_t d) {
  asm volatile("st.shared.v4.b32 [%0], {%1, %2, %3, %4};" ::"r"(addr), "r"(a), "r"(b), "r"(c), "r"(d) : "memory");
}
__device__ __forceinline__ uint32_t pack2(float lo, float hi) {
  uint32_t r; asm("cvt.rn.bf16x2.f32 %0, %1, %2;" : "=r"(r) : "f"(hi), "f"(lo)); return r;
}
__device__ __forceinline__ float bf_lo(uint32_t v) { return __uint_as_float(v << 16); }
__device__ __forceinline__ float bf_hi(uint32_t v) { return __uint_as_float(v & 0xffff0000u); }
__device__ __forceinline__ float bf_round(float v) { return __bfloat162float(__float2bfloat16_rn(v)); }
__device__ __forceinline__ void ldsm4(uint32_t addr, uint32_t (&r)[4]) {
  asm volatile("ldmatrix.sync.aligned.m8n8.x4.shared.b16 {%0, %1, %2, %3}, [%4];" : "=r"(r[0]), "=r"(r[1]), "=r"(r[2]), "=r"(r[3]) : "r"(addr) : "memory");
}
__device__ __forceinline__ uint4 lds128(uint32_t addr) {
  uint4 v; asm volatile("ld.volatile.shared.v4.u32 {%0, %1, %2, %3}, [%4];" : "=r"(v.x), "=r"(v.y), "=r"(v.z), "=r"(v.w) : "r"(addr) : "memory"); return v;
}
__device__ __forceinline__ uint2 lds64(uint32_t addr) { uint2 v; asm volatile("ld.volatile.shared.v2.u32 {%0, %1}, [%2];" : "=r"(v.x), "=r"(v.y) : "r"(addr) : "memory"); return v; }
__device__ __forceinline__ uint32_t lds32(uint32_t addr) { uint32_t v; asm volatile("ld.volatile.shared.u32 %0, [%1];" : "=r"(v) : "r"(addr) : "memory"); return v; }
__device__ __forceinline__ uint32_t ld_generic(const void* p) { uint32_t v; asm volatile("ld.volatile.u32 %0, [%1];" : "=r"(v) : "l"(p) : "memory"); return v; }
__device__ __forceinline__ void sts32(uint32_t addr, uint32_t v) { asm volatile("st.shared.u32 [%0], %1;" ::"r"(addr), "r"(v) : "memory"); }
__device__ __forceinline__ uint32_t fma_bf2(uint32_t a, uint32_t b, uint32_t c) { uint32_t r; asm("fma.rn.bf16x2 %0, %1, %2, %3;" : "=r"(r) : "r"(a), "r"(b), "r"(c)); return r; }
__device__ __forceinline__ uint32_t mul_bf2(uint32_t a, uint32_t b) { uint32_t r; asm("mul.rn.bf16x2 %0, %1, %2;" : "=r"(r) : "r"(a), "r"(b)); return r; }
__device__ __forceinline__ unsigned ld_relaxed(const unsigned* p) { unsigned v; asm volatile("ld.relaxed.gpu.global.u32 %0, [%1];" : "=r"(v) : "l"(p) : "memory"); return v; }
__device__ __forceinline__ void st_relaxed(unsigned* p, unsigned v) { asm volatile("st.relaxed.gpu.global.u32 [%0], %1;" ::"l"(p), "r"(v) : "memory"); }
__device__ __forceinline__ uint4 ld_relaxed4(const void* p) {
  uint4 v; asm volatile("ld.relaxed.gpu.global.v4.u32 {%0, %1, %2, %3}, [%4];" : "=r"(v.x), "=r"(v.y), "=r"(v.z), "=r"(v.w) : "l"(p) : "memory"); return v;
}
__device__ __forceinline__ float4 ld_relaxed_f4(const void* p) {
  float4 v; asm volatile("ld.relaxed.gpu.global.v4.f32 {%0, %1, %2, %3}, [%4];" : "=f"(v.x), "=f"(v.y), "=f"(v.z), "=f"(v.w) : "l"(p) : "memory"); return v;
}
__device__ __forceinline__ void red_add4(void* p, float a, float b, float c, float d) {
  asm volatile("red.relaxed.gpu.global.add.v4.f32 [%0], {%1, %2, %3, %4};" ::"l"(p), "f"(a), "f"(b), "f"(c), "f"(d) : "memory");
}
__device__ __forceinline__ void red_add_bf(void* p, uint32_t a, uint32_t b, uint32_t c) {
  asm volatile("red.relaxed.gpu.global.add.noftz.v4.bf16x2 [%0], {%1, %2, %3, %4};" ::"l"(p), "r"(a), "r"(b), "r"(c), "r"(0x3F803F80u) : "memory");
}
__device__ __forceinline__ void red_add(unsigned* p, unsigned v) { asm volatile("red.relaxed.gpu.global.add.u32 [%0], %1;" ::"l"(p), "r"(v) : "memory"); }
__device__ __forceinline__ float rcp(float v) { float r; asm("rcp.approx.ftz.f32 %0, %1;" : "=f"(r) : "f"(v)); return r; }
__device__ __forceinline__ float sigmoidf_(float v) { return rcp(1.f + __expf(-v)); }
__device__ __forceinline__ uint32_t phi2(float a, float b, float l2e = 1.4426950408889634f) {
  float ea, eb;
  asm("ex2.approx.ftz.f32 %0, %1;" : "=f"(ea) : "f"(a * l2e));
  asm("ex2.approx.ftz.f32 %0, %1;" : "=f"(eb) : "f"(b * l2e));
  uint32_t t = pack2(a, b), e = pack2(ea, eb), r;
  asm("max.NaN.bf16x2 %0, %0, %1;" : "+r"(t) : "r"(0x35863586u));
  asm("min.bf16x2 %0, %0, %1;" : "+r"(e) : "r"(0x3F803F80u));
  asm("add.rn.bf16x2 %0, %1, %2;" : "=r"(r) : "r"(t), "r"(e));
  return r;
}
__device__ __forceinline__ uint64_t mkdesc(uint32_t addr, uint32_t lbo, uint32_t sbo, uint32_t sw) {
  return (uint64_t)(((addr & 0x3FFFF) >> 4) | ((lbo >> 4) << 16)) | ((uint64_t)((sbo >> 4) | (sw << 30)) << 32);
}

template <int TA, int TB>
__device__ __forceinline__ void mma128(float (&d)[64], uint64_t da, uint64_t db, int sc) {
  asm volatile("{\n.reg .pred p;\nsetp.ne.b32 p, %66, 0;\n"
    "wgmma.mma_async.sync.aligned.m64n128k16.f32.bf16.bf16 "
    "{%0,%1,%2,%3,%4,%5,%6,%7,%8,%9,%10,%11,%12,%13,%14,%15,%16,%17,%18,%19,%20,%21,%22,%23,"
    "%24,%25,%26,%27,%28,%29,%30,%31,%32,%33,%34,%35,%36,%37,%38,%39,%40,%41,%42,%43,%44,%45,%46,%47,"
    "%48,%49,%50,%51,%52,%53,%54,%55,%56,%57,%58,%59,%60,%61,%62,%63}, "
    "%64, %65, p, 1, 1, %67, %68;\n}\n"
    : "+f"(d[0]), "+f"(d[1]), "+f"(d[2]), "+f"(d[3]), "+f"(d[4]), "+f"(d[5]), "+f"(d[6]), "+f"(d[7]),
      "+f"(d[8]), "+f"(d[9]), "+f"(d[10]), "+f"(d[11]), "+f"(d[12]), "+f"(d[13]), "+f"(d[14]), "+f"(d[15]),
      "+f"(d[16]), "+f"(d[17]), "+f"(d[18]), "+f"(d[19]), "+f"(d[20]), "+f"(d[21]), "+f"(d[22]), "+f"(d[23]),
      "+f"(d[24]), "+f"(d[25]), "+f"(d[26]), "+f"(d[27]), "+f"(d[28]), "+f"(d[29]), "+f"(d[30]), "+f"(d[31]),
      "+f"(d[32]), "+f"(d[33]), "+f"(d[34]), "+f"(d[35]), "+f"(d[36]), "+f"(d[37]), "+f"(d[38]), "+f"(d[39]),
      "+f"(d[40]), "+f"(d[41]), "+f"(d[42]), "+f"(d[43]), "+f"(d[44]), "+f"(d[45]), "+f"(d[46]), "+f"(d[47]),
      "+f"(d[48]), "+f"(d[49]), "+f"(d[50]), "+f"(d[51]), "+f"(d[52]), "+f"(d[53]), "+f"(d[54]), "+f"(d[55]),
      "+f"(d[56]), "+f"(d[57]), "+f"(d[58]), "+f"(d[59]), "+f"(d[60]), "+f"(d[61]), "+f"(d[62]), "+f"(d[63])
    : "l"(da), "l"(db), "r"(sc), "n"(TA), "n"(TB));
}

__device__ __forceinline__ void mma_ktv(float (&d)[36], const uint32_t (&a)[4], uint64_t db, int sc) {
  asm volatile("{\n.reg .pred p;\nsetp.ne.b32 p, %41, 0;\n"
    "wgmma.mma_async.sync.aligned.m64n72k16.f32.bf16.bf16 "
    "{%0,%1,%2,%3,%4,%5,%6,%7,%8,%9,%10,%11,%12,%13,%14,%15,%16,%17,%18,%19,%20,%21,%22,%23,"
    "%24,%25,%26,%27,%28,%29,%30,%31,%32,%33,%34,%35}, "
    "{%36,%37,%38,%39}, %40, p, 1, 1, 0;\n}\n"
    : "+f"(d[0]), "+f"(d[1]), "+f"(d[2]), "+f"(d[3]), "+f"(d[4]), "+f"(d[5]), "+f"(d[6]), "+f"(d[7]),
      "+f"(d[8]), "+f"(d[9]), "+f"(d[10]), "+f"(d[11]), "+f"(d[12]), "+f"(d[13]), "+f"(d[14]), "+f"(d[15]),
      "+f"(d[16]), "+f"(d[17]), "+f"(d[18]), "+f"(d[19]), "+f"(d[20]), "+f"(d[21]), "+f"(d[22]), "+f"(d[23]),
      "+f"(d[24]), "+f"(d[25]), "+f"(d[26]), "+f"(d[27]), "+f"(d[28]), "+f"(d[29]), "+f"(d[30]), "+f"(d[31]),
      "+f"(d[32]), "+f"(d[33]), "+f"(d[34]), "+f"(d[35])
    : "r"(a[0]), "r"(a[1]), "r"(a[2]), "r"(a[3]), "l"(db), "r"(sc));
}

__device__ __forceinline__ void mma_qkvz(float (&d)[20], uint64_t da, uint64_t db, int sc) {
  asm volatile("{\n.reg .pred p;\nsetp.ne.b32 p, %22, 0;\n"
    "wgmma.mma_async.sync.aligned.m64n40k16.f32.bf16.bf16 "
    "{%0,%1,%2,%3,%4,%5,%6,%7,%8,%9,%10,%11,%12,%13,%14,%15,%16,%17,%18,%19}, "
    "%20, %21, p, 1, 1, 0, 1;\n}\n"
    : "+f"(d[0]), "+f"(d[1]), "+f"(d[2]), "+f"(d[3]), "+f"(d[4]), "+f"(d[5]), "+f"(d[6]), "+f"(d[7]),
      "+f"(d[8]), "+f"(d[9]), "+f"(d[10]), "+f"(d[11]), "+f"(d[12]), "+f"(d[13]), "+f"(d[14]), "+f"(d[15]),
      "+f"(d[16]), "+f"(d[17]), "+f"(d[18]), "+f"(d[19])
    : "l"(da), "l"(db), "r"(sc));
}

template <int N> __device__ __forceinline__ void pin(float (&d)[N]) {
#pragma unroll
  for (int i = 0; i < N; i++) asm volatile("" : "+f"(d[i])::"memory");
}

struct Params {
  CUtensorMap x, w, xr, gate, up, wo, out, down;
};

__device__ __forceinline__ uint32_t dup_lo(uint32_t v) { uint32_t r; asm("{\n.reg .b16 l, h;\nmov.b32 {l, h}, %1;\nmov.b32 %0, {l, l};\n}" : "=r"(r) : "r"(v)); return r; }
__device__ __forceinline__ uint32_t dup_hi(uint32_t v) { uint32_t r; asm("{\n.reg .b16 l, h;\nmov.b32 {l, h}, %1;\nmov.b32 %0, {h, h};\n}" : "=r"(r) : "r"(v)); return r; }
__device__ __forceinline__ float butterfly8(float (&s)[8], int lane, int o) {
#pragma unroll
  for (int k = 1; k < 8; k <<= 1) {
    const bool up = lane & (o * k);
#pragma unroll
    for (int j = 0; j < 4 / k; j++) s[j] = (up ? s[2 * j + 1] : s[2 * j]) + __shfl_xor_sync(~0u, up ? s[2 * j] : s[2 * j + 1], o * k);
  }
  return s[0];
}
constexpr int OWN = 8, PEER = 9;
static_assert((OA_SLOTS >> OWN * 4 & 15) * SLOT == OFF_V && (OA_SLOTS >> PEER * 4 & 15) * SLOT == OFF_PK, "");
template <int B> __device__ __forceinline__ void verify_tiles(uint32_t sb, Scratch* gs, int tm, int tn, int w, int lane) {
  const uint32_t par = lds32(sb + OFF_MISC + 24), fix = sb + BAR_FIX + (B * 4 + w) * 8;
  uint32_t slots = (uint32_t)(OA_SLOTS >> B * 40);
#pragma unroll 1
  for (int i = 0; i < 8 - 2 * B; i++, slots >>= 4) {
    const uint32_t a = sb + OFF_RING + (slots & 15) * SLOT + w * 1024, cw = a + lane * 32 + (lane >> 2) * 4;
    if (!B && i == 4) mbar_wait(sb + BAR_EMPTY + 7 * 8, 1);
    mbar_wait(sb + BAR_LAND + i * 8, B);
    for (;;) {
      const uint32_t u0 = lds32(cw), u1 = lds32(cw + 4096), u2 = lds32(cw + 8192), u3 = lds32(cw + 12288);
      if (__all_sync(~0u, !(mism(mism(u0, u1, par), mism(u2, u3, par), 0) & 1))) break;
      const uint4* src = gs->o[tm][!B ? i : i < (tn & 6) ? i + 8 : i + 10] + w * 64;
      const uint32_t ph = !mbar_test(fix, 1);
      fence_async_smem();
      __syncwarp();
      if (elect()) {
        mbar_expect_tx(fix, 4096);
#pragma unroll 1
        for (int j = 0; j < 4; j++) bulk_load(a + j * 4096, src + j * 256, 1024, fix);
      }
      mbar_wait(fix, ph);
    }
    mbar_arrive_warp(sb + BAR_OFULL + (i < 5 ? i : i - 5) * 8);
  }
}
template <bool BY_SM> struct Tile {
  int sm, tm, tn, mu;
  bool spare;
  __device__ __forceinline__ Tile() {
    if (BY_SM) asm volatile("mov.u32 %0, %%smid;" : "=r"(sm));
    else sm = blockIdx.x + (blockIdx.x >= 120) * 4;
    const int tp = sm >> 1, pr = sm & 1;
    const int v = tp < 32 ? tp : tp < 60 ? (tp * 293 - 928) >> 8 : tp * 8 - 464, g = v & 7, i = v >> 3;
    tm = (v & 6) * 2 + (i & 3); tn = (v & 1) * 4 + (v >> 4 & 2) + pr;
    mu = i == 5 ? 112 : g * 14 + (i - (i > 5)) * 2 + pr;
    spare = (tp | 1) == 61;
  }
};

template <bool BY_SM> __global__ void __cluster_dims__(2, 1, 1) __launch_bounds__(NTHREADS, 1) fused_kernel(const __nv_bfloat16* __restrict__ px, Scratch* gs, const __nv_bfloat16* __restrict__ w_gate,
             const __nv_bfloat16* __restrict__ w_up, const __nv_bfloat16* __restrict__ w_r, const __nv_bfloat16* __restrict__ gate_w, const __nv_bfloat16* __restrict__ w_down,
             const __grid_constant__ Params p) {
  extern __shared__ __align__(1024) uint8_t smem[];
  const uint32_t sb = __shfl_sync(~0u, (uint32_t)__cvta_generic_to_shared(smem), 0);
  const int tid = threadIdx.x, lane = tid & 31;
  const int warp = __shfl_sync(~0u, tid >> 5, 0), wg = warp >> 2;
  const uint32_t t_start = clock32();
  const Tile<BY_SM> tile;
  const int tm = tile.tm, tn = tile.tn, mu = tile.mu, cta = tm * 8 + tn;
  const uint32_t zero = tile.sm >> 12;
  if (warp == 0) {
#pragma unroll
    for (int s = 0; s < PRE; s++)
      if (elect()) mbar_init(sb + BAR_FULL + s * 8, 1);
    asm volatile("fence.mbarrier_init.release.cluster;" ::: "memory");
    if (!tile.spare) {
#pragma unroll
      for (int s = 0; s < PRE; s++) {
        if (elect()) tma3d(sb + OFF_W1 + s * WQKV_BYTES, &p.w, tn * 64, s * 64, 0, sb + BAR_FULL + s * 8);
        if (elect()) tma2d(sb + OFF_RING + s * SLOT, &p.x, s * 64, tm * 128, sb + BAR_FULL + s * 8);
        PROF(lane == 0, 64 + s);
      }
      if (elect()) {
#pragma unroll
        for (int s = 0; s < PRE; s++) mbar_expect_tx(sb + BAR_FULL + s * 8, SLOT + WQKV_BYTES);
      }
    }
  }
  if (warp) {
    const int wi = warp == 15 ? 0 : warp;
    const uint32_t lo = wi & 8 ? (wi & 4 ? (uint32_t)bar_counts(48) : (uint32_t)bar_counts(32)) : (wi & 4 ? (uint32_t)bar_counts(16) : (uint32_t)bar_counts(0));
    const uint32_t hi = wi & 8 ? (wi & 4 ? bar_counts(48) >> 32 : bar_counts(32) >> 32) : (wi & 4 ? bar_counts(16) >> 32 : bar_counts(0) >> 32);
    const uint32_t cnt = (wi & 2 ? hi : lo) >> (wi & 1) * 16;
#pragma unroll
    for (int i = 0; i < 4; i++)
      if ((i >= PRE || wi) && elect()) mbar_init(sb + OFF_BAR + wi * 32 + i * 8, cnt >> i * 4 & 15);
    asm volatile("fence.mbarrier_init.release.cluster;" ::: "memory");
  }
  __syncthreads();
  if (tile.spare) {
    if (warp == 0) {
      const unsigned tag = (ld_relaxed(&gs->spare[tile.sm & 3]) + 1) & 0xFFF;
      const unsigned long long t0 = gtime();
      uint4 r4;
      do {
        __nanosleep(2048);
        if (gtime() - t0 > WATCHDOG_NS) __trap();
        r4 = ld_relaxed4(&gs->rslot[tile.sm & 3][lane * 4]);
      } while (!__all_sync(~0u, (((r4.x ^ tag) | (r4.y ^ tag) | (r4.z ^ tag) | (r4.w ^ tag)) & 0xFFF) == 0));
      if (tid == 0) st_relaxed(&gs->spare[tile.sm & 3], tag);
    }
    return;
  }

  if (wg == 3) {
    asm volatile("setmaxnreg.dec.sync.aligned.u32 24;");
    if (warp == 12) {
      mbar_wait(sb + BAR_PUB, 0);
      while (!__all_sync(~0u, ld_relaxed(gs->cnt[tm]) == 0x44444444u)) __nanosleep(A_SLEEP);
      fence_acquire();
      fence_async_global();
      PROF(lane == 0, 7);
      mbar_wait(sb + BAR_GATE, 0);
      const uint32_t lowb = (1u << (tn & 6) * 4) - 1;
      uint32_t slabs = 0x76543210u, deps = 0xA9877654u;
      const unsigned* flag = gs->cnt[16 + tm];
      const uint4* src = gs->o[tm][0];
#pragma unroll 1
      for (int n = 8; n >= 6; n -= 2) {
        unsigned seen = n == 8 ? ~0u : 0;
        uint32_t slots = n == 8 ? (uint32_t)OA_SLOTS : (uint32_t)(OA_SLOTS >> 40);
#pragma unroll 1
        for (int i = 0; i < n; i++, slabs >>= 4, deps >>= 4, slots >>= 4) {
          const uint32_t need = 4u << (slabs & 7) * 4, land = sb + BAR_LAND + i * 8;
          if (!__all_sync(~0u, seen & need)) {
            while (!__all_sync(~0u, (seen = ld_relaxed(flag)) & need)) __nanosleep(32);
            fence_acquire();
            fence_async_global();
          }
          mbar_wait(sb + BAR_EMPTY + (deps & 15) * 8, i < 5);
          if (elect()) bulk_load(sb + OFF_RING + (slots & 15) * SLOT, src + (slabs & 7) * 1024, SLOT, land);
          if (elect()) mbar_expect_tx(land, SLOT);
          PROF(lane == 0, 44 + i + (n == 6) * 10);
        }
        slabs = (0x76543210u & lowb) | (0x765432u & ~lowb);
        deps = 0x8CBA98u;
        src += 8 * 1024;
        mbar_wait(sb + BAR_PUB + 8, 0);
      }
    } else if (warp == 13) {
#pragma unroll 1
      for (int g = PRE; g < 32; g++) {
        const bool reuse = (g >> 2) == 4;
        const uint32_t s = g & 3, full = sb + BAR_FULL + (g & 7) * 8, c0 = tn * 64 + (g & 16) * 32, c1 = (g < 16 ? g : g - 4 & 15) * 64;
        if (g < 4) while ((int)(clock32() - t_start) < g * ST1) {}
        mbar_wait(sb + BAR_EMPTY + (g + 4 & 7) * 8, (g + 4 >> 3 & 1) ^ 1);
        if (!reuse && elect()) tma2d(sb + OFF_RING + s * SLOT, &p.x, c1, tm * 128, full);
        if (elect()) tma3d(sb + OFF_W1 + s * WQKV_BYTES, &p.w, c0, c1, 0, full);
        if (elect()) mbar_expect_tx(full, reuse ? WQKV_BYTES : SLOT + WQKV_BYTES);
        PROF(lane == 0, 64 + g);
        const uint32_t i = g - RT_G0;
        if (i < 4 && elect()) {
          mbar_expect_tx(sb + BAR_RT + i * 8, i ? 8192 : 8192 + 4096);
          tma2d(sb + OFF_PK + i * 8192 + (i == 3) * 1024, &p.xr, ((i + RT_ROT) & 3) * 256, cta * 16, sb + BAR_RT + i * 8);
          if (i == 0) { bulk_load(sb + OFF_KVB, w_r, 2048, sb + BAR_RT); bulk_load(sb + OFF_KVB + 2048, gate_w, 2048, sb + BAR_RT); }
        }
        const uint32_t c = g - MOD_START;
        if (c == MOD_BUFS) mbar_wait(sb + BAR_RTD, 0);
        if (c < MOD_BUFS0 && mu < MOD_CTAS && elect()) {
          PROF(true, 192 + c);
          const uint32_t mb = c < MOD_BUFS ? c + 2 : c - MOD_BUFS, mfull = sb + BAR_MFULL + mb * 8, mdst = sb + OFF_V + mb * MOD_STEP;
          mbar_expect_tx(mfull, c ? 8192 : 8192 + 2048);
          tma3d(mdst, &p.gate, mu * 32, c * 16, 0, mfull); tma3d(mdst + 4096, &p.up, mu * 32, c * 16, 0, mfull);
        }
        const uint32_t pc = g - PF_MOD;
        if (pc < 16 && elect()) bulk_prefetch((cta & 64 ? w_up : w_gate) + (size_t)(pc * 64 + (cta & 63)) * F_, F_ * 2);
      }
      mbar_arrive_warp(sb + BAR_GATE);
      const uint32_t lowb = (1u << (tn & 6) * 4) - 1;
      uint64_t slabs = (uint64_t)((0xFEDCBA98u & lowb) | (0xFEDCBAu & ~lowb)) << 40 | (uint64_t)(8 + (tn ^ 1)) << 36 | (uint64_t)(8 + tn) << 32 | 0x76543210u;
      uint64_t deps = 0x8CBA98CBA9876554ull, ws = OW_SLOTS;
      uint32_t full = sb + BAR_OFULL, ph = 1;
#pragma unroll 1
      for (int g = 0; g < 16; g++, slabs >>= 4, deps >>= 4, ws >>= 4) {
        mbar_wait(sb + BAR_EMPTY + ((uint32_t)deps & 15) * 8, ph);
        if (elect()) tma3d(sb + OFF_RING + ((uint32_t)ws & 15) * SLOT, &p.wo, 0, ((uint32_t)slabs & 15) * 64, tn * 2, full);
        if (elect()) mbar_expect_tx(full, SLOT);
        PROF(lane == 0, 96 + g);
        if (g >> 1 == OWN / 2 && lane < 4) mbar_arrive(full);
        full += 8;
        if (full == sb + BAR_OFULL + 40) { full -= 40; ph ^= 1; }
      }
    } else if (warp == 14) {
      if (mu < MOD_CTAS) {
        uint32_t full = sb + BAR_MFULL + 16, dst = sb + OFF_MOD, ph = 0;
#pragma unroll 1
        for (int c = MOD_BUFS0; c < 24; c++) {
          mbar_wait(full + (BAR_MEMPTY - BAR_MFULL), ph);
          PROF(lane == 0, 192 + c);
          if (c < 16) {
            if (elect()) { tma3d(dst, &p.gate, mu * 32, c * 16, 0, full); tma3d(dst + 4096, &p.up, mu * 32, c * 16, 0, full); }
          } else if (elect()) tma3d(dst, &p.down, 0, mu * 32 + (c - 16) * 4, 0, full);
          if (elect()) mbar_expect_tx(full, 8192);
          if (PD && (uint32_t)(c + PD - 16) < 8 && elect()) bulk_prefetch(w_down + (size_t)(mu * 32 + (c + PD - 16) * 4) * D_, 8192);
          full += 8; dst += MOD_STEP;
          if (full == sb + BAR_FIX) { full -= MOD_BUFS * 8; dst = sb + OFF_MOD; ph ^= 1; }
        }
      }
      if (elect()) {
      mbar_wait(sb + BAR_IDX, 0);
      const bool paired = PAIRED && ld_relaxed(&gs->block[cta ^ 1]) == (blockIdx.x ^ 1);
      if (paired) mbar_expect_tx(sb + BAR_PEER, SLOT);
      mbar_expect_tx(sb + BAR_X, 32768);
      mbar_wait(sb + BAR_OEMPTY + 3 * 8, 0);
      tma2d(sb + OFF_RES, &p.x, tn * 128, tm * 128, sb + BAR_X);
      mbar_wait(sb + BAR_OEMPTY + 4 * 8, 0);
      tma2d(sb + OFF_RES + RES_H, &p.x, tn * 128 + 64, tm * 128, sb + BAR_X);
      if (!paired) {
        mbar_wait(sb + BAR_OWN, 0);
        while (!(ld_relaxed(gs->cnt[16 + tm]) & 4u << (tn ^ 1) * 4)) __nanosleep(32);
        fence_acquire();
        fence_async_global();
        const uint32_t par = lds32(sb + OFF_MISC + 24);
        for (uint32_t ph = 0, bad = 1; bad & 1; ph ^= 1) {
          fence_async_smem();
          mbar_expect_tx(sb + BAR_FIX + 64, SLOT);
          bulk_load(sb + OFF_PK, gs->o[tm][8 + (tn ^ 1)], SLOT, sb + BAR_FIX + 64);
          mbar_wait(sb + BAR_FIX + 64, ph);
          bad = 0;
#pragma unroll 1
          for (int i = 0; i < 512; i++) bad |= lds32(sb + OFF_PK + i * 32 + (i & 28)) ^ par;
        }
        mbar_arrive(sb + BAR_PEER);
      }
      }
    } else {
#pragma unroll 1
      for (int i = 2; i < 8; i++)
        if (elect()) asm volatile("prefetch.tensormap [%0];" ::"l"(&p.x + i) : "memory");
      mbar_wait_bounded(sb + BAR_DONE, 0);
    }
  } else if (wg == 2) {
    asm volatile("setmaxnreg.dec.sync.aligned.u32 40;");
    const int mw = warp & 3;
    if (mw == 0) {
      const unsigned tag = (ld_relaxed(&gs->rslot[tn][cta]) + 1) & 0xFFF;
#pragma unroll
      for (int i = 0; i < 2; i++)
        if (lane < 28) ((float4*)gs)[cta * 56 + i * 28 + lane] = make_float4(0.f, 0.f, 0.f, 0.f);
      if (lane == 29) gs->block[cta] = blockIdx.x;
      fence_release();
      nb_sync(NB_KEY, 160);
      const uint4 k4 = lds128(sb + OFF_MISC);
      if (lane < 8) st_relaxed(&gs->rslot[lane][cta], max(max(k4.x, k4.y), max(k4.z, k4.w)) | tag);
      if (lane < 16) st_relaxed(&gs->gslot[cta * 16 + lane], lds32(sb + OFF_G + lane * 4) | tag);
      PROF(lane == 0, 20);
      uint4 r4;
      do {
        __nanosleep(RT_SLEEP);
        r4 = ld_relaxed4(&gs->rslot[tn][lane * 4]);
      } while (!__all_sync(~0u, (((r4.x ^ tag) | (r4.y ^ tag) | (r4.z ^ tag) | (r4.w ^ tag)) & 0xFFF) == 0));
      const int c0 = 0xFFF0 - lane * 64;
      unsigned key = max(max((r4.x & 0xFFFF0000u) | (c0 + ((r4.x >> 12) & 15)), (r4.y & 0xFFFF0000u) | (c0 - 16 + ((r4.y >> 12) & 15))),
                         max((r4.z & 0xFFFF0000u) | (c0 - 32 + ((r4.z >> 12) & 15)), (r4.w & 0xFFFF0000u) | (c0 - 48 + ((r4.w >> 12) & 15))));
      key = __reduce_max_sync(~0u, key);
      if (elect()) {
        sts32(sb + OFF_MISC + 16, key);
        sts32(sb + OFF_MISC + 24, tag & 1);
        if (mu < MOD_CTAS) {
          const __nv_bfloat16* row = px + (size_t)(0xFFFF - (key & 0xFFFF)) * D_;
          bulk_load(sb + OFF_XSEL, row, 1024, sb + BAR_MFULL + 16);
          bulk_load(sb + OFF_XSEL + MOD_STEP, row + 512, 1024, sb + BAR_MFULL + 16);
        }
      }
      PROF(lane == 0, 21);
      do {
        r4 = ld_relaxed4(&gs->gslot[tm * 128 + lane * 4]);
      } while (!__all_sync(~0u, (((r4.x ^ tag) | (r4.y ^ tag) | (r4.z ^ tag) | (r4.w ^ tag)) & 0xFFF) == 0));
      sts128(sb + OFF_G + lane * 16, r4.x & 0xFFFF0000u, r4.y & 0xFFFF0000u, r4.z & 0xFFFF0000u, r4.w & 0xFFFF0000u);
      fence_acquire();
      __syncwarp();
      mbar_arrive_warp(sb + BAR_IDX);
    }
    PROF(tid == 256, 22);
    if (mu >= MOD_CTAS) {
      mbar_arrive_warp(sb + BAR_IDX);
    } else {
      const uint32_t wp = sb + OFF_V + (mw >> 1) * 4096 + (mw & 1) * 512 + lane * 16;
      uint32_t mp = sb + OFF_XSEL + (mw & 1) * 64 + (lane >> 2) * 8, mc = 128;
      float acc[8] = {0.f, 0.f, 0.f, 0.f, 0.f, 0.f, 0.f, 0.f};
      uint32_t b = 2, ph = 0;
#pragma unroll 1
      for (int c = 0; c < 24; c++) {
        if (GO) mbar_wait(sb + BAR_RT + mw * 8, 0);
        if (MOD_SLEEP && c >= MOD_S0) __nanosleep(MOD_SLEEP);
        mbar_wait(sb + BAR_MFULL + b * 8, ph);
        PROF_C(tid == 256, 216 + c);
        const uint32_t a = wp + b * MOD_STEP;
        const uint2 m = lds64(mp);
        const uint4 w0 = lds128(a), w1 = lds128(a + 1024), w2 = lds128(a + 2048), w3 = lds128(a + 3072);
        mp += c == 7 ? MOD_STEP - 1024 + 128 : mc;
        const uint32_t m0 = dup_lo(m.x), m1 = dup_hi(m.x), m2 = dup_lo(m.y), m3 = dup_hi(m.y);
        uint4 q = make_uint4(mul_bf2(w0.x, m0), mul_bf2(w0.y, m0), mul_bf2(w0.z, m0), mul_bf2(w0.w, m0));
        q = make_uint4(fma_bf2(w1.x, m1, q.x), fma_bf2(w1.y, m1, q.y), fma_bf2(w1.z, m1, q.z), fma_bf2(w1.w, m1, q.w));
        q = make_uint4(fma_bf2(w2.x, m2, q.x), fma_bf2(w2.y, m2, q.y), fma_bf2(w2.z, m2, q.z), fma_bf2(w2.w, m2, q.w));
        mbar_arrive_warp(sb + BAR_MEMPTY + b * 8 + (w3.x & zero));
        q = make_uint4(fma_bf2(w3.x, m3, q.x), fma_bf2(w3.y, m3, q.y), fma_bf2(w3.z, m3, q.z), fma_bf2(w3.w, m3, q.w));
        if (++b == 5) b = c < 3 ? 0 : 2;
        if (b == 2) ph ^= 1;
        acc[0] += bf_lo(q.x); acc[1] += bf_hi(q.x); acc[2] += bf_lo(q.y); acc[3] += bf_hi(q.y);
        acc[4] += bf_lo(q.z); acc[5] += bf_hi(q.z); acc[6] += bf_lo(q.w); acc[7] += bf_hi(q.w);
        if (c == 15) {
          const uint32_t ft = fresh_tid(), fl = ft & 31;
          sts32(sb + OFF_PART + (ft & 96) * 4 + ((ft & 3) * 8 + (fl >> 2)) * 4, __float_as_uint(butterfly8(acc, fl, 4)));
          nb_sync(NB_MODW, 128);
          const float* part = (const float*)(smem + OFF_PART) + fl;
          const float gp = bf_round(part[0] + part[32]), up = bf_round(part[64] + part[96]);
          *(__nv_bfloat16*)(smem + OFF_PART + 512 + fl * 2) = __float2bfloat16_rn(bf_round(gp * sigmoidf_(gp)) * up);
          __syncwarp();
          mp = sb + OFF_PART + 512; mc = 8;
#pragma unroll
          for (int i = 0; i < 8; i++) acc[i] = 0.f;
          PROF(lane == 0 && mw == 0, 23);
        }
      }
      float4* yacc = gs->y[tn & 1][0] + (fresh_tid() & 127);
      red_add4(yacc, acc[0], acc[1], acc[2], 1.f);
      red_add4(yacc + 128, acc[3], acc[4], acc[5], 1.f);
      red_add4(yacc + 256, acc[6], acc[7], 0.f, 1.f);
      PROF(lane == 0 && mw == 0, 25);
    }
    mbar_wait(sb + BAR_GATE, 0);
    mbar_wait(sb + BAR_IDX, 0);
    verify_tiles<0>(sb, gs, tm, tn, mw, lane);
    const unsigned key = lds32(sb + OFF_MISC + 16);
    const int sel = 0xFFFF - (int)(key & 0xFFFF) - tm * 128;
    if (mw == 0 && sel >= 0 && sel < 128) {
      const unsigned k16 = key >> 16;
      const float rs = bf_round(sigmoidf_(__uint_as_float(((k16 & 0x8000u) ? (k16 & 0x7FFFu) : (~k16 & 0xFFFFu)) << 16)));
      float v[12];
      const float4* yp = gs->y[lane >> 4][0] + tn * 16 + (lane & 15);
      for (;;) {
#pragma unroll
        for (int i = 0; i < 3; i++) {
          const float4 u = ld_relaxed_f4(yp + i * 128);
          v[4 * i] = u.x; v[4 * i + 1] = u.y; v[4 * i + 2] = u.z; v[4 * i + 3] = u.w;
        }
        const float n = v[3] + v[7] + v[11];
        if (__all_sync(~0u, n + __shfl_xor_sync(~0u, n, 16) == 3.f * MOD_CTAS)) break;
        __nanosleep(Y_SLEEP);
      }
#pragma unroll
      for (int i = 0; i < 10; i++) v[i] = bf_round(bf_round(v[i] + __shfl_xor_sync(~0u, v[i], 16)) * rs);
      PROF(lane == 0, 24);
      mbar_wait(sb + BAR_X, 0);
      if (lane < 16) {
        uint4* xp = (uint4*)(smem + OFF_RES + (lane >> 3) * RES_H + sel * 128 + (((lane ^ sel) & 7) << 4));
        const uint4 xv = *xp;
        *xp = make_uint4(pack2(bf_lo(xv.x) + v[0], bf_hi(xv.x) + v[1]), pack2(bf_lo(xv.y) + v[2], bf_hi(xv.y) + v[4]),
                         pack2(bf_lo(xv.z) + v[5], bf_hi(xv.z) + v[6]), pack2(bf_lo(xv.w) + v[8], bf_hi(xv.w) + v[9]));
      }
      __syncwarp();
      mbar_arrive_warp(sb + BAR_Y);
    }
  } else {
    asm volatile("setmaxnreg.inc.sync.aligned.u32 224;");
    const int w = warp & 3, wt = tid & 127;
    const int nb_self = NB_WG0 + wg;
    const uint64_t da0 = mkdesc(sb + OFF_RING, 16, 1024, 1), db0 = mkdesc(sb + OFF_RING, 8192, 1024, 1);

    auto go = [&]() { mbar_arrive_warp(sb + BAR_RT + w * 8); };
    if (wg == 1) {
      sts128(sb + OFF_ONES - (w >> 1) * 9216 + (w & 1) * 512 + lane * 16, 0x3F803F80u, 0x3F803F80u, 0x3F803F80u, 0x3F803F80u);
      sts32(sb + OFF_MISC + 20, 0x3FB8AA3Bu);
      fence_async_smem();
      float s[8] = {0.f, 0.f, 0.f, 0.f, 0.f, 0.f, 0.f, 0.f};
      uint32_t mask = 0xffff0000u;
#pragma unroll 1
      for (int i = 0; i < 4; i++) {
        const uint32_t u = (i + RT_ROT) & 3;
        mbar_wait(sb + BAR_RT + i * 8, 0);
        const uint4 wr = lds128(sb + OFF_KVB + u * 512 + lane * 16), gw = lds128(sb + OFF_KVB + 2048 + u * 512 + lane * 16);
        uint4 xv[4];
#pragma unroll
        for (int r = 0; r < 4; r++) xv[r] = lds128(sb + OFF_PK + i * 8192 + (i == 3) * 1024 + (w * 4 + r) * 512 + lane * 16);
        const float wf[16] = {bf_lo(wr.x), bf_hi(wr.x), bf_lo(wr.y), bf_hi(wr.y), bf_lo(wr.z), bf_hi(wr.z), bf_lo(wr.w), bf_hi(wr.w),
                              bf_lo(gw.x), bf_hi(gw.x), bf_lo(gw.y), bf_hi(gw.y), bf_lo(gw.z), bf_hi(gw.z), bf_lo(gw.w), bf_hi(gw.w)};
#pragma unroll
        for (int r = 0; r < 4; r++) {
          const uint4 xq = xv[r];
          const float xf[8] = {bf_lo(xq.x), __uint_as_float(xq.x & mask), bf_lo(xq.y), bf_hi(xq.y), bf_lo(xq.z), bf_hi(xq.z), bf_lo(xq.w), bf_hi(xq.w)};
#pragma unroll
          for (int j = 0; j < 8; j++) { s[2 * r] = fmaf(xf[j ^ 1], wf[j ^ 1], s[2 * r]); s[2 * r + 1] = fmaf(xf[j ^ 1], wf[8 + (j ^ 1)], s[2 * r + 1]); }
          mask = ((__float_as_uint(s[2 * r]) | __float_as_uint(s[2 * r + 1])) & zero) | 0xffff0000u;
        }
      }
      mbar_arrive_warp(sb + BAR_RTD);
      float v = butterfly8(s, lane, 1);
      PROF_C(wt == 0 && v != 12345.f, 19);
      v += __shfl_xor_sync(~0u, v, 8);
      v = bf_round(v + __shfl_xor_sync(~0u, v, 16));
      const unsigned rb = __float_as_uint(v) >> 16, row = w * 4 + ((lane & 7) >> 1);
      unsigned key = (lane & 1) ? 0u : ((((rb & 0x8000u) ? (~rb & 0xFFFFu) : (rb | 0x8000u)) << 16) | ((15 - row) << 12));
      key = __reduce_max_sync(~0u, key);
      if (lane == 0) sts32(sb + OFF_MISC + w * 4, key);
      if (lane < 8 && (lane & 1)) sts32(sb + OFF_G + row * 4, __float_as_uint(bf_round(sigmoidf_(v))));
      nb_arrive(NB_KEY, 160);
      nb_sync(NB_ORDER_12, 256);
    }
    uint4* const kvacc = &gs->kv[wg][tn][0][wt];
    float aq[64];
    uint32_t su[9];
    {
      float ak[64], av[64], c[36];
      uint32_t pk[8][4];
      PROF_C(wt == 0, 1 + wg * 8);
#pragma unroll 1
      for (int g = 0; g < 16; g++) {
        const uint64_t dx = da0 + (g & 3) * (SLOT >> 4), dw = da0 + ((OFF_W1 >> 4) + (g & 3) * (WQKV_BYTES >> 4));
        mbar_wait(sb + BAR_FULL + (g & 7) * 8, g >> 3);
        if (g == 0) PROF_C(wt == 0, 2 + wg * 8);
        wg_fence();
#pragma unroll
        for (int kk = 0; kk < 4; kk++) mma128<1, 0>(ak, dw + (512 + kk * 128), dx + kk * 2, kk ? 1 : g);
        wg_commit();
        if (G1 == 1) {
          wg_wait<1>();
          if (g) mbar_arrive_warp(sb + BAR_EMPTY + (g - 1 & 7) * 8);
          wg_fence();
        }
#pragma unroll
        for (int kk = 0; kk < 4; kk++) mma128<1, 0>(av, dw + (1024 + kk * 128), dx + kk * 2, kk ? 1 : g);
        wg_commit();
        if (G1 == 2) {
          wg_wait<2>();
          if (g) mbar_arrive_warp(sb + BAR_EMPTY + (g - 1 & 7) * 8);
          wg_fence();
        }
#pragma unroll
        for (int kk = 0; kk < 4; kk++) mma128<1, 0>(aq, dw + kk * 128, dx + kk * 2, kk ? 1 : g);
        wg_commit();
      }
      if (wg == 0) nb_arrive(NB_ORDER_12, 256);
      if (wg == 1 && EARLY_O) nb_arrive(NB_ORDER_3O, 256);
      mbar_wait(sb + BAR_IDX, 0);
      if (wg == 1) nb_sync(NB_STG, 256);
      if (GO & (wg ? 8 : 1)) go();
      wg_wait<2>();
      pin(ak);
      PROF_C(wt == 0, 3 + wg * 8);
      const uint32_t va = sb + OFF_V + (w * 16 + (lane & 15)) * 128;
      uint32_t lk[8];
#pragma unroll
      for (int u = 0; u < 8; u++) {
        if (u < VK + KL || !KL) lk[u] = 0x3FB8AA3Bu;
#pragma unroll
        for (int i = 0; i < 4; i++) pk[u][i] = phi2(ak[8 * u + 2 * i], ak[8 * u + 2 * i + 1], __uint_as_float(lk[u]));
        if (u == VK) { wg_wait<1>(); pin(av); }
        if (u == MM) { wg_wait<0>(); mbar_arrive_warp(sb + BAR_EMPTY + 7 * 8); }
        const uint32_t z = mism(pk[u][0], pk[u][1], 0) | mism(pk[u][2], pk[u][3], 0);
#pragma unroll
        for (int t = u < VK ? 8 : (u - VK) * 8 / (8 - VK); t < (u - VK + 1) * 8 / (8 - VK); t++) {
          const float* v = &av[8 * t];
          stsm4(va + (t >> 2) * 9216 + ((((lane >> 4) + 2 * (t & 3)) ^ (lane & 7)) << 4) + (z & zero), pack2(v[0], v[1]), pack2(v[2], v[3]), pack2(v[4], v[5]), pack2(v[6], v[7]));
        }
        if (KL && u >= VK && u + KL < 8) lk[u + KL] = lds32(sb + OFF_MISC + 20);
      }
      fence_async_smem();
      nb_sync(nb_self, 128);
      PROF_C(wt == 0, 8 + wg * 8);
      const uint64_t dv = mkdesc(sb + OFF_V, 16, 1024, 1);
      wg_fence();
#pragma unroll
      for (int kk = 0; kk < 8; kk++) mma_ktv(c, pk[kk], dv + ((kk >> 2) * 576 + (kk & 3) * 2), kk ? 1 : 0);
      wg_commit();
      if (wg == 1 && !EARLY_O) nb_arrive(NB_ORDER_3O, 256);
      if (GO & (wg ? 8 : 1)) go();
      wg_wait<0>();
      if (GO & (wg ? 16 : 2)) go();
      pin(c); pin(aq);
      PROF_C(wt == 0, 4 + wg * 8);
#pragma unroll
      for (int i = 0; i < 8; i++) {
        const int j = (i & 3) * 4 + (i >> 2) * 2;
        su[i] = w >= 2 ? pack2(c[16 + j], c[17 + j]) : pack2(c[j], c[j + 1]);
      }
      su[8] = pack2(c[32], c[34]);
#pragma unroll
      for (int u = 0; u < 3; u++)
        if (u < R0 || wg) red_add_bf(kvacc + u * 128, su[3 * u], su[3 * u + 1], su[3 * u + 2]);
    }
    const uint32_t par = lds32(sb + OFF_MISC + 24);
    {
      const bool paired = PAIRED && ld_relaxed(&gs->block[cta ^ 1]) == (blockIdx.x ^ 1);
      uint4 kv[3];
      int tries = wg ? 0 : TRY_A;
      const uint8_t* gl = smem + OFF_MISC + 20;
      asm volatile("" : "+l"(gl));
      const uint32_t l2e = ld_generic(gl);
    auto stage_kv = [&]() {
      const uint32_t kb = sb + OFF_KVB + w * 256, ka = kb + (lane & 3) * KVB_N + (lane >> 2) * 16;
      sts128(ka, kv[0].x, kv[0].y, kv[0].z, kv[1].x);
      sts128(ka + 128, kv[1].y, kv[1].z, kv[2].x, kv[2].y);
      sts32(kb + 4 * KVB_N + lane * 4, dup_lo(kv[2].z));
      sts32(kb + 4 * KVB_N + 128 + lane * 4, dup_hi(kv[2].z));
      return __all_sync(~0u, (kv[0].w & kv[1].w & kv[2].w) == 0x41804180u && (kv[0].w | kv[1].w | kv[2].w) == 0x41804180u);
    };
      bool have = false;
      const uint32_t qa = sb + OFF_PK + ((lane >> 4) * 8 + (lane & 7)) * 128 + (((2 * w + ((lane >> 3) & 1)) ^ (lane & 7)) << 4);
      uint32_t lq[8];
#pragma unroll
      for (int u = 0; u < QA; u++) lq[u] = l2e;
#pragma unroll
      for (int u = 0; u < 8; u++) {
        uint32_t r[4];
        if (u == KF && wg) {
#pragma unroll
          for (int i = 0; i < 3; i++) kv[i] = ld_relaxed4(kvacc + i * 128);
        }
#pragma unroll
        for (int i = 0; i < 4; i++) r[i] = phi2(aq[8 * u + 2 * i], aq[8 * u + 2 * i + 1], __uint_as_float(lq[u]));
        stsm4t(qa + u * 2048, r[0], r[1], r[2], r[3]);
        if (u % RS == RS - 1 && u / RS + R0 < 3 && !wg) red_add_bf(kvacc + (u / RS + R0) * 128, su[3 * (u / RS + R0)], su[3 * (u / RS + R0) + 1], su[3 * (u / RS + R0) + 2]);
        if (u + QA < 8) lq[u + QA] = QD ? ld_generic(gl) : lds32(sb + OFF_MISC + 20);
        if (u == KU && wg) have = stage_kv();
      }
      PROF_C(wt == 0, 34 + wg * 2);
      if (GO & (wg ? 16 : 2)) go();
      if (NAP_A && !wg) __nanosleep(NAP_A);
      if (KU > 7 && KF < 8 && wg) have = stage_kv();
      for (; !have; tries++) {
        if (tries > RETRY)
          while (ld_relaxed((const unsigned*)&(kvacc - lane)[256 + 31].w) != 0x41804180u) __nanosleep(wg ? KV_SLEEP : KV_SLEEP_A);
#pragma unroll
        for (int i = 0; i < 3; i++) kv[i] = ld_relaxed4(kvacc + i * 128);
        have = stage_kv();
      }
      PROF_C(wt == 0, 5 + wg * 8);
      fence_async_smem();
      nb_sync(nb_self, 128);
      float o[2][2][20];
      const uint64_t dq = mkdesc(sb + OFF_PK, 16, 1024, 1), dz = mkdesc(sb + OFF_KVB, 128, KVB_N, 0);
      wg_fence();
#pragma unroll
      for (int m = 0; m < 2; m++) {
#pragma unroll
        for (int h = 0; h < 2; h++)
#pragma unroll
          for (int kk = 0; kk < 2; kk++) mma_qkvz(o[m][h], dq + (m * 512 + h * 4 + kk * 2), dz + (h * 32 + kk * 16), kk);
        wg_commit();
      }
      if (HOLD < 8 && HP == 0 && wg) nb_arrive(NB_HOLD, 256);
      uint32_t tag[2][4];
#pragma unroll
      for (int i = 0; i < 8; i++) tag[i >> 2][i & 3] = (lane >> 3) == (i & 3) && ((lane ^ (lane >> 3)) & 1) == (i >> 2);
      uint32_t gr[8];
      const uint8_t* ga = smem + OFF_G + (w * 16 + (lane >> 2)) * 4;
      asm volatile("" : "+l"(ga));
#pragma unroll
      for (int i = 0; i < OA; i++) gr[i] = ld_generic(ga + (i >> 2) * 256 + (i & 1) * 32);
      const uint32_t oo = w * 1024 + (lane >> 2) * 64 + (((lane ^ (lane >> 3)) & 3) << 4);
      uint8_t* const og = (uint8_t*)gs->o[tm][wg * 8 + tn] + oo;
      uint32_t ob[8][4];
#pragma unroll
      for (int m = 0; m < 2; m++) {
        if (m == 0) wg_wait<1>(); else wg_wait<0>();
        pin(o[m][0]); pin(o[m][1]);
        if (m && !wg) nb_arrive(NB_STG, 256);
        if (HOLD < 8 && HP == 1 && m && wg) nb_arrive(NB_HOLD, 256);
        if (m && wg && paired && elect()) mbar_arrive_peer(peer_addr(sb + BAR_PA));
        if (m == 0 && GO & (wg ? 32 : 4)) go();
        if (m == 0) PROF_C(wt == 0, 6 + wg * 8);
#pragma unroll
        for (int u = 0; u < 4; u++) {
          const int h = u >> 1, i = u & 1;
          const float* on = o[m][h];
          const float sc = __uint_as_float(gr[m * 4 + u]) * rcp(on[16 + 2 * i] + 1e-6f);
          const uint32_t sc2 = pack2(sc, sc);
#pragma unroll
          for (int j = 0; j < 4; j++) {
            const uint32_t v = HS ? mul_bf2(pack2(on[4 * j + 2 * i], on[4 * j + 2 * i + 1]), sc2) : pack2(on[4 * j + 2 * i] * sc, on[4 * j + 2 * i + 1] * sc);
            asm("lop3.b32 %0, %1, %2, %3, 0xB8;" : "=r"(ob[m * 4 + u][j]) : "r"(v), "r"(tag[i][j]), "r"(par));
          }
          st_relaxed4(og + (h * 8192 + m * 4096 + i * 512), ob[m * 4 + u]);
          if (OWN1 == 2 && wg) sts128(sb + OFF_V + oo + (h * 8192 + m * 4096 + i * 512), ob[m * 4 + u][0], ob[m * 4 + u][1], ob[m * 4 + u][2], ob[m * 4 + u][3]);
          const int n = m * 4 + u + OA;
          if (n < 8) gr[n] = ld_generic(ga + (n >> 2) * 256 + (n & 1) * 32);
        }
      }
      if (elect()) red_add(gs->cnt[wg * 16 + tm], 1u << tn * 4);
      mbar_arrive_warp(sb + BAR_PUB + wg * 8);
      if (HOLD < 8 && HP == 2 && wg) nb_arrive(NB_HOLD, 256);
      if (GO & (wg ? 32 : 4)) go();
      PROF(wt == 0, 17 + wg);
      if (wg) {
        auto to_peer = [&]() {
        if (paired) {
          const uint32_t pb = peer_addr(sb);
          mbar_wait(sb + BAR_PA, 0);
#pragma unroll
          for (int u = 0; u < 8; u++) st_async4(pb + OFF_PK + oo + ((u >> 1 & 1) * 8192 + (u >> 2) * 4096 + (u & 1) * 512), ob[u], pb + BAR_PEER);
        }
        };
        if (!OWN1) to_peer();
#pragma unroll
        for (int u = 0, z = 0; u < (OWN1 == 2 ? 0 : 8); u++) {
          sts128(sb + OFF_V + oo + ((u >> 1 & 1) * 8192 + (u >> 2) * 4096 + (u & 1) * 512) + z, ob[u][0], ob[u][1], ob[u][2], ob[u][3]);
          if (PO && u % PO == PO - 1 && u < 7) z = lds32(sb + OFF_ONES) & 16;
        }
        fence_async_smem();
        __syncwarp();
        mbar_arrive_warp(sb + BAR_OWN);
        if (HOLD < 8 && HP == 3) nb_arrive(NB_HOLD, 256);
        PROF(wt == 0, 15);
        if (OWN1) to_peer();
      }
    }
    if (wg == 1) {
      verify_tiles<1>(sb, gs, tm, tn, w, lane);
    } else {
      float acc[2][64];
      nb_sync(NB_ORDER_3O, 256);
      PROF_C(wt == 0, 26);
      uint32_t xr[2][8][4], q[2][2];
      const uint32_t ta = sb + OFF_RES + (uint32_t)(w * 16 + (lane & 15)) * 128;
      const uint64_t do0 = mkdesc(sb + OFF_RING, 16, 512, 2);
      uint64_t xs = OA_SLOTS, ws = OW_SLOTS;
#pragma unroll 1
      for (int g = 0; g < 13 - TL; g++, xs >>= 4, ws >>= 4) {
        const uint32_t r = g * 52 >> 8, s = g - r * 5;
        const uint64_t da = do0 + ((uint32_t)xs & 15) * (SLOT >> 4), db = db0 + ((uint32_t)ws & 15) * (SLOT >> 4);
        if (g == OWN) mbar_wait(sb + BAR_OWN, 0);
        if (g == PEER) { mbar_wait(sb + BAR_PEER, 0); fence_async_smem(); }
        if (g == HOLD) nb_sync(NB_HOLD, 256);
        mbar_wait(sb + BAR_OFULL + s * 8, r & 1);
        wg_fence();
#pragma unroll
        for (int kk = 0; kk < 4; kk++)
#pragma unroll
          for (int m = 0; m < 2; m++) mma128<0, 1>(acc[m], da + (m * 256 + (kk >> 1) * 512 + (kk & 1) * 2), db + kk * 128, kk ? 1 : g);
        wg_commit();
        wg_wait<1>();
        if (g) mbar_arrive_warp(sb + BAR_OEMPTY + (s ? s - 1 : 4) * 8);
      }
      mbar_wait(sb + BAR_X, 0);
      const int selw = ((0xFFFF - (int)(lds32(sb + OFF_MISC + 16) & 0xFFFF)) >> 4) - tm * 8 - w;
#pragma unroll
      for (int u = 0; u < 4; u++) {
        const int m = u >> 1, g = 13 - TL + u;
        const float g1 = 1.f - __uint_as_float(lds32(sb + OFF_G + (m * 64 + w * 16 + (u & 1) * 8 + (lane >> 2)) * 4));
        q[m][u & 1] = pack2(g1, g1);
#pragma unroll
        for (int j = 0; j < 4; j++) ldsm4(ta + (u & 1) * RES_H + m * 8192 + ((((lane >> 4) + 2 * j) ^ (lane & 7)) << 4), xr[m][(u & 1) * 4 + j]);
        if (u == 3) break;
        mbar_wait(sb + BAR_OFULL + g % 5 * 8, g / 5 & 1);
        wg_fence();
#pragma unroll
        for (int kk = 0; kk < 4; kk++)
#pragma unroll
          for (int mm = 0; mm < 2; mm++)
            mma128<0, 1>(acc[mm], do0 + ((OA_SLOTS >> g * 4 & 15) * (SLOT >> 4) + mm * 256 + (kk >> 1) * 512 + (kk & 1) * 2), db0 + ((OW_SLOTS >> g * 4 & 15) * (SLOT >> 4) + kk * 128), 1);
        wg_commit();
        wg_wait<1>();
        if (g <= 11) mbar_arrive_warp(sb + BAR_OEMPTY + (g + 4) % 5 * 8);
      }
#pragma unroll
      for (int m = 0; m < 2; m++) {
#pragma unroll
        for (int g = 16 - TL; g < 16; g++) {
          if (m == 0) { mbar_wait(sb + BAR_OFULL + g % 5 * 8, g / 5 & 1); wg_fence(); }
#pragma unroll
          for (int kk = 0; kk < 4; kk++)
            mma128<0, 1>(acc[m], do0 + ((OA_SLOTS >> g * 4 & 15) * (SLOT >> 4) + m * 256 + (kk >> 1) * 512 + (kk & 1) * 2), db0 + ((OW_SLOTS >> g * 4 & 15) * (SLOT >> 4) + kk * 128), 1);
        }
        wg_commit();
      }
      mbar_arrive_warp(sb + BAR_DONE);
#pragma unroll
      for (int m = 0; m < 2; m++) {
        if (selw == 4 * m) {
          mbar_wait(sb + BAR_Y, 0);
#pragma unroll
          for (int j = 0; j < 8; j++) ldsm4(ta + (j >> 2) * RES_H + m * 8192 + ((((lane >> 4) + 2 * (j & 3)) ^ (lane & 7)) << 4), xr[m][j]);
        }
        if (m == 0) wg_wait<1>(); else wg_wait<0>();
        if (m) PROF(wt == 0, 31);
#pragma unroll
        for (int h = 0; h < 2; h++) {
#pragma unroll
          for (int j = 4 * h; j < 4 * h + 4; j++) {
            const float* v = &acc[m][8 * j];
            stsm4(ta + h * RES_H + m * 8192 + ((((lane >> 4) + 2 * (j & 3)) ^ (lane & 7)) << 4),
                  fma_bf2(xr[m][j][0], q[m][0], pack2(v[0], v[1])), fma_bf2(xr[m][j][1], q[m][1], pack2(v[2], v[3])),
                  fma_bf2(xr[m][j][2], q[m][0], pack2(v[4], v[5])), fma_bf2(xr[m][j][3], q[m][1], pack2(v[6], v[7])));
          }
          fence_async_smem();
          __syncwarp();
          if (elect()) tma2d_store(&p.out, sb + OFF_RES + h * RES_H + m * 8192 + w * 2048, tn * 128 + h * 64, tm * 128 + m * 64 + w * 16);
          if (m && h && elect()) { bulk_commit(); asm volatile("cp.async.bulk.wait_group.read 0;" ::: "memory"); }
        }
        if (!m) PROF(wt == 0, 33);
      }
      PROF(wt == 0, 32);
    }
  }
}

typedef CUresult (*EncodeFn)(CUtensorMap*, CUtensorMapDataType, cuuint32_t, void*, const cuuint64_t*, const cuuint64_t*, const cuuint32_t*,
                             const cuuint32_t*, CUtensorMapInterleave, CUtensorMapSwizzle, CUtensorMapL2promotion, CUtensorMapFloatOOBfill);

void encode(EncodeFn fn, CUtensorMap* m, const void* ptr, int rank, const cuuint64_t* dims, const cuuint64_t* strides, const cuuint32_t* box,
            CUtensorMapSwizzle sw, CUtensorMapDataType dt = CU_TENSOR_MAP_DATA_TYPE_BFLOAT16) {
  const cuuint32_t es[3] = {1, 1, 1};
  fn(m, dt, rank, const_cast<void*>(ptr), dims, strides, box, es, CU_TENSOR_MAP_INTERLEAVE_NONE, sw,
     CU_TENSOR_MAP_L2_PROMOTION_L2_128B, CU_TENSOR_MAP_FLOAT_OOB_FILL_NONE);
}

}

extern "C" void kernel_launch(void* const* d_in, const int* in_sizes, int n_in, void* d_out, int out_size) {
  (void)in_sizes; (void)n_in; (void)out_size;
  EncodeFn fn = nullptr;
  cudaDriverEntryPointQueryResult qr;
  cudaGetDriverEntryPoint("cuTensorMapEncodeTiled", (void**)&fn, cudaEnableDefault, &qr);

  Params p;
  {
    const cuuint64_t dims[2] = {D_, S_}, str[1] = {D_ * 2};
    const cuuint32_t box[2] = {64, 128}, box_st[2] = {64, 16}, box_r[2] = {256, 16};
    encode(fn, &p.xr, d_in[0], 2, dims, str, box_r, CU_TENSOR_MAP_SWIZZLE_NONE);
    encode(fn, &p.x, d_in[0], 2, dims, str, box, CU_TENSOR_MAP_SWIZZLE_128B);
    encode(fn, &p.out, d_out, 2, dims, str, box_st, CU_TENSOR_MAP_SWIZZLE_128B);
  }
  {
    const cuuint64_t dims[3] = {D_, D_, 3}, str[2] = {3 * D_ * 2, D_ * 2};
    const cuuint32_t box[3] = {64, 64, 3};
    encode(fn, &p.w, d_in[1], 3, dims, str, box, CU_TENSOR_MAP_SWIZZLE_128B);
  }
  {
    const cuuint64_t dims[3] = {64, D_, D_ / 64}, str[2] = {D_ * 2, 128};
    const cuuint32_t box[3] = {64, 64, 2};
    encode(fn, &p.wo, d_in[2], 3, dims, str, box, CU_TENSOR_MAP_SWIZZLE_128B);
  }
  {
    const cuuint64_t dims[3] = {F_, D_ / 4, 4}, str[2] = {F_ * 8, F_ * 2};
    const cuuint32_t box[3] = {32, 16, 4};
    encode(fn, &p.gate, d_in[5], 3, dims, str, box, CU_TENSOR_MAP_SWIZZLE_NONE);
    encode(fn, &p.up, d_in[6], 3, dims, str, box, CU_TENSOR_MAP_SWIZZLE_NONE);
  }
  {
    const cuuint64_t dims[3] = {D_ / 4, F_, 2}, str[2] = {D_ * 2, D_};
    const cuuint32_t box[3] = {256, 4, 2};
    encode(fn, &p.down, d_in[7], 3, dims, str, box, CU_TENSOR_MAP_SWIZZLE_NONE, CU_TENSOR_MAP_DATA_TYPE_UINT32);
  }
  void* gs = nullptr;
  cudaGetSymbolAddress(&gs, g_scratch);
  typedef const __nv_bfloat16* bp;
  int dev = 0, sms = 0;
  cudaGetDevice(&dev);
  cudaDeviceGetAttribute(&sms, cudaDevAttrMultiProcessorCount, dev);
  const bool by_sm = BYSM && sms == NGRID;
  const auto kernel = by_sm ? fused_kernel<true> : fused_kernel<false>;
  cudaFuncSetAttribute(kernel, cudaFuncAttributeMaxDynamicSharedMemorySize, SMEM_BYTES);
  kernel<<<by_sm ? NGRID : NCTA, NTHREADS, SMEM_BYTES, cudaStreamPerThread>>>((bp)d_in[0], (Scratch*)gs, (bp)d_in[5], (bp)d_in[6], (bp)d_in[4], (bp)d_in[8], (bp)d_in[7], p);
}
```

```cpp
#include <cuda_runtime.h>
#include <cuda.h>
#include <cuda_bf16.h>
#include <stdint.h>
#include <stddef.h>
#include <type_traits>

namespace {

constexpr int S_ = 2048, D_ = 1024, F_ = 3584;
constexpr int NCTA = 128, NGRID = 132, NTHREADS = 512;
#define NOMOD 0
constexpr int MOD_CTAS = NOMOD ? 0 : F_ / 32;

#define PRE 2
#define ST1 700
#define RT_G0 2
#define RT_ROT 1
#define RT_SLEEP 500
#define PF_MOD 7
#define MOD_START 9
#define MM 3
#define PO 2
#define A_SLEEP 128
#define KU 99
#define HS 1
#define HOLD 5
#define OWN1 0
#define KF 5
#define QA 3
#define R0 1
#define OA 3
#define QD 0
#define MOD_SLEEP 0
#define MOD_S0 8
#define Y_SLEEP 200
#define PD 0
#define TRY_A 9
#define NAP_A 0
#define VK 1
#define G1 1
#define HP 2
#define FS 2
#define QE 0
#define KL 3
#define RS 2
#define EARLY_O 0
#define RETRY 1
#define KV_SLEEP_A 64
#define KV_SLEEP 50
#define TL 3
#define PAIRED 1
#define BYSM 1

constexpr uint32_t SLOT = 16384, WQKV_BYTES = 24576;
constexpr int MOD_BUFS = 3, MOD_BUFS0 = MOD_BUFS + 2;
static_assert(MOD_START + MOD_BUFS0 <= 16, "first FFN round is requested during W1");
constexpr uint32_t OFF_RING = 0, OFF_W1 = 4 * SLOT;
constexpr uint64_t OA_SLOTS = 0x0AB210AB21098210ull, OW_SLOTS = 0x4376543765437654ull;
constexpr uint32_t OFF_RES = OFF_RING + 8 * SLOT, RES_H = SLOT;
constexpr uint32_t OFF_PK = 10 * SLOT;
constexpr uint32_t OFF_V = 11 * SLOT;
constexpr uint32_t OFF_ONES = OFF_V + 9216 + 8192;
constexpr uint32_t MOD_STEP = 9216, OFF_MOD = OFF_V + 2 * MOD_STEP;
constexpr uint32_t OFF_XSEL = OFF_MOD + 8192;
constexpr uint32_t OFF_KVB = OFF_MOD + 2 * MOD_STEP + 8192;
constexpr uint32_t KVB_N = 1056;
constexpr uint32_t OFF_G = OFF_KVB + 4 * KVB_N + 1024;
constexpr uint32_t OFF_PART = OFF_G + 512;
constexpr uint32_t OFF_MISC = OFF_PART + 576;
constexpr uint32_t OFF_BAR = OFF_MISC + 32;
constexpr uint32_t SMEM_BYTES = OFF_BAR + 480;
constexpr uint32_t BAR_FULL = OFF_BAR, BAR_Y = BAR_FULL + 64, BAR_X = BAR_Y + 8, BAR_PEER = BAR_X + 8, BAR_GATE = BAR_PEER + 8, BAR_RT = BAR_GATE + 8,
                   BAR_FIX = BAR_RT,
                   BAR_MFULL = BAR_FIX + 64, BAR_LAND = BAR_FULL,
                   BAR_EMPTY = OFF_BAR + 28 * 8, BAR_OEMPTY = BAR_EMPTY + 64, BAR_RTD = BAR_OEMPTY + 40, BAR_DONE = BAR_RTD + 8,
                   BAR_OWN = BAR_DONE + 8, BAR_PA = BAR_OWN + 8, BAR_PUB = BAR_PA + 8, BAR_MEMPTY = BAR_PUB + 16,
                   BAR_IDX = BAR_MEMPTY + 8,
                   BAR_OFULL = OFF_BAR + 52 * 8;
static_assert(BAR_MFULL + MOD_BUFS0 * 8 <= BAR_EMPTY && BAR_MEMPTY + MOD_BUFS0 * 8 == BAR_OFULL, "barrier groups");
static_assert(SMEM_BYTES <= 232448, "smem");
static_assert(TL == 3 && PRE == 2, "schedule");

constexpr int NB_WG0 = 1, NB_ORDER_12 = 3, NB_ORDER_3O = 4, NB_STG = 5, NB_MODW = 6, NB_KEY = 7, NB_HOLD = 8;

struct Scratch {
  uint4 kv[2][8][3][128];
  float4 y[2][3][128];
  unsigned cnt[32][32];
  unsigned gslot[S_];
  unsigned rslot[8][NCTA];
  unsigned spare[128];
  unsigned block[NCTA];
  uint4 o[16][16][1024];
};
static_assert(offsetof(Scratch, gslot) == NCTA * 56 * 16, "clear size");
__device__ __align__(1024) Scratch g_scratch;

#define PROF(cond, i) do {} while (0)
#define PROF_C(cond, i) do {} while (0)

__device__ __forceinline__ void mbar_init(uint32_t bar, int cnt) { asm volatile("mbarrier.init.shared::cta.b64 [%0], %1;" ::"r"(bar), "r"(cnt)); }
__device__ __forceinline__ void mbar_expect_tx(uint32_t bar, uint32_t bytes) { asm volatile("mbarrier.arrive.expect_tx.shared::cta.b64 _, [%0], %1;" ::"r"(bar), "r"(bytes) : "memory"); }
__device__ __forceinline__ void mbar_arrive(uint32_t bar) { asm volatile("mbarrier.arrive.shared::cta.b64 _, [%0];" ::"r"(bar) : "memory"); }
__device__ __forceinline__ uint32_t peer_addr(uint32_t a) {
  uint32_t r;
  asm volatile("{\n.reg .u32 c;\nmov.u32 c, %%cluster_ctarank;\nxor.b32 c, c, 1;\nmapa.shared::cluster.u32 %0, %1, c;\n}" : "=r"(r) : "r"(a));
  return r;
}
__device__ __forceinline__ void mbar_arrive_peer(uint32_t bar) { asm volatile("mbarrier.arrive.shared::cluster.b64 _, [%0];" ::"r"(bar) : "memory"); }
__device__ __forceinline__ uint32_t mism(uint32_t a, uint32_t b, uint32_t p) {
  uint32_t r; asm("lop3.b32 %0, %1, %2, %3, 0x7E;" : "=r"(r) : "r"(a), "r"(b), "r"(p)); return r;
}
__device__ __forceinline__ bool elect() {
  uint32_t r;
  asm volatile("{\n.reg .pred p;\nelect.sync _|p, 0xffffffff;\nselp.u32 %0, 1, 0, p;\n}" : "=r"(r));
  return r;
}
__device__ __forceinline__ uint32_t fresh_tid() { uint32_t r; asm volatile("mov.u32 %0, %%tid.x;" : "=r"(r)); return r; }
__device__ __forceinline__ void mbar_arrive_warp(uint32_t bar) {
  asm volatile("{\n.reg .pred p;\nelect.sync _|p, 0xffffffff;\n@p mbarrier.arrive.shared::cta.b64 _, [%0];\n}" ::"r"(bar) : "memory");
}
__device__ __forceinline__ void mbar_wait(uint32_t bar, uint32_t parity) {
  asm volatile("{\n.reg .pred p;\nWAIT_L:\nmbarrier.try_wait.parity.shared::cta.b64 p, [%0], %1;\n@p bra DONE_L;\nbra WAIT_L;\nDONE_L:\n}"
               ::"r"(bar), "r"(parity) : "memory");
}
__device__ __forceinline__ uint32_t mbar_try(uint32_t bar, uint32_t parity) {
  uint32_t ok;
  asm volatile("{\n.reg .pred p;\nmbarrier.try_wait.parity.shared::cta.b64 p, [%1], %2;\nselp.u32 %0, 1, 0, p;\n}" : "=r"(ok) : "r"(bar), "r"(parity) : "memory");
  return ok;
}
__device__ __forceinline__ uint32_t mbar_test(uint32_t bar, uint32_t parity) {
  uint32_t ok;
  asm volatile("{\n.reg .pred p;\nmbarrier.test_wait.parity.shared::cta.b64 p, [%1], %2;\nselp.u32 %0, 1, 0, p;\n}" : "=r"(ok) : "r"(bar), "r"(parity) : "memory");
  return ok;
}
constexpr unsigned long long WATCHDOG_NS = 2000000000ull;
__device__ __forceinline__ unsigned long long gtime() { unsigned long long t; asm volatile("mov.u64 %0, %%globaltimer;" : "=l"(t)); return t; }
__device__ __forceinline__ uint32_t clock32() { uint32_t t; asm volatile("mov.u32 %0, %%clock;" : "=r"(t)); return t; }
__device__ __forceinline__ void mbar_wait_bounded(uint32_t bar, uint32_t parity) {
  unsigned long long t0 = 0;
  for (;;) {
    uint32_t ok;
    asm volatile("{\n.reg .pred p;\nmbarrier.try_wait.parity.shared::cta.b64 p, [%1], %2;\nselp.u32 %0, 1, 0, p;\n}" : "=r"(ok) : "r"(bar), "r"(parity) : "memory");
    if (ok) break;
    const unsigned long long t1 = gtime();
    if (t0 == 0) t0 = t1;
    if (t1 - t0 > WATCHDOG_NS) __trap();
  }
}
__device__ __forceinline__ void tma2d(uint32_t dst, const CUtensorMap* m, int c0, int c1, uint32_t bar) {
  asm volatile("cp.async.bulk.tensor.2d.shared::cluster.global.mbarrier::complete_tx::bytes [%0], [%1, {%3, %4}], [%2];"
               ::"r"(dst), "l"(m), "r"(bar), "r"(c0), "r"(c1) : "memory");
}
__device__ __forceinline__ void tma3d(uint32_t dst, const CUtensorMap* m, int c0, int c1, int c2, uint32_t bar) {
  asm volatile("cp.async.bulk.tensor.3d.shared::cluster.global.mbarrier::complete_tx::bytes [%0], [%1, {%3, %4, %5}], [%2];"
               ::"r"(dst), "l"(m), "r"(bar), "r"(c0), "r"(c1), "r"(c2) : "memory");
}
__device__ __forceinline__ void bulk_load(uint32_t dst, const void* src, uint32_t bytes, uint32_t bar) {
  asm volatile("cp.async.bulk.shared::cluster.global.mbarrier::complete_tx::bytes [%0], [%1], %2, [%3];" ::"r"(dst), "l"(src), "r"(bytes), "r"(bar) : "memory");
}
__device__ __forceinline__ void bulk_store(void* dst, uint32_t src, uint32_t bytes) {
  asm volatile("cp.async.bulk.global.shared::cta.bulk_group [%0], [%1], %2;" ::"l"(dst), "r"(src), "r"(bytes) : "memory");
}
__device__ __forceinline__ void st_async4(uint32_t dst, const uint32_t (&v)[4], uint32_t bar) {
  asm volatile("st.async.shared::cluster.mbarrier::complete_tx::bytes.v4.b32 [%0], {%1, %2, %3, %4}, [%5];" ::"r"(dst), "r"(v[0]), "r"(v[1]), "r"(v[2]), "r"(v[3]), "r"(bar) : "memory");
}
__device__ __forceinline__ void bulk_commit() { asm volatile("cp.async.bulk.commit_group;" ::: "memory"); }
__device__ __forceinline__ void bulk_prefetch(const void* p, uint32_t bytes) {
  asm volatile("cp.async.bulk.prefetch.L2.global [%0], %1;" ::"l"(p), "r"(bytes) : "memory");
}
__device__ __forceinline__ void tma2d_store(const CUtensorMap* m, uint32_t src, int c0, int c1) {
  asm volatile("cp.async.bulk.tensor.2d.global.shared::cta.bulk_group [%0, {%2, %3}], [%1];" ::"l"(m), "r"(src), "r"(c0), "r"(c1) : "memory");
}
__device__ __forceinline__ void wg_fence() { asm volatile("wgmma.fence.sync.aligned;" ::: "memory"); }
__device__ __forceinline__ void wg_commit() { asm volatile("wgmma.commit_group.sync.aligned;" ::: "memory"); }
template <int N> __device__ __forceinline__ void wg_wait() { asm volatile("wgmma.wait_group.sync.aligned %0;" ::"n"(N) : "memory"); }
__device__ __forceinline__ void fence_async_smem() { asm volatile("fence.proxy.async.shared::cta;" ::: "memory"); }
__device__ __forceinline__ void fence_async_global() { asm volatile("fence.proxy.async.global;" ::: "memory"); }
__device__ __forceinline__ void fence_release() { asm volatile("fence.release.gpu;" ::: "memory"); }
__device__ __forceinline__ void fence_acquire() { asm volatile("fence.acquire.gpu;" ::: "memory"); }
__device__ __forceinline__ void nb_sync(int id, int n) { asm volatile("bar.sync %0, %1;" ::"r"(id), "r"(n) : "memory"); }
__device__ __forceinline__ void nb_arrive(int id, int n) { asm volatile("bar.arrive %0, %1;" ::"r"(id), "r"(n) : "memory"); }
__device__ __forceinline__ void stsm4(uint32_t addr, uint32_t r0, uint32_t r1, uint32_t r2, uint32_t r3) {
  asm volatile("stmatrix.sync.aligned.m8n8.x4.shared.b16 [%0], {%1, %2, %3, %4};" ::"r"(addr), "r"(r0), "r"(r1), "r"(r2), "r"(r3) : "memory");
}
__device__ __forceinline__ void stsm4t(uint32_t addr, uint32_t r0, uint32_t r1, uint32_t r2, uint32_t r3) {
  asm volatile("stmatrix.sync.aligned.m8n8.x4.trans.shared.b16 [%0], {%1, %2, %3, %4};" ::"r"(addr), "r"(r0), "r"(r1), "r"(r2), "r"(r3) : "memory");
}
__device__ __forceinline__ void st_relaxed4(void* p, const uint32_t (&v)[4]) {
  asm volatile("st.relaxed.gpu.global.v4.u32 [%0], {%1, %2, %3, %4};" ::"l"(p), "r"(v[0]), "r"(v[1]), "r"(v[2]), "r"(v[3]) : "memory");
}
__device__ __forceinline__ void sts128(uint32_t addr, uint32_t a, uint32_t b, uint32_t c, uint32_t d) {
  asm volatile("st.shared.v4.b32 [%0], {%1, %2, %3, %4};" ::"r"(addr), "r"(a), "r"(b), "r"(c), "r"(d) : "memory");
}
__device__ __forceinline__ uint32_t pack2(float lo, float hi) {
  uint32_t r; asm("cvt.rn.bf16x2.f32 %0, %1, %2;" : "=r"(r) : "f"(hi), "f"(lo)); return r;
}
__device__ __forceinline__ float bf_lo(uint32_t v) { return __uint_as_float(v << 16); }
__device__ __forceinline__ float bf_hi(uint32_t v) { return __uint_as_float(v & 0xffff0000u); }
__device__ __forceinline__ float bf_round(float v) { return __bfloat162float(__float2bfloat16_rn(v)); }
__device__ __forceinline__ void ldsm4(uint32_t addr, uint32_t (&r)[4]) {
  asm volatile("ldmatrix.sync.aligned.m8n8.x4.shared.b16 {%0, %1, %2, %3}, [%4];" : "=r"(r[0]), "=r"(r[1]), "=r"(r[2]), "=r"(r[3]) : "r"(addr) : "memory");
}
__device__ __forceinline__ uint4 lds128(uint32_t addr) {
  uint4 v; asm volatile("ld.volatile.shared.v4.u32 {%0, %1, %2, %3}, [%4];" : "=r"(v.x), "=r"(v.y), "=r"(v.z), "=r"(v.w) : "r"(addr) : "memory"); return v;
}
__device__ __forceinline__ uint2 lds64(uint32_t addr) { uint2 v; asm volatile("ld.volatile.shared.v2.u32 {%0, %1}, [%2];" : "=r"(v.x), "=r"(v.y) : "r"(addr) : "memory"); return v; }
__device__ __forceinline__ uint32_t lds32(uint32_t addr) { uint32_t v; asm volatile("ld.volatile.shared.u32 %0, [%1];" : "=r"(v) : "r"(addr) : "memory"); return v; }
__device__ __forceinline__ uint32_t ld_generic(const void* p) { uint32_t v; asm volatile("ld.volatile.u32 %0, [%1];" : "=r"(v) : "l"(p) : "memory"); return v; }
__device__ __forceinline__ void sts32(uint32_t addr, uint32_t v) { asm volatile("st.shared.u32 [%0], %1;" ::"r"(addr), "r"(v) : "memory"); }
__device__ __forceinline__ uint32_t fma_bf2(uint32_t a, uint32_t b, uint32_t c) { uint32_t r; asm("fma.rn.bf16x2 %0, %1, %2, %3;" : "=r"(r) : "r"(a), "r"(b), "r"(c)); return r; }
__device__ __forceinline__ uint32_t mul_bf2(uint32_t a, uint32_t b) { uint32_t r; asm("mul.rn.bf16x2 %0, %1, %2;" : "=r"(r) : "r"(a), "r"(b)); return r; }
__device__ __forceinline__ unsigned ld_relaxed(const unsigned* p) { unsigned v; asm volatile("ld.relaxed.gpu.global.u32 %0, [%1];" : "=r"(v) : "l"(p) : "memory"); return v; }
__device__ __forceinline__ void st_relaxed(unsigned* p, unsigned v) { asm volatile("st.relaxed.gpu.global.u32 [%0], %1;" ::"l"(p), "r"(v) : "memory"); }
__device__ __forceinline__ uint4 ld_relaxed4(const void* p) {
  uint4 v; asm volatile("ld.relaxed.gpu.global.v4.u32 {%0, %1, %2, %3}, [%4];" : "=r"(v.x), "=r"(v.y), "=r"(v.z), "=r"(v.w) : "l"(p) : "memory"); return v;
}
__device__ __forceinline__ float4 ld_relaxed_f4(const void* p) {
  float4 v; asm volatile("ld.relaxed.gpu.global.v4.f32 {%0, %1, %2, %3}, [%4];" : "=f"(v.x), "=f"(v.y), "=f"(v.z), "=f"(v.w) : "l"(p) : "memory"); return v;
}
__device__ __forceinline__ void red_add4(void* p, float a, float b, float c, float d) {
  asm volatile("red.relaxed.gpu.global.add.v4.f32 [%0], {%1, %2, %3, %4};" ::"l"(p), "f"(a), "f"(b), "f"(c), "f"(d) : "memory");
}
__device__ __forceinline__ void red_add_bf(void* p, uint32_t a, uint32_t b, uint32_t c) {
  asm volatile("red.relaxed.gpu.global.add.noftz.v4.bf16x2 [%0], {%1, %2, %3, %4};" ::"l"(p), "r"(a), "r"(b), "r"(c), "r"(0x3F803F80u) : "memory");
}
__device__ __forceinline__ void red_add(unsigned* p, unsigned v) { asm volatile("red.relaxed.gpu.global.add.u32 [%0], %1;" ::"l"(p), "r"(v) : "memory"); }
__device__ __forceinline__ float rcp(float v) { float r; asm("rcp.approx.ftz.f32 %0, %1;" : "=f"(r) : "f"(v)); return r; }
__device__ __forceinline__ float sigmoidf_(float v) { return rcp(1.f + __expf(-v)); }
__device__ __forceinline__ uint32_t phi2(float a, float b, float l2e = 1.4426950408889634f) {
  float ea, eb;
  asm("ex2.approx.ftz.f32 %0, %1;" : "=f"(ea) : "f"(a * l2e));
  asm("ex2.approx.ftz.f32 %0, %1;" : "=f"(eb) : "f"(b * l2e));
  uint32_t t = pack2(a, b), e = pack2(ea, eb), r;
  asm("max.NaN.bf16x2 %0, %0, %1;" : "+r"(t) : "r"(0x35863586u));
  asm("min.bf16x2 %0, %0, %1;" : "+r"(e) : "r"(0x3F803F80u));
  asm("add.rn.bf16x2 %0, %1, %2;" : "=r"(r) : "r"(t), "r"(e));
  return r;
}
__device__ __forceinline__ uint64_t mkdesc(uint32_t addr, uint32_t lbo, uint32_t sbo, uint32_t sw) {
  return (uint64_t)(((addr & 0x3FFFF) >> 4) | ((lbo >> 4) << 16)) | ((uint64_t)((sbo >> 4) | (sw << 30)) << 32);
}

template <int TA, int TB>
__device__ __forceinline__ void mma128(float (&d)[64], uint64_t da, uint64_t db, int sc) {
  asm volatile("{\n.reg .pred p;\nsetp.ne.b32 p, %66, 0;\n"
    "wgmma.mma_async.sync.aligned.m64n128k16.f32.bf16.bf16 "
    "{%0,%1,%2,%3,%4,%5,%6,%7,%8,%9,%10,%11,%12,%13,%14,%15,%16,%17,%18,%19,%20,%21,%22,%23,"
    "%24,%25,%26,%27,%28,%29,%30,%31,%32,%33,%34,%35,%36,%37,%38,%39,%40,%41,%42,%43,%44,%45,%46,%47,"
    "%48,%49,%50,%51,%52,%53,%54,%55,%56,%57,%58,%59,%60,%61,%62,%63}, "
    "%64, %65, p, 1, 1, %67, %68;\n}\n"
    : "+f"(d[0]), "+f"(d[1]), "+f"(d[2]), "+f"(d[3]), "+f"(d[4]), "+f"(d[5]), "+f"(d[6]), "+f"(d[7]),
      "+f"(d[8]), "+f"(d[9]), "+f"(d[10]), "+f"(d[11]), "+f"(d[12]), "+f"(d[13]), "+f"(d[14]), "+f"(d[15]),
      "+f"(d[16]), "+f"(d[17]), "+f"(d[18]), "+f"(d[19]), "+f"(d[20]), "+f"(d[21]), "+f"(d[22]), "+f"(d[23]),
      "+f"(d[24]), "+f"(d[25]), "+f"(d[26]), "+f"(d[27]), "+f"(d[28]), "+f"(d[29]), "+f"(d[30]), "+f"(d[31]),
      "+f"(d[32]), "+f"(d[33]), "+f"(d[34]), "+f"(d[35]), "+f"(d[36]), "+f"(d[37]), "+f"(d[38]), "+f"(d[39]),
      "+f"(d[40]), "+f"(d[41]), "+f"(d[42]), "+f"(d[43]), "+f"(d[44]), "+f"(d[45]), "+f"(d[46]), "+f"(d[47]),
      "+f"(d[48]), "+f"(d[49]), "+f"(d[50]), "+f"(d[51]), "+f"(d[52]), "+f"(d[53]), "+f"(d[54]), "+f"(d[55]),
      "+f"(d[56]), "+f"(d[57]), "+f"(d[58]), "+f"(d[59]), "+f"(d[60]), "+f"(d[61]), "+f"(d[62]), "+f"(d[63])
    : "l"(da), "l"(db), "r"(sc), "n"(TA), "n"(TB));
}

__device__ __forceinline__ void mma_ktv(float (&d)[36], const uint32_t (&a)[4], uint64_t db, int sc) {
  asm volatile("{\n.reg .pred p;\nsetp.ne.b32 p, %41, 0;\n"
    "wgmma.mma_async.sync.aligned.m64n72k16.f32.bf16.bf16 "
    "{%0,%1,%2,%3,%4,%5,%6,%7,%8,%9,%10,%11,%12,%13,%14,%15,%16,%17,%18,%19,%20,%21,%22,%23,"
    "%24,%25,%26,%27,%28,%29,%30,%31,%32,%33,%34,%35}, "
    "{%36,%37,%38,%39}, %40, p, 1, 1, 0;\n}\n"
    : "+f"(d[0]), "+f"(d[1]), "+f"(d[2]), "+f"(d[3]), "+f"(d[4]), "+f"(d[5]), "+f"(d[6]), "+f"(d[7]),
      "+f"(d[8]), "+f"(d[9]), "+f"(d[10]), "+f"(d[11]), "+f"(d[12]), "+f"(d[13]), "+f"(d[14]), "+f"(d[15]),
      "+f"(d[16]), "+f"(d[17]), "+f"(d[18]), "+f"(d[19]), "+f"(d[20]), "+f"(d[21]), "+f"(d[22]), "+f"(d[23]),
      "+f"(d[24]), "+f"(d[25]), "+f"(d[26]), "+f"(d[27]), "+f"(d[28]), "+f"(d[29]), "+f"(d[30]), "+f"(d[31]),
      "+f"(d[32]), "+f"(d[33]), "+f"(d[34]), "+f"(d[35])
    : "r"(a[0]), "r"(a[1]), "r"(a[2]), "r"(a[3]), "l"(db), "r"(sc));
}

__device__ __forceinline__ void mma_qkvz(float (&d)[20], uint64_t da, uint64_t db, int sc) {
  asm volatile("{\n.reg .pred p;\nsetp.ne.b32 p, %22, 0;\n"
    "wgmma.mma_async.sync.aligned.m64n40k16.f32.bf16.bf16 "
    "{%0,%1,%2,%3,%4,%5,%6,%7,%8,%9,%10,%11,%12,%13,%14,%15,%16,%17,%18,%19}, "
    "%20, %21, p, 1, 1, 0, 1;\n}\n"
    : "+f"(d[0]), "+f"(d[1]), "+f"(d[2]), "+f"(d[3]), "+f"(d[4]), "+f"(d[5]), "+f"(d[6]), "+f"(d[7]),
      "+f"(d[8]), "+f"(d[9]), "+f"(d[10]), "+f"(d[11]), "+f"(d[12]), "+f"(d[13]), "+f"(d[14]), "+f"(d[15]),
      "+f"(d[16]), "+f"(d[17]), "+f"(d[18]), "+f"(d[19])
    : "l"(da), "l"(db), "r"(sc));
}

template <int N> __device__ __forceinline__ void pin(float (&d)[N]) {
#pragma unroll
  for (int i = 0; i < N; i++) asm volatile("" : "+f"(d[i])::"memory");
}

struct Params {
  CUtensorMap x, w, xr, gate, up, wo, out, down;
};

__device__ __forceinline__ uint32_t dup_lo(uint32_t v) { uint32_t r; asm("{\n.reg .b16 l, h;\nmov.b32 {l, h}, %1;\nmov.b32 %0, {l, l};\n}" : "=r"(r) : "r"(v)); return r; }
__device__ __forceinline__ uint32_t dup_hi(uint32_t v) { uint32_t r; asm("{\n.reg .b16 l, h;\nmov.b32 {l, h}, %1;\nmov.b32 %0, {h, h};\n}" : "=r"(r) : "r"(v)); return r; }
__device__ __forceinline__ float butterfly8(float (&s)[8], int lane, int o) {
#pragma unroll
  for (int k = 1; k < 8; k <<= 1) {
    const bool up = lane & (o * k);
#pragma unroll
    for (int j = 0; j < 4 / k; j++) s[j] = (up ? s[2 * j + 1] : s[2 * j]) + __shfl_xor_sync(~0u, up ? s[2 * j] : s[2 * j + 1], o * k);
  }
  return s[0];
}
constexpr int OWN = 8, PEER = 9;
static_assert((OA_SLOTS >> OWN * 4 & 15) * SLOT == OFF_V && (OA_SLOTS >> PEER * 4 & 15) * SLOT == OFF_PK, "");
template <int B> __device__ __forceinline__ void verify_tiles(uint32_t sb, Scratch* gs, int tm, int tn, int w, int lane) {
  const uint32_t par = lds32(sb + OFF_MISC + 24), fix = sb + BAR_FIX + (B * 4 + w) * 8;
  uint32_t slots = (uint32_t)(OA_SLOTS >> B * 40);
#pragma unroll 1
  for (int i = 0; i < 8 - 2 * B; i++, slots >>= 4) {
    const uint32_t a = sb + OFF_RING + (slots & 15) * SLOT + w * 1024, cw = a + lane * 32 + (lane >> 2) * 4;
    if (!B && i == 4) mbar_wait(sb + BAR_EMPTY + 7 * 8, 1);
    mbar_wait(sb + BAR_LAND + i * 8, B);
    for (;;) {
      const uint32_t u0 = lds32(cw), u1 = lds32(cw + 4096), u2 = lds32(cw + 8192), u3 = lds32(cw + 12288);
      if (__all_sync(~0u, !(mism(mism(u0, u1, par), mism(u2, u3, par), 0) & 1))) break;
      const uint4* src = gs->o[tm][!B ? i : i < (tn & 6) ? i + 8 : i + 10] + w * 64;
      const uint32_t ph = !mbar_test(fix, 1);
      fence_async_smem();
      __syncwarp();
      if (elect()) {
        mbar_expect_tx(fix, 4096);
#pragma unroll 1
        for (int j = 0; j < 4; j++) bulk_load(a + j * 4096, src + j * 256, 1024, fix);
      }
      mbar_wait(fix, ph);
    }
    mbar_arrive_warp(sb + BAR_OFULL + (i < 5 ? i : i - 5) * 8);
  }
}
template <bool BY_SM> struct Tile {
  int sm, tm, tn, mu;
  bool spare;
  __device__ __forceinline__ Tile() {
    if (BY_SM) asm volatile("mov.u32 %0, %%smid;" : "=r"(sm));
    else sm = blockIdx.x + (blockIdx.x >= 120) * 4;
    const int tp = sm >> 1, pr = sm & 1;
    const int v = tp < 32 ? tp : tp < 60 ? (tp * 293 - 928) >> 8 : tp * 8 - 464, g = v & 7, i = v >> 3;
    tm = (v & 6) * 2 + (i & 3); tn = (v & 1) * 4 + (v >> 4 & 2) + pr;
    mu = i == 5 ? 112 : g * 14 + (i - (i > 5)) * 2 + pr;
    spare = (tp | 1) == 61;
  }
};

template <bool BY_SM> __global__ void __cluster_dims__(2, 1, 1) __launch_bounds__(NTHREADS, 1) fused_kernel(const __nv_bfloat16* __restrict__ px, Scratch* gs, const __nv_bfloat16* __restrict__ w_gate,
             const __nv_bfloat16* __restrict__ w_up, const __nv_bfloat16* __restrict__ w_r, const __nv_bfloat16* __restrict__ gate_w, const __nv_bfloat16* __restrict__ w_down, __nv_bfloat16* __restrict__ pout,
             const __grid_constant__ Params p) {
  extern __shared__ __align__(1024) uint8_t smem[];
  const uint32_t sb = __shfl_sync(~0u, (uint32_t)__cvta_generic_to_shared(smem), 0);
  const int tid = threadIdx.x, lane = tid & 31;
  const int warp = __shfl_sync(~0u, tid >> 5, 0), wg = warp >> 2;
  const uint32_t t_start = clock32();
  const Tile<BY_SM> tile;
  const int tm = tile.tm, tn = tile.tn, mu = tile.mu, cta = tm * 8 + tn;
  const uint32_t zero = tile.sm >> 12;
  if (warp == 0) {
#pragma unroll
    for (int s = 0; s < PRE; s++)
      if (elect()) mbar_init(sb + BAR_FULL + s * 8, 1);
    asm volatile("fence.mbarrier_init.release.cluster;" ::: "memory");
    if (!tile.spare) {
#pragma unroll
      for (int s = 0; s < PRE; s++) {
        if (elect()) tma3d(sb + OFF_W1 + s * WQKV_BYTES, &p.w, tn * 64, s * 64, 0, sb + BAR_FULL + s * 8);
        if (elect()) tma2d(sb + OFF_RING + s * SLOT, &p.x, s * 64, tm * 128, sb + BAR_FULL + s * 8);
        PROF(lane == 0, 64 + s);
      }
      if (elect()) {
#pragma unroll
        for (int s = 0; s < PRE; s++) mbar_expect_tx(sb + BAR_FULL + s * 8, SLOT + WQKV_BYTES);
      }
    }
  }
  if (warp) {
    const int wi = warp == 15 ? 0 : warp;
    const int cnt = wi < 7 ? 1 : wi < 13 ? 4 : 5;
#pragma unroll
    for (int i = 0; i < 4; i++)
      if ((i >= PRE || wi) && elect()) mbar_init(sb + OFF_BAR + wi * 32 + i * 8, cnt);
    asm volatile("fence.mbarrier_init.release.cluster;" ::: "memory");
  }
  __syncthreads();
  if (tile.spare) {
    if (warp == 0) {
      const unsigned tag = (ld_relaxed(&gs->spare[tile.sm & 3]) + 1) & 0xFFF;
      const unsigned long long t0 = gtime();
      uint4 r4;
      do {
        __nanosleep(2048);
        if (gtime() - t0 > WATCHDOG_NS) __trap();
        r4 = ld_relaxed4(&gs->rslot[tile.sm & 3][lane * 4]);
      } while (!__all_sync(~0u, (((r4.x ^ tag) | (r4.y ^ tag) | (r4.z ^ tag) | (r4.w ^ tag)) & 0xFFF) == 0));
      if (tid == 0) st_relaxed(&gs->spare[tile.sm & 3], tag);
    }
    return;
  }

  if (wg == 3) {
    asm volatile("setmaxnreg.dec.sync.aligned.u32 24;");
    if (warp == 12) {
      mbar_wait(sb + BAR_PUB, 0);
      while (!__all_sync(~0u, ld_relaxed(gs->cnt[tm]) == 0x44444444u)) __nanosleep(A_SLEEP);
      fence_acquire();
      fence_async_global();
      PROF(lane == 0, 7);
      mbar_wait(sb + BAR_GATE, 0);
      const uint32_t lowb = (1u << (tn & 6) * 4) - 1;
      uint32_t slabs = 0x76543210u, deps = 0xA9877654u;
      const unsigned* flag = gs->cnt[16 + tm];
      const uint4* src = gs->o[tm][0];
#pragma unroll 1
      for (int n = 8; n >= 6; n -= 2) {
        unsigned seen = n == 8 ? ~0u : 0;
        uint32_t slots = n == 8 ? (uint32_t)OA_SLOTS : (uint32_t)(OA_SLOTS >> 40);
#pragma unroll 1
        for (int i = 0; i < n; i++, slabs >>= 4, deps >>= 4, slots >>= 4) {
          const uint32_t need = 4u << (slabs & 7) * 4, land = sb + BAR_LAND + i * 8;
          if (!__all_sync(~0u, seen & need)) {
            while (!__all_sync(~0u, (seen = ld_relaxed(flag)) & need)) __nanosleep(32);
            fence_acquire();
            fence_async_global();
          }
          mbar_wait(sb + BAR_EMPTY + (deps & 15) * 8, i < 5);
          if (elect()) bulk_load(sb + OFF_RING + (slots & 15) * SLOT, src + (slabs & 7) * 1024, SLOT, land);
          if (elect()) mbar_expect_tx(land, SLOT);
          PROF(lane == 0, 44 + i + (n == 6) * 10);
        }
        slabs = (0x76543210u & lowb) | (0x765432u & ~lowb);
        deps = 0x8CBA98u;
        src += 8 * 1024;
        mbar_wait(sb + BAR_PUB + 8, 0);
      }
    } else if (warp == 13) {
#pragma unroll 1
      for (int g = PRE; g < 32; g++) {
        const bool reuse = (g >> 2) == 4;
        const uint32_t s = g & 3, full = sb + BAR_FULL + (g & 7) * 8, c0 = tn * 64 + (g & 16) * 32, c1 = (g < 16 ? g : g - 4 & 15) * 64;
        if (g < 4) while ((int)(clock32() - t_start) < g * ST1) {}
        mbar_wait(sb + BAR_EMPTY + (g + 4 & 7) * 8, (g + 4 >> 3 & 1) ^ 1);
        if (!reuse && elect()) tma2d(sb + OFF_RING + s * SLOT, &p.x, c1, tm * 128, full);
        if (elect()) tma3d(sb + OFF_W1 + s * WQKV_BYTES, &p.w, c0, c1, 0, full);
        if (elect()) mbar_expect_tx(full, reuse ? WQKV_BYTES : SLOT + WQKV_BYTES);
        PROF(lane == 0, 64 + g);
        const uint32_t i = g - RT_G0;
        if (i < 4 && elect()) {
          mbar_expect_tx(sb + BAR_RT + i * 8, i ? 8192 : 8192 + 4096);
          tma2d(sb + OFF_PK + i * 8192 + (i == 3) * 1024, &p.xr, ((i + RT_ROT) & 3) * 256, cta * 16, sb + BAR_RT + i * 8);
          if (i == 0) { bulk_load(sb + OFF_KVB, w_r, 2048, sb + BAR_RT); bulk_load(sb + OFF_KVB + 2048, gate_w, 2048, sb + BAR_RT); }
        }
        const uint32_t c = g - MOD_START;
        if (c == MOD_BUFS) mbar_wait(sb + BAR_RTD, 0);
        if (c < MOD_BUFS0 && mu < MOD_CTAS && elect()) {
          PROF(true, 192 + c);
          const uint32_t mb = c < MOD_BUFS ? c + 2 : c - MOD_BUFS, mfull = sb + BAR_MFULL + mb * 8, mdst = sb + OFF_V + mb * MOD_STEP;
          mbar_expect_tx(mfull, c ? 8192 : 8192 + 2048);
          tma3d(mdst, &p.gate, mu * 32, c * 16, 0, mfull); tma3d(mdst + 4096, &p.up, mu * 32, c * 16, 0, mfull);
        }
        const uint32_t pc = g - PF_MOD;
        if (pc < 16 && elect()) bulk_prefetch((cta & 64 ? w_up : w_gate) + (size_t)(pc * 64 + (cta & 63)) * F_, F_ * 2);
      }
      mbar_arrive_warp(sb + BAR_GATE);
      const uint32_t lowb = (1u << (tn & 6) * 4) - 1;
      uint64_t slabs = (uint64_t)((0xFEDCBA98u & lowb) | (0xFEDCBAu & ~lowb)) << 40 | (uint64_t)(8 + (tn ^ 1)) << 36 | (uint64_t)(8 + tn) << 32 | 0x76543210u;
      uint64_t deps = 0x8CBA98CBA9876554ull, ws = OW_SLOTS;
      uint32_t full = sb + BAR_OFULL, ph = 1;
#pragma unroll 1
      for (int g = 0; g < 16; g++, slabs >>= 4, deps >>= 4, ws >>= 4) {
        mbar_wait(sb + BAR_EMPTY + ((uint32_t)deps & 15) * 8, ph);
        if (elect()) tma3d(sb + OFF_RING + ((uint32_t)ws & 15) * SLOT, &p.wo, 0, ((uint32_t)slabs & 15) * 64, tn * 2, full);
        if (elect()) mbar_expect_tx(full, SLOT);
        PROF(lane == 0, 96 + g);
        if (g >> 1 == OWN / 2 && lane < 4) mbar_arrive(full);
        full += 8;
        if (full == sb + BAR_OFULL + 40) { full -= 40; ph ^= 1; }
      }
    } else if (warp == 14) {
      if (mu < MOD_CTAS) {
        uint32_t full = sb + BAR_MFULL + 16, dst = sb + OFF_MOD, ph = 0;
#pragma unroll 1
        for (int c = MOD_BUFS0; c < 24; c++) {
          mbar_wait(full + (BAR_MEMPTY - BAR_MFULL), ph);
          PROF(lane == 0, 192 + c);
          if (c < 16) {
            if (elect()) { tma3d(dst, &p.gate, mu * 32, c * 16, 0, full); tma3d(dst + 4096, &p.up, mu * 32, c * 16, 0, full); }
          } else if (elect()) tma3d(dst, &p.down, 0, mu * 32 + (c - 16) * 4, 0, full);
          if (elect()) mbar_expect_tx(full, 8192);
          if (PD && (uint32_t)(c + PD - 16) < 8 && elect()) bulk_prefetch(w_down + (size_t)(mu * 32 + (c + PD - 16) * 4) * D_, 8192);
          full += 8; dst += MOD_STEP;
          if (full == sb + BAR_MFULL + MOD_BUFS0 * 8) { full -= MOD_BUFS * 8; dst = sb + OFF_MOD; ph ^= 1; }
        }
      }
      if (elect()) {
      mbar_wait(sb + BAR_IDX, 0);
      const bool paired = PAIRED && ld_relaxed(&gs->block[cta ^ 1]) == (blockIdx.x ^ 1);
      if (paired) mbar_expect_tx(sb + BAR_PEER, SLOT);
      mbar_expect_tx(sb + BAR_X, 32768);
      mbar_wait(sb + BAR_OEMPTY + 3 * 8, 0);
      tma2d(sb + OFF_RES, &p.x, tn * 128, tm * 128, sb + BAR_X);
      mbar_wait(sb + BAR_OEMPTY + 4 * 8, 0);
      tma2d(sb + OFF_RES + RES_H, &p.x, tn * 128 + 64, tm * 128, sb + BAR_X);
      if (!paired) {
        mbar_wait(sb + BAR_OWN, 0);
        while (!(ld_relaxed(gs->cnt[16 + tm]) & 4u << (tn ^ 1) * 4)) __nanosleep(32);
        fence_acquire();
        fence_async_global();
        const uint32_t par = lds32(sb + OFF_MISC + 24);
        for (uint32_t ph = !mbar_test(sb + BAR_MFULL, 1), bad = 1; bad & 1; ph ^= 1) {
          fence_async_smem();
          mbar_expect_tx(sb + BAR_MFULL, SLOT);
          bulk_load(sb + OFF_PK, gs->o[tm][8 + (tn ^ 1)], SLOT, sb + BAR_MFULL);
          mbar_wait(sb + BAR_MFULL, ph);
          bad = 0;
#pragma unroll 1
          for (int i = 0; i < 512; i++) bad |= lds32(sb + OFF_PK + i * 32 + (i & 28)) ^ par;
        }
        mbar_arrive(sb + BAR_PEER);
      }
      }
    } else {
#pragma unroll 1
      for (int i = 2; i < 8; i++)
        if (elect()) asm volatile("prefetch.tensormap [%0];" ::"l"(&p.x + i) : "memory");
      mbar_wait_bounded(sb + BAR_DONE, 0);
    }
  } else if (wg == 2) {
    asm volatile("setmaxnreg.dec.sync.aligned.u32 40;");
    const int mw = warp & 3;
    if (mw == 0) {
      const unsigned tag = (ld_relaxed(&gs->rslot[tn][cta]) + 1) & 0xFFF;
#pragma unroll
      for (int i = 0; i < 2; i++)
        if (lane < 28) ((float4*)gs)[cta * 56 + i * 28 + lane] = make_float4(0.f, 0.f, 0.f, 0.f);
      if (lane == 29) gs->block[cta] = blockIdx.x;
      fence_release();
      nb_sync(NB_KEY, 160);
      const uint4 k4 = lds128(sb + OFF_MISC);
      if (lane < 8) st_relaxed(&gs->rslot[lane][cta], max(max(k4.x, k4.y), max(k4.z, k4.w)) | tag);
      if (lane < 16) st_relaxed(&gs->gslot[cta * 16 + lane], lds32(sb + OFF_G + lane * 4) | tag);
      PROF(lane == 0, 20);
      uint4 r4;
      do {
        __nanosleep(RT_SLEEP);
        r4 = ld_relaxed4(&gs->rslot[tn][lane * 4]);
      } while (!__all_sync(~0u, (((r4.x ^ tag) | (r4.y ^ tag) | (r4.z ^ tag) | (r4.w ^ tag)) & 0xFFF) == 0));
      const int c0 = 0xFFF0 - lane * 64;
      unsigned key = max(max((r4.x & 0xFFFF0000u) | (c0 + ((r4.x >> 12) & 15)), (r4.y & 0xFFFF0000u) | (c0 - 16 + ((r4.y >> 12) & 15))),
                         max((r4.z & 0xFFFF0000u) | (c0 - 32 + ((r4.z >> 12) & 15)), (r4.w & 0xFFFF0000u) | (c0 - 48 + ((r4.w >> 12) & 15))));
      key = __reduce_max_sync(~0u, key);
      if (elect()) {
        sts32(sb + OFF_MISC + 16, key);
        sts32(sb + OFF_MISC + 24, tag & 1);
        if (mu < MOD_CTAS) {
          const __nv_bfloat16* row = px + (size_t)(0xFFFF - (key & 0xFFFF)) * D_;
          bulk_load(sb + OFF_XSEL, row, 1024, sb + BAR_MFULL + 16);
          bulk_load(sb + OFF_XSEL + MOD_STEP, row + 512, 1024, sb + BAR_MFULL + 16);
        }
      }
      PROF(lane == 0, 21);
      do {
        r4 = ld_relaxed4(&gs->gslot[tm * 128 + lane * 4]);
      } while (!__all_sync(~0u, (((r4.x ^ tag) | (r4.y ^ tag) | (r4.z ^ tag) | (r4.w ^ tag)) & 0xFFF) == 0));
      sts128(sb + OFF_G + lane * 16, r4.x & 0xFFFF0000u, r4.y & 0xFFFF0000u, r4.z & 0xFFFF0000u, r4.w & 0xFFFF0000u);
      fence_acquire();
      __syncwarp();
    }
    PROF(tid == 256, 22);
    if (mu >= MOD_CTAS) {
      mbar_arrive_warp(sb + BAR_IDX);
    } else {
      const uint32_t wp = sb + OFF_V + (mw >> 1) * 4096 + (mw & 1) * 512 + lane * 16;
      uint32_t mp = sb + OFF_XSEL + (mw & 1) * 64 + (lane >> 2) * 8, mc = 128;
      float acc[8] = {0.f, 0.f, 0.f, 0.f, 0.f, 0.f, 0.f, 0.f};
      uint32_t b = 2, ph = 0;
#pragma unroll 1
      for (int c = 0; c < 24; c++) {
        if (MOD_SLEEP && c >= MOD_S0) __nanosleep(MOD_SLEEP);
        mbar_wait(sb + BAR_MFULL + b * 8, ph);
        PROF_C(tid == 256, 216 + c);
        const uint32_t a = wp + b * MOD_STEP;
        const uint2 m = lds64(mp);
        const uint4 w0 = lds128(a), w1 = lds128(a + 1024), w2 = lds128(a + 2048), w3 = lds128(a + 3072);
        mp += c == 7 ? MOD_STEP - 1024 + 128 : mc;
        const uint32_t m0 = dup_lo(m.x), m1 = dup_hi(m.x), m2 = dup_lo(m.y), m3 = dup_hi(m.y);
        uint4 q = make_uint4(mul_bf2(w0.x, m0), mul_bf2(w0.y, m0), mul_bf2(w0.z, m0), mul_bf2(w0.w, m0));
        q = make_uint4(fma_bf2(w1.x, m1, q.x), fma_bf2(w1.y, m1, q.y), fma_bf2(w1.z, m1, q.z), fma_bf2(w1.w, m1, q.w));
        q = make_uint4(fma_bf2(w2.x, m2, q.x), fma_bf2(w2.y, m2, q.y), fma_bf2(w2.z, m2, q.z), fma_bf2(w2.w, m2, q.w));
        mbar_arrive_warp(sb + BAR_MEMPTY + b * 8 + (w3.x & zero));
        q = make_uint4(fma_bf2(w3.x, m3, q.x), fma_bf2(w3.y, m3, q.y), fma_bf2(w3.z, m3, q.z), fma_bf2(w3.w, m3, q.w));
        if (++b == 5) b = c < 3 ? 0 : 2;
        if (b == 2) ph ^= 1;
        acc[0] += bf_lo(q.x); acc[1] += bf_hi(q.x); acc[2] += bf_lo(q.y); acc[3] += bf_hi(q.y);
        acc[4] += bf_lo(q.z); acc[5] += bf_hi(q.z); acc[6] += bf_lo(q.w); acc[7] += bf_hi(q.w);
        if (c == 15) {
          const uint32_t ft = fresh_tid(), fl = ft & 31;
          sts32(sb + OFF_PART + (ft & 96) * 4 + ((ft & 3) * 8 + (fl >> 2)) * 4, __float_as_uint(butterfly8(acc, fl, 4)));
          nb_sync(NB_MODW, 128);
          const float* part = (const float*)(smem + OFF_PART) + fl;
          const float gp = bf_round(part[0] + part[32]), up = bf_round(part[64] + part[96]);
          *(__nv_bfloat16*)(smem + OFF_PART + 512 + fl * 2) = __float2bfloat16_rn(bf_round(gp * sigmoidf_(gp)) * up);
          __syncwarp();
          mp = sb + OFF_PART + 512; mc = 8;
#pragma unroll
          for (int i = 0; i < 8; i++) acc[i] = 0.f;
          PROF(lane == 0 && mw == 0, 23);
        }
      }
      float4* yacc = gs->y[tn & 1][0] + (fresh_tid() & 127);
      red_add4(yacc, acc[0], acc[1], acc[2], 1.f);
      red_add4(yacc + 128, acc[3], acc[4], acc[5], 1.f);
      red_add4(yacc + 256, acc[6], acc[7], 0.f, 1.f);
      PROF(lane == 0 && mw == 0, 25);
    }
    mbar_wait(sb + BAR_GATE, 0);
    mbar_wait(sb + BAR_IDX, 0);
    verify_tiles<0>(sb, gs, tm, tn, mw, lane);
    const unsigned key = lds32(sb + OFF_MISC + 16);
    const int sel = 0xFFFF - (int)(key & 0xFFFF) - tm * 128;
    if (mw == 0 && sel >= 0 && sel < 128) {
      const unsigned k16 = key >> 16;
      const float rs = bf_round(sigmoidf_(__uint_as_float(((k16 & 0x8000u) ? (k16 & 0x7FFFu) : (~k16 & 0xFFFFu)) << 16)));
      float v[12];
      const float4* yp = gs->y[lane >> 4][0] + tn * 16 + (lane & 15);
      for (;;) {
#pragma unroll
        for (int i = 0; i < 3; i++) {
          const float4 u = ld_relaxed_f4(yp + i * 128);
          v[4 * i] = u.x; v[4 * i + 1] = u.y; v[4 * i + 2] = u.z; v[4 * i + 3] = u.w;
        }
        const float n = v[3] + v[7] + v[11];
        if (__all_sync(~0u, n + __shfl_xor_sync(~0u, n, 16) == 3.f * MOD_CTAS)) break;
        __nanosleep(Y_SLEEP);
      }
#pragma unroll
      for (int i = 0; i < 10; i++) v[i] = bf_round(bf_round(v[i] + __shfl_xor_sync(~0u, v[i], 16)) * rs);
      PROF(lane == 0, 24);
      mbar_wait(sb + BAR_X, 0);
      if (lane < 16) {
        uint4* xp = (uint4*)(smem + OFF_RES + (lane >> 3) * RES_H + sel * 128 + (((lane ^ sel) & 7) << 4));
        const uint4 xv = *xp;
        *xp = make_uint4(pack2(bf_lo(xv.x) + v[0], bf_hi(xv.x) + v[1]), pack2(bf_lo(xv.y) + v[2], bf_hi(xv.y) + v[4]),
                         pack2(bf_lo(xv.z) + v[5], bf_hi(xv.z) + v[6]), pack2(bf_lo(xv.w) + v[8], bf_hi(xv.w) + v[9]));
      }
      __syncwarp();
      mbar_arrive_warp(sb + BAR_Y);
    }
  } else {
    asm volatile("setmaxnreg.inc.sync.aligned.u32 224;");
    const int w = warp & 3, wt = tid & 127;
    const int nb_self = NB_WG0 + wg;
    const uint64_t da0 = mkdesc(sb + OFF_RING, 16, 1024, 1), db0 = mkdesc(sb + OFF_RING, 8192, 1024, 1);

    if (wg == 1) {
      sts128(sb + OFF_ONES - (w >> 1) * 9216 + (w & 1) * 512 + lane * 16, 0x3F803F80u, 0x3F803F80u, 0x3F803F80u, 0x3F803F80u);
      sts32(sb + OFF_MISC + 20, 0x3FB8AA3Bu);
      fence_async_smem();
      float s[8] = {0.f, 0.f, 0.f, 0.f, 0.f, 0.f, 0.f, 0.f};
      uint32_t mask = 0xffff0000u;
#pragma unroll 1
      for (int i = 0; i < 4; i++) {
        const uint32_t u = (i + RT_ROT) & 3;
        mbar_wait(sb + BAR_RT + i * 8, 0);
        const uint4 wr = lds128(sb + OFF_KVB + u * 512 + lane * 16), gw = lds128(sb + OFF_KVB + 2048 + u * 512 + lane * 16);
        uint4 xv[4];
#pragma unroll
        for (int r = 0; r < 4; r++) xv[r] = lds128(sb + OFF_PK + i * 8192 + (i == 3) * 1024 + (w * 4 + r) * 512 + lane * 16);
        const float wf[16] = {bf_lo(wr.x), bf_hi(wr.x), bf_lo(wr.y), bf_hi(wr.y), bf_lo(wr.z), bf_hi(wr.z), bf_lo(wr.w), bf_hi(wr.w),
                              bf_lo(gw.x), bf_hi(gw.x), bf_lo(gw.y), bf_hi(gw.y), bf_lo(gw.z), bf_hi(gw.z), bf_lo(gw.w), bf_hi(gw.w)};
#pragma unroll
        for (int r = 0; r < 4; r++) {
          const uint4 xq = xv[r];
          const float xf[8] = {bf_lo(xq.x), __uint_as_float(xq.x & mask), bf_lo(xq.y), bf_hi(xq.y), bf_lo(xq.z), bf_hi(xq.z), bf_lo(xq.w), bf_hi(xq.w)};
#pragma unroll
          for (int j = 0; j < 8; j++) { s[2 * r] = fmaf(xf[j ^ 1], wf[j ^ 1], s[2 * r]); s[2 * r + 1] = fmaf(xf[j ^ 1], wf[8 + (j ^ 1)], s[2 * r + 1]); }
          mask = ((__float_as_uint(s[2 * r]) | __float_as_uint(s[2 * r + 1])) & zero) | 0xffff0000u;
        }
      }
      mbar_arrive_warp(sb + BAR_RTD);
      float v = butterfly8(s, lane, 1);
      PROF_C(wt == 0 && v != 12345.f, 19);
      v += __shfl_xor_sync(~0u, v, 8);
      v = bf_round(v + __shfl_xor_sync(~0u, v, 16));
      const unsigned rb = __float_as_uint(v) >> 16, row = w * 4 + ((lane & 7) >> 1);
      unsigned key = (lane & 1) ? 0u : ((((rb & 0x8000u) ? (~rb & 0xFFFFu) : (rb | 0x8000u)) << 16) | ((15 - row) << 12));
      key = __reduce_max_sync(~0u, key);
      if (lane == 0) sts32(sb + OFF_MISC + w * 4, key);
      if (lane < 8 && (lane & 1)) sts32(sb + OFF_G + row * 4, __float_as_uint(bf_round(sigmoidf_(v))));
      nb_arrive(NB_KEY, 160);
      nb_sync(NB_ORDER_12, 256);
    }
    uint4* const kvacc = &gs->kv[wg][tn][0][wt];
    float aq[64];
    uint32_t su[9];
    {
      float ak[64], av[64], c[36];
      uint32_t pk[8][4];
      PROF_C(wt == 0, 1 + wg * 8);
#pragma unroll 1
      for (int g = 0; g < 16; g++) {
        const uint64_t dx = da0 + (g & 3) * (SLOT >> 4), dw = da0 + ((OFF_W1 >> 4) + (g & 3) * (WQKV_BYTES >> 4));
        mbar_wait(sb + BAR_FULL + (g & 7) * 8, g >> 3);
        if (g == 0) PROF_C(wt == 0, 2 + wg * 8);
        wg_fence();
#pragma unroll
        for (int kk = 0; kk < 4; kk++) mma128<1, 0>(ak, dw + (512 + kk * 128), dx + kk * 2, kk ? 1 : g);
        wg_commit();
        if (G1 == 1) {
          wg_wait<1>();
          if (g) mbar_arrive_warp(sb + BAR_EMPTY + (g - 1 & 7) * 8);
          wg_fence();
        }
#pragma unroll
        for (int kk = 0; kk < 4; kk++) mma128<1, 0>(av, dw + (1024 + kk * 128), dx + kk * 2, kk ? 1 : g);
        wg_commit();
        if (G1 == 2) {
          wg_wait<2>();
          if (g) mbar_arrive_warp(sb + BAR_EMPTY + (g - 1 & 7) * 8);
          wg_fence();
        }
#pragma unroll
        for (int kk = 0; kk < 4; kk++) mma128<1, 0>(aq, dw + kk * 128, dx + kk * 2, kk ? 1 : g);
        wg_commit();
      }
      if (wg == 0) nb_arrive(NB_ORDER_12, 256);
      if (wg == 1 && EARLY_O) nb_arrive(NB_ORDER_3O, 256);
      mbar_wait(sb + BAR_IDX, 0);
      if (wg == 1) nb_sync(NB_STG, 256);
      wg_wait<2>();
      pin(ak);
      PROF_C(wt == 0, 3 + wg * 8);
      const uint32_t va = sb + OFF_V + (w * 16 + (lane & 15)) * 128;
      uint32_t lk[8];
#pragma unroll
      for (int u = 0; u < 8; u++) {
        if (u < VK + KL || !KL) lk[u] = 0x3FB8AA3Bu;
#pragma unroll
        for (int i = 0; i < 4; i++) pk[u][i] = phi2(ak[8 * u + 2 * i], ak[8 * u + 2 * i + 1], __uint_as_float(lk[u]));
        if (u == VK) { wg_wait<1>(); pin(av); }
        if (u == MM) { wg_wait<0>(); mbar_arrive_warp(sb + BAR_EMPTY + 7 * 8); }
        const uint32_t z = mism(pk[u][0], pk[u][1], 0) | mism(pk[u][2], pk[u][3], 0);
#pragma unroll
        for (int t = u < VK ? 8 : (u - VK) * 8 / (8 - VK); t < (u - VK + 1) * 8 / (8 - VK); t++) {
          const float* v = &av[8 * t];
          stsm4(va + (t >> 2) * 9216 + ((((lane >> 4) + 2 * (t & 3)) ^ (lane & 7)) << 4) + (z & zero), pack2(v[0], v[1]), pack2(v[2], v[3]), pack2(v[4], v[5]), pack2(v[6], v[7]));
        }
        if (KL && u >= VK && u + KL < 8) lk[u + KL] = lds32(sb + OFF_MISC + 20);
      }
      fence_async_smem();
      nb_sync(nb_self, 128);
      PROF_C(wt == 0, 8 + wg * 8);
      const uint64_t dv = mkdesc(sb + OFF_V, 16, 1024, 1);
      wg_fence();
#pragma unroll
      for (int kk = 0; kk < 8; kk++) mma_ktv(c, pk[kk], dv + ((kk >> 2) * 576 + (kk & 3) * 2), kk ? 1 : 0);
      wg_commit();
      if (wg == 1 && !EARLY_O) nb_arrive(NB_ORDER_3O, 256);
      wg_wait<0>();
      pin(c); pin(aq);
      PROF_C(wt == 0, 4 + wg * 8);
#pragma unroll
      for (int i = 0; i < 8; i++) {
        const int j = (i & 3) * 4 + (i >> 2) * 2;
        su[i] = w >= 2 ? pack2(c[16 + j], c[17 + j]) : pack2(c[j], c[j + 1]);
      }
      su[8] = pack2(c[32], c[34]);
#pragma unroll
      for (int u = 0; u < 3; u++)
        if (u < R0 || wg) red_add_bf(kvacc + u * 128, su[3 * u], su[3 * u + 1], su[3 * u + 2]);
    }
    const uint32_t par = lds32(sb + OFF_MISC + 24);
    {
      const bool paired = PAIRED && ld_relaxed(&gs->block[cta ^ 1]) == (blockIdx.x ^ 1);
      uint4 kv[3];
      int tries = wg ? 0 : TRY_A;
      const uint8_t* gl = smem + OFF_MISC + 20;
      asm volatile("" : "+l"(gl));
      const uint32_t l2e = ld_generic(gl);
    auto stage_kv = [&]() {
      const uint32_t kb = sb + OFF_KVB + w * 256, ka = kb + (lane & 3) * KVB_N + (lane >> 2) * 16;
      sts128(ka, kv[0].x, kv[0].y, kv[0].z, kv[1].x);
      sts128(ka + 128, kv[1].y, kv[1].z, kv[2].x, kv[2].y);
      sts32(kb + 4 * KVB_N + lane * 4, dup_lo(kv[2].z));
      sts32(kb + 4 * KVB_N + 128 + lane * 4, dup_hi(kv[2].z));
      return __all_sync(~0u, (kv[0].w & kv[1].w & kv[2].w) == 0x41804180u && (kv[0].w | kv[1].w | kv[2].w) == 0x41804180u);
    };
      bool have = false;
      const uint32_t qa = sb + OFF_PK + ((lane >> 4) * 8 + (lane & 7)) * 128 + (((2 * w + ((lane >> 3) & 1)) ^ (lane & 7)) << 4);
      uint32_t lq[8];
#pragma unroll
      for (int u = 0; u < QA; u++) lq[u] = l2e;
#pragma unroll
      for (int u = 0; u < 8; u++) {
        uint32_t r[4];
        if (u == KF && wg) {
#pragma unroll
          for (int i = 0; i < 3; i++) kv[i] = ld_relaxed4(kvacc + i * 128);
        }
#pragma unroll
        for (int i = 0; i < 4; i++) r[i] = phi2(aq[8 * u + 2 * i], aq[8 * u + 2 * i + 1], __uint_as_float(lq[u]));
        stsm4t(qa + u * 2048, r[0], r[1], r[2], r[3]);
        if (u % RS == RS - 1 && u / RS + R0 < 3 && !wg) red_add_bf(kvacc + (u / RS + R0) * 128, su[3 * (u / RS + R0)], su[3 * (u / RS + R0) + 1], su[3 * (u / RS + R0) + 2]);
        if (u + QA < 8) lq[u + QA] = QD ? ld_generic(gl) : lds32(sb + OFF_MISC + 20);
        if (u == KU && wg) have = stage_kv();
      }
      PROF_C(wt == 0, 34 + wg * 2);
      if (NAP_A && !wg) __nanosleep(NAP_A);
      if (KU > 7 && KF < 8 && wg) have = stage_kv();
      for (; !have; tries++) {
        if (tries > RETRY)
          while (ld_relaxed((const unsigned*)&(kvacc - lane)[256 + 31].w) != 0x41804180u) __nanosleep(wg ? KV_SLEEP : KV_SLEEP_A);
#pragma unroll
        for (int i = 0; i < 3; i++) kv[i] = ld_relaxed4(kvacc + i * 128);
        have = stage_kv();
      }
      PROF_C(wt == 0, 5 + wg * 8);
      fence_async_smem();
      nb_sync(nb_self, 128);
      float o[2][2][20];
      const uint64_t dq = mkdesc(sb + OFF_PK, 16, 1024, 1), dz = mkdesc(sb + OFF_KVB, 128, KVB_N, 0);
      wg_fence();
#pragma unroll
      for (int m = 0; m < 2; m++) {
#pragma unroll
        for (int h = 0; h < 2; h++)
#pragma unroll
          for (int kk = 0; kk < 2; kk++) mma_qkvz(o[m][h], dq + (m * 512 + h * 4 + kk * 2), dz + (h * 32 + kk * 16), kk);
        wg_commit();
      }
      if (HOLD < 8 && HP == 0 && wg) nb_arrive(NB_HOLD, 256);
      uint32_t tag[2][4];
#pragma unroll
      for (int i = 0; i < 8; i++) tag[i >> 2][i & 3] = (lane >> 3) == (i & 3) && ((lane ^ (lane >> 3)) & 1) == (i >> 2);
      uint32_t gr[8];
      const uint8_t* ga = smem + OFF_G + (w * 16 + (lane >> 2)) * 4;
      asm volatile("" : "+l"(ga));
#pragma unroll
      for (int i = 0; i < OA; i++) gr[i] = ld_generic(ga + (i >> 2) * 256 + (i & 1) * 32);
      const uint32_t oo = w * 1024 + (lane >> 2) * 64 + (((lane ^ (lane >> 3)) & 3) << 4);
      uint8_t* const og = (uint8_t*)gs->o[tm][wg * 8 + tn] + oo;
      uint32_t ob[8][4];
#pragma unroll
      for (int m = 0; m < 2; m++) {
        if (m == 0) wg_wait<1>(); else wg_wait<0>();
        pin(o[m][0]); pin(o[m][1]);
        if (m && !wg) nb_arrive(NB_STG, 256);
        if (HOLD < 8 && HP == 1 && m && wg) nb_arrive(NB_HOLD, 256);
        if (m && wg && paired && elect()) mbar_arrive_peer(peer_addr(sb + BAR_PA));
        if (m == 0) PROF_C(wt == 0, 6 + wg * 8);
#pragma unroll
        for (int u = 0; u < 4; u++) {
          const int h = u >> 1, i = u & 1;
          const float* on = o[m][h];
          const float sc = __uint_as_float(gr[m * 4 + u]) * rcp(on[16 + 2 * i] + 1e-6f);
          const uint32_t sc2 = pack2(sc, sc);
#pragma unroll
          for (int j = 0; j < 4; j++) {
            const uint32_t v = HS ? mul_bf2(pack2(on[4 * j + 2 * i], on[4 * j + 2 * i + 1]), sc2) : pack2(on[4 * j + 2 * i] * sc, on[4 * j + 2 * i + 1] * sc);
            asm("lop3.b32 %0, %1, %2, %3, 0xB8;" : "=r"(ob[m * 4 + u][j]) : "r"(v), "r"(tag[i][j]), "r"(par));
          }
          st_relaxed4(og + (h * 8192 + m * 4096 + i * 512), ob[m * 4 + u]);
          if (OWN1 == 2 && wg) sts128(sb + OFF_V + oo + (h * 8192 + m * 4096 + i * 512), ob[m * 4 + u][0], ob[m * 4 + u][1], ob[m * 4 + u][2], ob[m * 4 + u][3]);
          const int n = m * 4 + u + OA;
          if (n < 8) gr[n] = ld_generic(ga + (n >> 2) * 256 + (n & 1) * 32);
        }
      }
      if (elect()) red_add(gs->cnt[wg * 16 + tm], 1u << tn * 4);
      mbar_arrive_warp(sb + BAR_PUB + wg * 8);
      if (HOLD < 8 && HP == 2 && wg) nb_arrive(NB_HOLD, 256);
      PROF(wt == 0, 17 + wg);
      if (wg) {
        auto to_peer = [&]() {
        if (paired) {
          const uint32_t pb = peer_addr(sb);
          mbar_wait(sb + BAR_PA, 0);
#pragma unroll
          for (int u = 0; u < 8; u++) st_async4(pb + OFF_PK + oo + ((u >> 1 & 1) * 8192 + (u >> 2) * 4096 + (u & 1) * 512), ob[u], pb + BAR_PEER);
        }
        };
        if (!OWN1) to_peer();
#pragma unroll
        for (int u = 0, z = 0; u < (OWN1 == 2 ? 0 : 8); u++) {
          sts128(sb + OFF_V + oo + ((u >> 1 & 1) * 8192 + (u >> 2) * 4096 + (u & 1) * 512) + z, ob[u][0], ob[u][1], ob[u][2], ob[u][3]);
          if (PO && u % PO == PO - 1 && u < 7) z = lds32(sb + OFF_ONES) & 16;
        }
        fence_async_smem();
        __syncwarp();
        mbar_arrive_warp(sb + BAR_OWN);
        if (HOLD < 8 && HP == 3) nb_arrive(NB_HOLD, 256);
        PROF(wt == 0, 15);
        if (OWN1) to_peer();
      }
    }
    if (wg == 1) {
      verify_tiles<1>(sb, gs, tm, tn, w, lane);
    } else {
      float acc[2][64];
      nb_sync(NB_ORDER_3O, 256);
      PROF_C(wt == 0, 26);
      uint32_t xr[2][8][4], q[2][2];
      const uint32_t ta = sb + OFF_RES + (uint32_t)(w * 16 + (lane & 15)) * 128;
      const uint64_t do0 = mkdesc(sb + OFF_RING, 16, 512, 2);
      uint64_t xs = OA_SLOTS, ws = OW_SLOTS;
#pragma unroll 1
      for (int g = 0; g < 13 - TL; g++, xs >>= 4, ws >>= 4) {
        const uint32_t r = g * 52 >> 8, s = g - r * 5;
        const uint64_t da = do0 + ((uint32_t)xs & 15) * (SLOT >> 4), db = db0 + ((uint32_t)ws & 15) * (SLOT >> 4);
        if (g == OWN) mbar_wait(sb + BAR_OWN, 0);
        if (g == PEER) { mbar_wait(sb + BAR_PEER, 0); fence_async_smem(); }
        if (g == HOLD) nb_sync(NB_HOLD, 256);
        mbar_wait(sb + BAR_OFULL + s * 8, r & 1);
        wg_fence();
#pragma unroll
        for (int kk = 0; kk < 4; kk++)
#pragma unroll
          for (int m = 0; m < 2; m++) mma128<0, 1>(acc[m], da + (m * 256 + (kk >> 1) * 512 + (kk & 1) * 2), db + kk * 128, kk ? 1 : g);
        wg_commit();
        wg_wait<1>();
        if (g) mbar_arrive_warp(sb + BAR_OEMPTY + (s ? s - 1 : 4) * 8);
      }
      mbar_wait(sb + BAR_X, 0);
      const int selw = ((0xFFFF - (int)(lds32(sb + OFF_MISC + 16) & 0xFFFF)) >> 4) - tm * 8 - w;
#pragma unroll
      for (int u = 0; u < 4; u++) {
        const int m = u >> 1, g = 13 - TL + u;
        const float g1 = 1.f - __uint_as_float(lds32(sb + OFF_G + (m * 64 + w * 16 + (u & 1) * 8 + (lane >> 2)) * 4));
        q[m][u & 1] = pack2(g1, g1);
#pragma unroll
        for (int j = 0; j < 4; j++) ldsm4(ta + (u & 1) * RES_H + m * 8192 + ((((lane >> 4) + 2 * j) ^ (lane & 7)) << 4), xr[m][(u & 1) * 4 + j]);
        if (u == 3) break;
        mbar_wait(sb + BAR_OFULL + g % 5 * 8, g / 5 & 1);
        wg_fence();
#pragma unroll
        for (int kk = 0; kk < 4; kk++)
#pragma unroll
          for (int mm = 0; mm < 2; mm++)
            mma128<0, 1>(acc[mm], do0 + ((OA_SLOTS >> g * 4 & 15) * (SLOT >> 4) + mm * 256 + (kk >> 1) * 512 + (kk & 1) * 2), db0 + ((OW_SLOTS >> g * 4 & 15) * (SLOT >> 4) + kk * 128), 1);
        wg_commit();
        wg_wait<1>();
        if (g <= 11) mbar_arrive_warp(sb + BAR_OEMPTY + (g + 4) % 5 * 8);
      }
#pragma unroll
      for (int m = 0; m < 2; m++) {
#pragma unroll
        for (int g = 16 - TL; g < 16; g++) {
          if (m == 0) { mbar_wait(sb + BAR_OFULL + g % 5 * 8, g / 5 & 1); wg_fence(); }
#pragma unroll
          for (int kk = 0; kk < 4; kk++)
            mma128<0, 1>(acc[m], do0 + ((OA_SLOTS >> g * 4 & 15) * (SLOT >> 4) + m * 256 + (kk >> 1) * 512 + (kk & 1) * 2), db0 + ((OW_SLOTS >> g * 4 & 15) * (SLOT >> 4) + kk * 128), 1);
        }
        wg_commit();
      }
      mbar_arrive_warp(sb + BAR_DONE);
      const uint32_t tb = sb + OFF_RES + w * 2048 + (lane >> 3) * 128 + (((lane ^ (lane >> 3)) & 7) << 4), tx = lane & 4 ? 64 : -64;
      uint8_t* const og = (uint8_t*)pout + (size_t)(tm * 128 + w * 16 + (lane >> 3)) * 2048 + tn * 256 + (lane & 7) * 16;
#pragma unroll
      for (int m = 0; m < 2; m++) {
        if (selw == 4 * m) {
          mbar_wait(sb + BAR_Y, 0);
#pragma unroll
          for (int j = 0; j < 8; j++) ldsm4(ta + (j >> 2) * RES_H + m * 8192 + ((((lane >> 4) + 2 * (j & 3)) ^ (lane & 7)) << 4), xr[m][j]);
        }
        if (m == 0) wg_wait<1>(); else wg_wait<0>();
        if (m) PROF(wt == 0, 31);
#pragma unroll
        for (int h = 0; h < 2; h++) {
#pragma unroll
          for (int j = 4 * h; j < 4 * h + 4; j++) {
            const float* v = &acc[m][8 * j];
            stsm4(ta + h * RES_H + m * 8192 + ((((lane >> 4) + 2 * (j & 3)) ^ (lane & 7)) << 4),
                  fma_bf2(xr[m][j][0], q[m][0], pack2(v[0], v[1])), fma_bf2(xr[m][j][1], q[m][1], pack2(v[2], v[3])),
                  fma_bf2(xr[m][j][2], q[m][0], pack2(v[4], v[5])), fma_bf2(xr[m][j][3], q[m][1], pack2(v[6], v[7])));
          }
          if (FS >> m & 1) {
            __syncwarp();
            uint4 t[4];
#pragma unroll
            for (int j = 0; j < 4; j++) t[j] = lds128(tb + h * RES_H + m * 8192 + j * 512 - (j & 1) * tx);
#pragma unroll
            for (int j = 0; j < 4; j++) *(uint4*)(og + (m * 64 + j * 4) * 2048 + h * 128) = t[j];
          } else {
            fence_async_smem();
            __syncwarp();
            if (elect()) tma2d_store(&p.out, sb + OFF_RES + h * RES_H + m * 8192 + w * 2048, tn * 128 + h * 64, tm * 128 + m * 64 + w * 16);
          }
          if (FS != 3 && m && h && elect()) { bulk_commit(); asm volatile("cp.async.bulk.wait_group.read 0;" ::: "memory"); }
        }
        if (!m) PROF(wt == 0, 33);
      }
      PROF(wt == 0, 32);
    }
  }
}

typedef CUresult (*EncodeFn)(CUtensorMap*, CUtensorMapDataType, cuuint32_t, void*, const cuuint64_t*, const cuuint64_t*, const cuuint32_t*,
                             const cuuint32_t*, CUtensorMapInterleave, CUtensorMapSwizzle, CUtensorMapL2promotion, CUtensorMapFloatOOBfill);

void encode(EncodeFn fn, CUtensorMap* m, const void* ptr, int rank, const cuuint64_t* dims, const cuuint64_t* strides, const cuuint32_t* box,
            CUtensorMapSwizzle sw, CUtensorMapDataType dt = CU_TENSOR_MAP_DATA_TYPE_BFLOAT16) {
  const cuuint32_t es[3] = {1, 1, 1};
  fn(m, dt, rank, const_cast<void*>(ptr), dims, strides, box, es, CU_TENSOR_MAP_INTERLEAVE_NONE, sw,
     CU_TENSOR_MAP_L2_PROMOTION_L2_128B, CU_TENSOR_MAP_FLOAT_OOB_FILL_NONE);
}

}

extern "C" void kernel_launch(void* const* d_in, const int* in_sizes, int n_in, void* d_out, int out_size) {
  (void)in_sizes; (void)n_in; (void)out_size;
  EncodeFn fn = nullptr;
  cudaDriverEntryPointQueryResult qr;
  cudaGetDriverEntryPoint("cuTensorMapEncodeTiled", (void**)&fn, cudaEnableDefault, &qr);

  Params p;
  {
    const cuuint64_t dims[2] = {D_, S_}, str[1] = {D_ * 2};
    const cuuint32_t box[2] = {64, 128}, box_st[2] = {64, 16}, box_r[2] = {256, 16};
    encode(fn, &p.xr, d_in[0], 2, dims, str, box_r, CU_TENSOR_MAP_SWIZZLE_NONE);
    encode(fn, &p.x, d_in[0], 2, dims, str, box, CU_TENSOR_MAP_SWIZZLE_128B);
    encode(fn, &p.out, d_out, 2, dims, str, box_st, CU_TENSOR_MAP_SWIZZLE_128B);
  }
  {
    const cuuint64_t dims[3] = {D_, D_, 3}, str[2] = {3 * D_ * 2, D_ * 2};
    const cuuint32_t box[3] = {64, 64, 3};
    encode(fn, &p.w, d_in[1], 3, dims, str, box, CU_TENSOR_MAP_SWIZZLE_128B);
  }
  {
    const cuuint64_t dims[3] = {64, D_, D_ / 64}, str[2] = {D_ * 2, 128};
    const cuuint32_t box[3] = {64, 64, 2};
    encode(fn, &p.wo, d_in[2], 3, dims, str, box, CU_TENSOR_MAP_SWIZZLE_128B);
  }
  {
    const cuuint64_t dims[3] = {F_, D_ / 4, 4}, str[2] = {F_ * 8, F_ * 2};
    const cuuint32_t box[3] = {32, 16, 4};
    encode(fn, &p.gate, d_in[5], 3, dims, str, box, CU_TENSOR_MAP_SWIZZLE_NONE);
    encode(fn, &p.up, d_in[6], 3, dims, str, box, CU_TENSOR_MAP_SWIZZLE_NONE);
  }
  {
    const cuuint64_t dims[3] = {D_ / 4, F_, 2}, str[2] = {D_ * 2, D_};
    const cuuint32_t box[3] = {256, 4, 2};
    encode(fn, &p.down, d_in[7], 3, dims, str, box, CU_TENSOR_MAP_SWIZZLE_NONE, CU_TENSOR_MAP_DATA_TYPE_UINT32);
  }
  void* gs = nullptr;
  cudaGetSymbolAddress(&gs, g_scratch);
  typedef const __nv_bfloat16* bp;
  int dev = 0, sms = 0;
  cudaGetDevice(&dev);
  cudaDeviceGetAttribute(&sms, cudaDevAttrMultiProcessorCount, dev);
  const bool by_sm = BYSM && sms == NGRID;
  const auto kernel = by_sm ? fused_kernel<true> : fused_kernel<false>;
  cudaFuncSetAttribute(kernel, cudaFuncAttributeMaxDynamicSharedMemorySize, SMEM_BYTES);
  kernel<<<by_sm ? NGRID : NCTA, NTHREADS, SMEM_BYTES, cudaStreamPerThread>>>((bp)d_in[0], (Scratch*)gs, (bp)d_in[5], (bp)d_in[6], (bp)d_in[4], (bp)d_in[8], (bp)d_in[7], (__nv_bfloat16*)d_out, p);
}
```

```cpp
#include <cuda_runtime.h>
#include <cuda.h>
#include <cuda_bf16.h>
#include <stdint.h>
#include <stddef.h>
#include <type_traits>

namespace {

constexpr int S_ = 2048, D_ = 1024, F_ = 3584;
constexpr int NCTA = 128, NGRID = 132, NTHREADS = 512;
#define NOMOD 0
constexpr int MOD_CTAS = NOMOD ? 0 : F_ / 32;

#define PRE 2
#define ST1 700
#define RT_G0 2
#define RT_ROT 1
#define RT_SLEEP 500
#define PF_MOD 7
#define MOD_START 9
#define MM 3
#define PO 2
#define A_SLEEP 128
#define KU 99
#define HS 1
#define HOLD 5
#define OWN1 2
#define KF 5
#define QA 3
#define R0 1
#define OA 3
#define QD 0
#define MOD_SLEEP 0
#define MOD_S0 8
#define Y_SLEEP 200
#define PD 0
#define TRY_A 9
#define NAP_A 0
#define VK 1
#define G1 1
#define HP 1
#define FS 0
#define QE 0
#define KA 8
#define KL 3
#define RS 2
#define EARLY_O 0
#define RETRY 1
#define KV_SLEEP_A 64
#define KV_SLEEP 50
#define TL 3
#define EF 2
#define DYN 0
#define FN 0
#define PB 1
#define B_SLEEP 32
#define PW 1
#define HR 0
#define PAIRED 1
#define BYSM 1

constexpr uint32_t SLOT = 16384, WQKV_BYTES = 24576;
constexpr int MOD_BUFS = 3, MOD_BUFS0 = MOD_BUFS + 2;
static_assert(MOD_START + MOD_BUFS0 <= 16, "first FFN round is requested during W1");
constexpr uint32_t OFF_RING = 0, OFF_W1 = 4 * SLOT;
constexpr uint64_t OA_SLOTS = 0x0AB210AB21098210ull, OW_SLOTS = 0x4376543765437654ull;
constexpr uint32_t OFF_RES = OFF_RING + 8 * SLOT, RES_H = SLOT;
constexpr uint32_t OFF_PK = 10 * SLOT;
constexpr uint32_t OFF_V = 11 * SLOT;
constexpr uint32_t OFF_ONES = OFF_V + 9216 + 8192;
constexpr uint32_t MOD_STEP = 9216, OFF_MOD = OFF_V + 2 * MOD_STEP;
constexpr uint32_t OFF_XSEL = OFF_MOD + 8192;
constexpr uint32_t OFF_KVB = OFF_MOD + 2 * MOD_STEP + 8192;
constexpr uint32_t KVB_N = 1056;
constexpr uint32_t OFF_G = OFF_KVB + 4 * KVB_N + 1024;
constexpr uint32_t OFF_PART = OFF_G + 512;
constexpr uint32_t OFF_MISC = OFF_PART + 576;
constexpr uint32_t OFF_BAR = OFF_MISC + 32;
constexpr uint32_t SMEM_BYTES = OFF_BAR + 480;
constexpr uint32_t BAR_FULL = OFF_BAR, BAR_Y = BAR_FULL + 64, BAR_X = BAR_Y + 8, BAR_PEER = BAR_X + 8, BAR_GATE = BAR_PEER + 8, BAR_RT = BAR_GATE + 8,
                   BAR_FIX = BAR_RT,
                   BAR_MFULL = BAR_FIX + 64, BAR_LAND = BAR_FULL,
                   BAR_EMPTY = OFF_BAR + 28 * 8, BAR_OEMPTY = BAR_EMPTY + 64, BAR_RTD = BAR_OEMPTY + 40, BAR_DONE = BAR_RTD + 8,
                   BAR_OWN = BAR_DONE + 8, BAR_PA = BAR_OWN + 8, BAR_PUB = BAR_PA + 8, BAR_MEMPTY = BAR_PUB + 16,
                   BAR_IDX = BAR_MEMPTY + 8,
                   BAR_OFULL = OFF_BAR + 52 * 8;
static_assert(BAR_MFULL + MOD_BUFS0 * 8 <= BAR_EMPTY && BAR_MEMPTY + MOD_BUFS0 * 8 == BAR_OFULL, "barrier groups");
static_assert(SMEM_BYTES <= 232448, "smem");
static_assert(TL == 3 && PRE == 2, "schedule");

constexpr int NB_WG0 = 1, NB_ORDER_12 = 3, NB_ORDER_3O = 4, NB_STG = 5, NB_MODW = 6, NB_KEY = 7, NB_HOLD = 8;

struct Scratch {
  uint4 kv[2][8][3][128];
  float4 y[2][3][128];
  unsigned cnt[32][32];
  unsigned gslot[S_];
  unsigned rslot[8][NCTA];
  unsigned spare[128];
  unsigned block[NCTA];
  uint4 o[16][16][1024];
};
static_assert(offsetof(Scratch, gslot) == NCTA * 56 * 16, "clear size");
__device__ __align__(1024) Scratch g_scratch;

#define PROF(cond, i) do {} while (0)
#define PROF_C(cond, i) do {} while (0)

__device__ __forceinline__ void mbar_init(uint32_t bar, int cnt) { asm volatile("mbarrier.init.shared::cta.b64 [%0], %1;" ::"r"(bar), "r"(cnt)); }
__device__ __forceinline__ void mbar_expect_tx(uint32_t bar, uint32_t bytes) { asm volatile("mbarrier.arrive.expect_tx.shared::cta.b64 _, [%0], %1;" ::"r"(bar), "r"(bytes) : "memory"); }
__device__ __forceinline__ void mbar_arrive(uint32_t bar) { asm volatile("mbarrier.arrive.shared::cta.b64 _, [%0];" ::"r"(bar) : "memory"); }
__device__ __forceinline__ uint32_t peer_addr(uint32_t a) {
  uint32_t r;
  asm volatile("{\n.reg .u32 c;\nmov.u32 c, %%cluster_ctarank;\nxor.b32 c, c, 1;\nmapa.shared::cluster.u32 %0, %1, c;\n}" : "=r"(r) : "r"(a));
  return r;
}
__device__ __forceinline__ void mbar_arrive_peer(uint32_t bar) { asm volatile("mbarrier.arrive.shared::cluster.b64 _, [%0];" ::"r"(bar) : "memory"); }
__device__ __forceinline__ uint32_t mism(uint32_t a, uint32_t b, uint32_t p) {
  uint32_t r; asm("lop3.b32 %0, %1, %2, %3, 0x7E;" : "=r"(r) : "r"(a), "r"(b), "r"(p)); return r;
}
__device__ __forceinline__ bool elect() {
  uint32_t r;
  asm volatile("{\n.reg .pred p;\nelect.sync _|p, 0xffffffff;\nselp.u32 %0, 1, 0, p;\n}" : "=r"(r));
  return r;
}
__device__ __forceinline__ uint32_t fresh_tid() { uint32_t r; asm volatile("mov.u32 %0, %%tid.x;" : "=r"(r)); return r; }
__device__ __forceinline__ void mbar_arrive_warp(uint32_t bar) {
  asm volatile("{\n.reg .pred p;\nelect.sync _|p, 0xffffffff;\n@p mbarrier.arrive.shared::cta.b64 _, [%0];\n}" ::"r"(bar) : "memory");
}
__device__ __forceinline__ void mbar_wait(uint32_t bar, uint32_t parity) {
  asm volatile("{\n.reg .pred p;\nWAIT_L:\nmbarrier.try_wait.parity.shared::cta.b64 p, [%0], %1;\n@p bra DONE_L;\nbra WAIT_L;\nDONE_L:\n}"
               ::"r"(bar), "r"(parity) : "memory");
}
__device__ __forceinline__ uint32_t mbar_try(uint32_t bar, uint32_t parity) {
  uint32_t ok;
  asm volatile("{\n.reg .pred p;\nmbarrier.try_wait.parity.shared::cta.b64 p, [%1], %2;\nselp.u32 %0, 1, 0, p;\n}" : "=r"(ok) : "r"(bar), "r"(parity) : "memory");
  return ok;
}
__device__ __forceinline__ uint32_t mbar_test(uint32_t bar, uint32_t parity) {
  uint32_t ok;
  asm volatile("{\n.reg .pred p;\nmbarrier.test_wait.parity.shared::cta.b64 p, [%1], %2;\nselp.u32 %0, 1, 0, p;\n}" : "=r"(ok) : "r"(bar), "r"(parity) : "memory");
  return ok;
}
constexpr unsigned long long WATCHDOG_NS = 2000000000ull;
__device__ __forceinline__ unsigned long long gtime() { unsigned long long t; asm volatile("mov.u64 %0, %%globaltimer;" : "=l"(t)); return t; }
__device__ __forceinline__ uint32_t clock32() { uint32_t t; asm volatile("mov.u32 %0, %%clock;" : "=r"(t)); return t; }
__device__ __forceinline__ void mbar_wait_bounded(uint32_t bar, uint32_t parity) {
  unsigned long long t0 = 0;
  for (;;) {
    uint32_t ok;
    asm volatile("{\n.reg .pred p;\nmbarrier.try_wait.parity.shared::cta.b64 p, [%1], %2;\nselp.u32 %0, 1, 0, p;\n}" : "=r"(ok) : "r"(bar), "r"(parity) : "memory");
    if (ok) break;
    const unsigned long long t1 = gtime();
    if (t0 == 0) t0 = t1;
    if (t1 - t0 > WATCHDOG_NS) __trap();
  }
}
__device__ __forceinline__ void tma2d(uint32_t dst, const CUtensorMap* m, int c0, int c1, uint32_t bar) {
  asm volatile("cp.async.bulk.tensor.2d.shared::cluster.global.mbarrier::complete_tx::bytes [%0], [%1, {%3, %4}], [%2];"
               ::"r"(dst), "l"(m), "r"(bar), "r"(c0), "r"(c1) : "memory");
}
__device__ __forceinline__ void tma3d(uint32_t dst, const CUtensorMap* m, int c0, int c1, int c2, uint32_t bar) {
  asm volatile("cp.async.bulk.tensor.3d.shared::cluster.global.mbarrier::complete_tx::bytes [%0], [%1, {%3, %4, %5}], [%2];"
               ::"r"(dst), "l"(m), "r"(bar), "r"(c0), "r"(c1), "r"(c2) : "memory");
}
__device__ __forceinline__ void bulk_load(uint32_t dst, const void* src, uint32_t bytes, uint32_t bar) {
  asm volatile("cp.async.bulk.shared::cluster.global.mbarrier::complete_tx::bytes [%0], [%1], %2, [%3];" ::"r"(dst), "l"(src), "r"(bytes), "r"(bar) : "memory");
}
__device__ __forceinline__ void bulk_store(void* dst, uint32_t src, uint32_t bytes) {
  asm volatile("cp.async.bulk.global.shared::cta.bulk_group [%0], [%1], %2;" ::"l"(dst), "r"(src), "r"(bytes) : "memory");
}
__device__ __forceinline__ void st_async4(uint32_t dst, const uint32_t (&v)[4], uint32_t bar) {
  asm volatile("st.async.shared::cluster.mbarrier::complete_tx::bytes.v4.b32 [%0], {%1, %2, %3, %4}, [%5];" ::"r"(dst), "r"(v[0]), "r"(v[1]), "r"(v[2]), "r"(v[3]), "r"(bar) : "memory");
}
__device__ __forceinline__ void bulk_commit() { asm volatile("cp.async.bulk.commit_group;" ::: "memory"); }
__device__ __forceinline__ void bulk_prefetch(const void* p, uint32_t bytes) {
  asm volatile("cp.async.bulk.prefetch.L2.global [%0], %1;" ::"l"(p), "r"(bytes) : "memory");
}
__device__ __forceinline__ void tma2d_store(const CUtensorMap* m, uint32_t src, int c0, int c1) {
  asm volatile("cp.async.bulk.tensor.2d.global.shared::cta.bulk_group [%0, {%2, %3}], [%1];" ::"l"(m), "r"(src), "r"(c0), "r"(c1) : "memory");
}
__device__ __forceinline__ void wg_fence() { asm volatile("wgmma.fence.sync.aligned;" ::: "memory"); }
__device__ __forceinline__ void wg_commit() { asm volatile("wgmma.commit_group.sync.aligned;" ::: "memory"); }
template <int N> __device__ __forceinline__ void wg_wait() { asm volatile("wgmma.wait_group.sync.aligned %0;" ::"n"(N) : "memory"); }
__device__ __forceinline__ void fence_async_smem() { asm volatile("fence.proxy.async.shared::cta;" ::: "memory"); }
__device__ __forceinline__ void fence_async_global() { asm volatile("fence.proxy.async.global;" ::: "memory"); }
__device__ __forceinline__ void fence_release() { asm volatile("fence.release.gpu;" ::: "memory"); }
__device__ __forceinline__ void fence_acquire() { asm volatile("fence.acquire.gpu;" ::: "memory"); }
__device__ __forceinline__ void nb_sync(int id, int n) { asm volatile("bar.sync %0, %1;" ::"r"(id), "r"(n) : "memory"); }
__device__ __forceinline__ void nb_arrive(int id, int n) { asm volatile("bar.arrive %0, %1;" ::"r"(id), "r"(n) : "memory"); }
__device__ __forceinline__ void stsm4(uint32_t addr, uint32_t r0, uint32_t r1, uint32_t r2, uint32_t r3) {
  asm volatile("stmatrix.sync.aligned.m8n8.x4.shared.b16 [%0], {%1, %2, %3, %4};" ::"r"(addr), "r"(r0), "r"(r1), "r"(r2), "r"(r3) : "memory");
}
__device__ __forceinline__ void stsm4t(uint32_t addr, uint32_t r0, uint32_t r1, uint32_t r2, uint32_t r3) {
  asm volatile("stmatrix.sync.aligned.m8n8.x4.trans.shared.b16 [%0], {%1, %2, %3, %4};" ::"r"(addr), "r"(r0), "r"(r1), "r"(r2), "r"(r3) : "memory");
}
__device__ __forceinline__ void st_relaxed4(void* p, const uint32_t (&v)[4]) {
  asm volatile("st.relaxed.gpu.global.v4.u32 [%0], {%1, %2, %3, %4};" ::"l"(p), "r"(v[0]), "r"(v[1]), "r"(v[2]), "r"(v[3]) : "memory");
}
__device__ __forceinline__ void sts128(uint32_t addr, uint32_t a, uint32_t b, uint32_t c, uint32_t d) {
  asm volatile("st.shared.v4.b32 [%0], {%1, %2, %3, %4};" ::"r"(addr), "r"(a), "r"(b), "r"(c), "r"(d) : "memory");
}
__device__ __forceinline__ uint32_t pack2(float lo, float hi) {
  uint32_t r; asm("cvt.rn.bf16x2.f32 %0, %1, %2;" : "=r"(r) : "f"(hi), "f"(lo)); return r;
}
__device__ __forceinline__ float bf_lo(uint32_t v) { return __uint_as_float(v << 16); }
__device__ __forceinline__ float bf_hi(uint32_t v) { return __uint_as_float(v & 0xffff0000u); }
__device__ __forceinline__ float bf_round(float v) { return __bfloat162float(__float2bfloat16_rn(v)); }
__device__ __forceinline__ void ldsm4(uint32_t addr, uint32_t (&r)[4]) {
  asm volatile("ldmatrix.sync.aligned.m8n8.x4.shared.b16 {%0, %1, %2, %3}, [%4];" : "=r"(r[0]), "=r"(r[1]), "=r"(r[2]), "=r"(r[3]) : "r"(addr) : "memory");
}
__device__ __forceinline__ uint4 lds128(uint32_t addr) {
  uint4 v; asm volatile("ld.volatile.shared.v4.u32 {%0, %1, %2, %3}, [%4];" : "=r"(v.x), "=r"(v.y), "=r"(v.z), "=r"(v.w) : "r"(addr) : "memory"); return v;
}
__device__ __forceinline__ uint2 lds64(uint32_t addr) { uint2 v; asm volatile("ld.volatile.shared.v2.u32 {%0, %1}, [%2];" : "=r"(v.x), "=r"(v.y) : "r"(addr) : "memory"); return v; }
__device__ __forceinline__ uint32_t lds32(uint32_t addr) { uint32_t v; asm volatile("ld.volatile.shared.u32 %0, [%1];" : "=r"(v) : "r"(addr) : "memory"); return v; }
__device__ __forceinline__ uint32_t ld_generic(const void* p) { uint32_t v; asm volatile("ld.volatile.u32 %0, [%1];" : "=r"(v) : "l"(p) : "memory"); return v; }
__device__ __forceinline__ void sts32(uint32_t addr, uint32_t v) { asm volatile("st.shared.u32 [%0], %1;" ::"r"(addr), "r"(v) : "memory"); }
__device__ __forceinline__ uint32_t fma_bf2(uint32_t a, uint32_t b, uint32_t c) { uint32_t r; asm("fma.rn.bf16x2 %0, %1, %2, %3;" : "=r"(r) : "r"(a), "r"(b), "r"(c)); return r; }
__device__ __forceinline__ uint32_t mul_bf2(uint32_t a, uint32_t b) { uint32_t r; asm("mul.rn.bf16x2 %0, %1, %2;" : "=r"(r) : "r"(a), "r"(b)); return r; }
__device__ __forceinline__ unsigned ld_relaxed(const unsigned* p) { unsigned v; asm volatile("ld.relaxed.gpu.global.u32 %0, [%1];" : "=r"(v) : "l"(p) : "memory"); return v; }
__device__ __forceinline__ void st_relaxed(unsigned* p, unsigned v) { asm volatile("st.relaxed.gpu.global.u32 [%0], %1;" ::"l"(p), "r"(v) : "memory"); }
__device__ __forceinline__ uint4 ld_relaxed4(const void* p) {
  uint4 v; asm volatile("ld.relaxed.gpu.global.v4.u32 {%0, %1, %2, %3}, [%4];" : "=r"(v.x), "=r"(v.y), "=r"(v.z), "=r"(v.w) : "l"(p) : "memory"); return v;
}
__device__ __forceinline__ float4 ld_relaxed_f4(const void* p) {
  float4 v; asm volatile("ld.relaxed.gpu.global.v4.f32 {%0, %1, %2, %3}, [%4];" : "=f"(v.x), "=f"(v.y), "=f"(v.z), "=f"(v.w) : "l"(p) : "memory"); return v;
}
__device__ __forceinline__ void red_add4(void* p, float a, float b, float c, float d) {
  asm volatile("red.relaxed.gpu.global.add.v4.f32 [%0], {%1, %2, %3, %4};" ::"l"(p), "f"(a), "f"(b), "f"(c), "f"(d) : "memory");
}
__device__ __forceinline__ void red_add_bf(void* p, uint32_t a, uint32_t b, uint32_t c) {
  asm volatile("red.relaxed.gpu.global.add.noftz.v4.bf16x2 [%0], {%1, %2, %3, %4};" ::"l"(p), "r"(a), "r"(b), "r"(c), "r"(0x3F803F80u) : "memory");
}
__device__ __forceinline__ void red_add(unsigned* p, unsigned v) { asm volatile("red.relaxed.gpu.global.add.u32 [%0], %1;" ::"l"(p), "r"(v) : "memory"); }
__device__ __forceinline__ float rcp(float v) { float r; asm("rcp.approx.ftz.f32 %0, %1;" : "=f"(r) : "f"(v)); return r; }
__device__ __forceinline__ float sigmoidf_(float v) { return rcp(1.f + __expf(-v)); }
__device__ __forceinline__ uint32_t phi2(float a, float b, float l2e = 1.4426950408889634f) {
  float ea, eb;
  asm("ex2.approx.ftz.f32 %0, %1;" : "=f"(ea) : "f"(a * l2e));
  asm("ex2.approx.ftz.f32 %0, %1;" : "=f"(eb) : "f"(b * l2e));
  uint32_t t = pack2(a, b), e = pack2(ea, eb), r;
  asm("max.NaN.bf16x2 %0, %0, %1;" : "+r"(t) : "r"(0x35863586u));
  asm("min.bf16x2 %0, %0, %1;" : "+r"(e) : "r"(0x3F803F80u));
  asm("add.rn.bf16x2 %0, %1, %2;" : "=r"(r) : "r"(t), "r"(e));
  return r;
}
__device__ __forceinline__ uint64_t mkdesc(uint32_t addr, uint32_t lbo, uint32_t sbo, uint32_t sw) {
  return (uint64_t)(((addr & 0x3FFFF) >> 4) | ((lbo >> 4) << 16)) | ((uint64_t)((sbo >> 4) | (sw << 30)) << 32);
}

template <int TA, int TB>
__device__ __forceinline__ void mma128(float (&d)[64], uint64_t da, uint64_t db, int sc) {
  asm volatile("{\n.reg .pred p;\nsetp.ne.b32 p, %66, 0;\n"
    "wgmma.mma_async.sync.aligned.m64n128k16.f32.bf16.bf16 "
    "{%0,%1,%2,%3,%4,%5,%6,%7,%8,%9,%10,%11,%12,%13,%14,%15,%16,%17,%18,%19,%20,%21,%22,%23,"
    "%24,%25,%26,%27,%28,%29,%30,%31,%32,%33,%34,%35,%36,%37,%38,%39,%40,%41,%42,%43,%44,%45,%46,%47,"
    "%48,%49,%50,%51,%52,%53,%54,%55,%56,%57,%58,%59,%60,%61,%62,%63}, "
    "%64, %65, p, 1, 1, %67, %68;\n}\n"
    : "+f"(d[0]), "+f"(d[1]), "+f"(d[2]), "+f"(d[3]), "+f"(d[4]), "+f"(d[5]), "+f"(d[6]), "+f"(d[7]),
      "+f"(d[8]), "+f"(d[9]), "+f"(d[10]), "+f"(d[11]), "+f"(d[12]), "+f"(d[13]), "+f"(d[14]), "+f"(d[15]),
      "+f"(d[16]), "+f"(d[17]), "+f"(d[18]), "+f"(d[19]), "+f"(d[20]), "+f"(d[21]), "+f"(d[22]), "+f"(d[23]),
      "+f"(d[24]), "+f"(d[25]), "+f"(d[26]), "+f"(d[27]), "+f"(d[28]), "+f"(d[29]), "+f"(d[30]), "+f"(d[31]),
      "+f"(d[32]), "+f"(d[33]), "+f"(d[34]), "+f"(d[35]), "+f"(d[36]), "+f"(d[37]), "+f"(d[38]), "+f"(d[39]),
      "+f"(d[40]), "+f"(d[41]), "+f"(d[42]), "+f"(d[43]), "+f"(d[44]), "+f"(d[45]), "+f"(d[46]), "+f"(d[47]),
      "+f"(d[48]), "+f"(d[49]), "+f"(d[50]), "+f"(d[51]), "+f"(d[52]), "+f"(d[53]), "+f"(d[54]), "+f"(d[55]),
      "+f"(d[56]), "+f"(d[57]), "+f"(d[58]), "+f"(d[59]), "+f"(d[60]), "+f"(d[61]), "+f"(d[62]), "+f"(d[63])
    : "l"(da), "l"(db), "r"(sc), "n"(TA), "n"(TB));
}

__device__ __forceinline__ void mma_ktv(float (&d)[36], const uint32_t (&a)[4], uint64_t db, int sc) {
  asm volatile("{\n.reg .pred p;\nsetp.ne.b32 p, %41, 0;\n"
    "wgmma.mma_async.sync.aligned.m64n72k16.f32.bf16.bf16 "
    "{%0,%1,%2,%3,%4,%5,%6,%7,%8,%9,%10,%11,%12,%13,%14,%15,%16,%17,%18,%19,%20,%21,%22,%23,"
    "%24,%25,%26,%27,%28,%29,%30,%31,%32,%33,%34,%35}, "
    "{%36,%37,%38,%39}, %40, p, 1, 1, 0;\n}\n"
    : "+f"(d[0]), "+f"(d[1]), "+f"(d[2]), "+f"(d[3]), "+f"(d[4]), "+f"(d[5]), "+f"(d[6]), "+f"(d[7]),
      "+f"(d[8]), "+f"(d[9]), "+f"(d[10]), "+f"(d[11]), "+f"(d[12]), "+f"(d[13]), "+f"(d[14]), "+f"(d[15]),
      "+f"(d[16]), "+f"(d[17]), "+f"(d[18]), "+f"(d[19]), "+f"(d[20]), "+f"(d[21]), "+f"(d[22]), "+f"(d[23]),
      "+f"(d[24]), "+f"(d[25]), "+f"(d[26]), "+f"(d[27]), "+f"(d[28]), "+f"(d[29]), "+f"(d[30]), "+f"(d[31]),
      "+f"(d[32]), "+f"(d[33]), "+f"(d[34]), "+f"(d[35])
    : "r"(a[0]), "r"(a[1]), "r"(a[2]), "r"(a[3]), "l"(db), "r"(sc));
}

__device__ __forceinline__ void mma_qkvz(float (&d)[20], uint64_t da, uint64_t db, int sc) {
  asm volatile("{\n.reg .pred p;\nsetp.ne.b32 p, %22, 0;\n"
    "wgmma.mma_async.sync.aligned.m64n40k16.f32.bf16.bf16 "
    "{%0,%1,%2,%3,%4,%5,%6,%7,%8,%9,%10,%11,%12,%13,%14,%15,%16,%17,%18,%19}, "
    "%20, %21, p, 1, 1, 0, 1;\n}\n"
    : "+f"(d[0]), "+f"(d[1]), "+f"(d[2]), "+f"(d[3]), "+f"(d[4]), "+f"(d[5]), "+f"(d[6]), "+f"(d[7]),
      "+f"(d[8]), "+f"(d[9]), "+f"(d[10]), "+f"(d[11]), "+f"(d[12]), "+f"(d[13]), "+f"(d[14]), "+f"(d[15]),
      "+f"(d[16]), "+f"(d[17]), "+f"(d[18]), "+f"(d[19])
    : "l"(da), "l"(db), "r"(sc));
}

template <int N> __device__ __forceinline__ void pin(float (&d)[N]) {
#pragma unroll
  for (int i = 0; i < N; i++) asm volatile("" : "+f"(d[i])::"memory");
}

struct Params {
  CUtensorMap x, w, xr, gate, up, wo, out, down;
};

__device__ __forceinline__ uint32_t dup_lo(uint32_t v) { uint32_t r; asm("{\n.reg .b16 l, h;\nmov.b32 {l, h}, %1;\nmov.b32 %0, {l, l};\n}" : "=r"(r) : "r"(v)); return r; }
__device__ __forceinline__ uint32_t dup_hi(uint32_t v) { uint32_t r; asm("{\n.reg .b16 l, h;\nmov.b32 {l, h}, %1;\nmov.b32 %0, {h, h};\n}" : "=r"(r) : "r"(v)); return r; }
__device__ __forceinline__ float butterfly8(float (&s)[8], int lane, int o) {
#pragma unroll
  for (int k = 1; k < 8; k <<= 1) {
    const bool up = lane & (o * k);
#pragma unroll
    for (int j = 0; j < 4 / k; j++) s[j] = (up ? s[2 * j + 1] : s[2 * j]) + __shfl_xor_sync(~0u, up ? s[2 * j] : s[2 * j + 1], o * k);
  }
  return s[0];
}
constexpr int OWN = 8, PEER = 9;
static_assert((OA_SLOTS >> OWN * 4 & 15) * SLOT == OFF_V && (OA_SLOTS >> PEER * 4 & 15) * SLOT == OFF_PK, "");
template <int B> __device__ __forceinline__ void verify_tiles(uint32_t sb, Scratch* gs, int tm, int tn, int w, int lane) {
  const uint32_t par = lds32(sb + OFF_MISC + 24), fix = sb + BAR_FIX + (B * 4 + w) * 8;
  uint32_t slots = (uint32_t)(OA_SLOTS >> B * 40);
#pragma unroll 1
  for (int i = 0; i < 8 - 2 * B; i++, slots >>= 4) {
    const uint32_t a = sb + OFF_RING + (slots & 15) * SLOT + w * 1024, cw = a + lane * 32 + (lane >> 2) * 4;
    if (!B && i == 4) mbar_wait(sb + BAR_EMPTY + 7 * 8, 1);
    mbar_wait(sb + BAR_LAND + i * 8, B);
    for (;;) {
      const uint32_t u0 = lds32(cw), u1 = lds32(cw + 4096), u2 = lds32(cw + 8192), u3 = lds32(cw + 12288);
      if (__all_sync(~0u, !(mism(mism(u0, u1, par), mism(u2, u3, par), 0) & 1))) break;
      const uint4* src = gs->o[tm][!B ? i : DYN ? lds32(sb + OFF_MISC + (i & 4)) >> (i & 3) * 8 & 15 : i < (tn & 6) ? i + 8 : i + 10] + w * 64;
      const uint32_t ph = !mbar_test(fix, 1);
      fence_async_smem();
      __syncwarp();
      if (elect()) {
        mbar_expect_tx(fix, 4096);
#pragma unroll 1
        for (int j = 0; j < 4; j++) bulk_load(a + j * 4096, src + j * 256, 1024, fix);
      }
      mbar_wait(fix, ph);
    }
    mbar_arrive_warp(sb + BAR_OFULL + (i < 5 ? i : i - 5) * 8);
  }
}
template <bool BY_SM> struct Tile {
  int sm, tm, tn, mu;
  bool spare;
  __device__ __forceinline__ Tile() {
    if (BY_SM) asm volatile("mov.u32 %0, %%smid;" : "=r"(sm));
    else sm = blockIdx.x + (blockIdx.x >= 120) * 4;
    const int tp = sm >> 1, pr = sm & 1;
    const int v = tp < 32 ? tp : tp < 60 ? (tp * 293 - 928) >> 8 : tp * 8 - 464, g = v & 7, i = v >> 3;
    tm = (v & 6) * 2 + (i & 3); tn = (v & 1) * 4 + (v >> 4 & 2) + pr;
    mu = i == 5 ? 112 : g * 14 + (i - (i > 5)) * 2 + pr;
    spare = (tp | 1) == 61;
  }
};

template <bool BY_SM> __global__ void __cluster_dims__(2, 1, 1) __launch_bounds__(NTHREADS, 1) fused_kernel(const __nv_bfloat16* __restrict__ px, Scratch* gs, const __nv_bfloat16* __restrict__ w_gate,
             const __nv_bfloat16* __restrict__ w_up, const __nv_bfloat16* __restrict__ w_r, const __nv_bfloat16* __restrict__ gate_w, const __nv_bfloat16* __restrict__ w_down, __nv_bfloat16* __restrict__ pout,
             const __grid_constant__ Params p) {
  extern __shared__ __align__(1024) uint8_t smem[];
  const uint32_t sb = __shfl_sync(~0u, (uint32_t)__cvta_generic_to_shared(smem), 0);
  const int tid = threadIdx.x, lane = tid & 31;
  const int warp = __shfl_sync(~0u, tid >> 5, 0), wg = warp >> 2;
  const uint32_t t_start = clock32();
  const Tile<BY_SM> tile;
  const int tm = tile.tm, tn = tile.tn, mu = tile.mu, cta = tm * 8 + tn;
  const uint32_t zero = tile.sm >> 12;
  if (warp == 0) {
#pragma unroll
    for (int s = 0; s < PRE; s++)
      if (elect()) mbar_init(sb + BAR_FULL + s * 8, 1);
    asm volatile("fence.mbarrier_init.release.cluster;" ::: "memory");
    if (!tile.spare) {
#pragma unroll
      for (int s = 0; s < PRE; s++) {
        if (elect()) tma3d(sb + OFF_W1 + s * WQKV_BYTES, &p.w, tn * 64, s * 64, 0, sb + BAR_FULL + s * 8);
        if (elect()) tma2d(sb + OFF_RING + s * SLOT, &p.x, s * 64, tm * 128, sb + BAR_FULL + s * 8);
        PROF(lane == 0, 64 + s);
      }
      if (elect()) {
#pragma unroll
        for (int s = 0; s < PRE; s++) mbar_expect_tx(sb + BAR_FULL + s * 8, SLOT + WQKV_BYTES);
      }
    }
  }
  if (warp) {
    const int wi = warp == 15 ? 0 : warp;
    const int cnt = wi < 7 ? 1 : wi < 13 ? 4 : 5;
#pragma unroll
    for (int i = 0; i < 4; i++)
      if ((i >= PRE || wi) && elect()) mbar_init(sb + OFF_BAR + wi * 32 + i * 8, cnt);
    asm volatile("fence.mbarrier_init.release.cluster;" ::: "memory");
  }
  __syncthreads();
  if (tile.spare) {
    if (warp == 0) {
      const unsigned tag = (ld_relaxed(&gs->spare[tile.sm & 3]) + 1) & 0xFFF;
      const unsigned long long t0 = gtime();
      uint4 r4;
      do {
        __nanosleep(2048);
        if (gtime() - t0 > WATCHDOG_NS) __trap();
        r4 = ld_relaxed4(&gs->rslot[tile.sm & 3][lane * 4]);
      } while (!__all_sync(~0u, (((r4.x ^ tag) | (r4.y ^ tag) | (r4.z ^ tag) | (r4.w ^ tag)) & 0xFFF) == 0));
      if (tid == 0) st_relaxed(&gs->spare[tile.sm & 3], tag);
    }
    return;
  }

  if (wg == 3) {
    asm volatile("setmaxnreg.dec.sync.aligned.u32 24;");
    if (warp == 12) {
      mbar_wait(sb + BAR_PUB, 0);
      while (!__all_sync(~0u, ld_relaxed(gs->cnt[tm]) == 0x44444444u)) __nanosleep(A_SLEEP);
      if (FN) { fence_acquire(); fence_async_global(); }
      PROF(lane == 0, 7);
      mbar_wait(sb + BAR_GATE, 0);
      uint32_t slots = (uint32_t)OA_SLOTS, deps = 0xA9877654u;
#pragma unroll 1
      for (int i = 0; i < 8; i++, deps >>= 4, slots >>= 4) {
        mbar_wait(sb + BAR_EMPTY + (deps & 15) * 8, i < 5);
        if (elect()) bulk_load(sb + OFF_RING + (slots & 15) * SLOT, gs->o[tm][i], SLOT, sb + BAR_LAND + i * 8);
        if (elect()) mbar_expect_tx(sb + BAR_LAND + i * 8, SLOT);
        PROF(lane == 0, 44 + i);
      }
      slots = (uint32_t)(OA_SLOTS >> 40);
      uint32_t ws = (uint32_t)(OW_SLOTS >> 40), todo = 0x44444444u ^ 0x44u << (tn & 6) * 4, seen = 0, st = 0;
      mbar_wait(sb + BAR_PUB + 8, 0);
#pragma unroll 1
      for (int i = 0; i < 6; i++, slots >>= 4, ws >>= 4) {
        const uint32_t need = DYN ? todo : todo & -todo;
        if (!(seen & need)) {
          while (!((seen = __shfl_sync(~0u, ld_relaxed(gs->cnt[16 + tm]), 0)) & need)) __nanosleep(B_SLEEP);
          if (FN) { fence_acquire(); fence_async_global(); }
        }
        const uint32_t bit = seen & need & -(seen & need), slab = 8 + ((31 - __clz(bit)) >> 2);
        todo ^= bit;
        if (DYN && elect()) asm volatile("st.shared.u8 [%0], %1;" ::"r"(sb + OFF_MISC + i), "r"(slab) : "memory");
        mbar_wait(sb + BAR_OEMPTY + st * 8, i < 5);
        if (elect()) bulk_load(sb + OFF_RING + (slots & 15) * SLOT, gs->o[tm][slab], SLOT, sb + BAR_LAND + i * 8);
        if (DYN && elect()) tma3d(sb + OFF_RING + (ws & 15) * SLOT, &p.wo, 0, slab * 64, tn * 2, sb + BAR_OFULL + st * 8);
        if (elect()) mbar_expect_tx(sb + BAR_LAND + i * 8, SLOT);
        if (DYN && elect()) mbar_expect_tx(sb + BAR_OFULL + st * 8, SLOT);
        PROF(lane == 0, 54 + i);
        st = st == 4 ? 0 : st + 1;
      }
    } else if (warp == 13) {
#pragma unroll 1
      for (int g = PRE; g < 32; g++) {
        const bool reuse = (g >> 2) == 4;
        const uint32_t s = g & 3, full = sb + BAR_FULL + (g & 7) * 8, c0 = tn * 64 + (g & 16) * 32, c1 = (g < 16 ? g : g - 4 & 15) * 64;
        if (g < 4) while ((int)(clock32() - t_start) < g * ST1) {}
        mbar_wait(sb + BAR_EMPTY + (g + 4 & 7) * 8, (g + 4 >> 3 & 1) ^ 1);
        if (!reuse && elect()) tma2d(sb + OFF_RING + s * SLOT, &p.x, c1, tm * 128, full);
        if (elect()) tma3d(sb + OFF_W1 + s * WQKV_BYTES, &p.w, c0, c1, 0, full);
        if (elect()) mbar_expect_tx(full, reuse ? WQKV_BYTES : SLOT + WQKV_BYTES);
        PROF(lane == 0, 64 + g);
        const uint32_t i = g - RT_G0;
        if (i < 4 && elect()) {
          mbar_expect_tx(sb + BAR_RT + i * 8, i ? 8192 : 8192 + 4096);
          tma2d(sb + OFF_PK + i * 8192 + (i == 3) * 1024, &p.xr, ((i + RT_ROT) & 3) * 256, cta * 16, sb + BAR_RT + i * 8);
          if (i == 0) { bulk_load(sb + OFF_KVB, w_r, 2048, sb + BAR_RT); bulk_load(sb + OFF_KVB + 2048, gate_w, 2048, sb + BAR_RT); }
        }
        const uint32_t c = g - MOD_START;
        if (c == MOD_BUFS) mbar_wait(sb + BAR_RTD, 0);
        if (c < MOD_BUFS0 && mu < MOD_CTAS && elect()) {
          PROF(true, 192 + c);
          const uint32_t mb = c < MOD_BUFS ? c + 2 : c - MOD_BUFS, mfull = sb + BAR_MFULL + mb * 8, mdst = sb + OFF_V + mb * MOD_STEP;
          mbar_expect_tx(mfull, c ? 8192 : 8192 + 2048);
          tma3d(mdst, &p.gate, mu * 32, c * 16, 0, mfull); tma3d(mdst + 4096, &p.up, mu * 32, c * 16, 0, mfull);
        }
        const uint32_t pc = g - PF_MOD;
        if (pc < 16 && elect()) bulk_prefetch((cta & 64 ? w_up : w_gate) + (size_t)(pc * 64 + (cta & 63)) * F_, F_ * 2);
      }
      mbar_arrive_warp(sb + BAR_GATE);
      const uint32_t lowb = (1u << (tn & 6) * 4) - 1;
      uint64_t slabs = (uint64_t)((0xFEDCBA98u & lowb) | (0xFEDCBAu & ~lowb)) << 40 | (uint64_t)(8 + (tn ^ 1)) << 36 | (uint64_t)(8 + tn) << 32 | 0x76543210u;
      uint64_t deps = 0x8CBA98CBA9876554ull, ws = OW_SLOTS;
      uint32_t full = sb + BAR_OFULL, ph = 1;
#pragma unroll 1
      for (int g = 0; g < (DYN ? 10 : 16); g++, slabs >>= 4, deps >>= 4, ws >>= 4) {
        mbar_wait(sb + BAR_EMPTY + ((uint32_t)deps & 15) * 8, ph);
        if (elect()) tma3d(sb + OFF_RING + ((uint32_t)ws & 15) * SLOT, &p.wo, 0, ((uint32_t)slabs & 15) * 64, tn * 2, full);
        if (elect()) mbar_expect_tx(full, SLOT);
        PROF(lane == 0, 96 + g);
        if (g >> 1 == OWN / 2 && lane < 4) mbar_arrive(full);
        if (DYN && g == PW && tm < 8 && elect())
          asm volatile("cp.async.bulk.prefetch.tensor.3d.L2.global [%0, {%1, %2, %3}];" ::"l"(&p.wo), "r"(0), "r"((8 + tm) * 64), "r"(tn * 2) : "memory");
        full += 8;
        if (full == sb + BAR_OFULL + 40) { full -= 40; ph ^= 1; }
      }
    } else if (warp == 14) {
      if (mu < MOD_CTAS) {
        uint32_t full = sb + BAR_MFULL + 16, dst = sb + OFF_MOD, ph = 0;
#pragma unroll 1
        for (int c = MOD_BUFS0; c < 24; c++) {
          mbar_wait(full + (BAR_MEMPTY - BAR_MFULL), ph);
          PROF(lane == 0, 192 + c);
          if (c < 16) {
            if (elect()) { tma3d(dst, &p.gate, mu * 32, c * 16, 0, full); tma3d(dst + 4096, &p.up, mu * 32, c * 16, 0, full); }
          } else if (elect()) tma3d(dst, &p.down, 0, mu * 32 + (c - 16) * 4, 0, full);
          if (elect()) mbar_expect_tx(full, 8192);
          if (PD && (uint32_t)(c + PD - 16) < 8 && elect()) bulk_prefetch(w_down + (size_t)(mu * 32 + (c + PD - 16) * 4) * D_, 8192);
          full += 8; dst += MOD_STEP;
          if (full == sb + BAR_MFULL + MOD_BUFS0 * 8) { full -= MOD_BUFS * 8; dst = sb + OFF_MOD; ph ^= 1; }
        }
      }
      if (elect()) {
      mbar_wait(sb + BAR_IDX, 0);
      const bool paired = PAIRED && ld_relaxed(&gs->block[cta ^ 1]) == (blockIdx.x ^ 1);
      if (paired) mbar_expect_tx(sb + BAR_PEER, SLOT);
      mbar_expect_tx(sb + BAR_X, 32768);
      mbar_wait(sb + BAR_OEMPTY + 3 * 8, 0);
      tma2d(sb + OFF_RES, &p.x, tn * 128, tm * 128, sb + BAR_X);
      mbar_wait(sb + BAR_OEMPTY + 4 * 8, 0);
      tma2d(sb + OFF_RES + RES_H, &p.x, tn * 128 + 64, tm * 128, sb + BAR_X);
      if (!paired) {
        mbar_wait(sb + BAR_OWN, 0);
        while (!(ld_relaxed(gs->cnt[16 + tm]) & 4u << (tn ^ 1) * 4)) __nanosleep(32);
        fence_acquire();
        fence_async_global();
        const uint32_t par = lds32(sb + OFF_MISC + 24);
        for (uint32_t ph = !mbar_test(sb + BAR_MFULL, 1), bad = 1; bad & 1; ph ^= 1) {
          fence_async_smem();
          mbar_expect_tx(sb + BAR_MFULL, SLOT);
          bulk_load(sb + OFF_PK, gs->o[tm][8 + (tn ^ 1)], SLOT, sb + BAR_MFULL);
          mbar_wait(sb + BAR_MFULL, ph);
          bad = 0;
#pragma unroll 1
          for (int i = 0; i < 512; i++) bad |= lds32(sb + OFF_PK + i * 32 + (i & 28)) ^ par;
        }
        mbar_arrive(sb + BAR_PEER);
      }
      }
    } else {
#pragma unroll 1
      for (int i = 2; i < 8; i++)
        if (elect()) asm volatile("prefetch.tensormap [%0];" ::"l"(&p.x + i) : "memory");
      mbar_wait_bounded(sb + BAR_DONE, 0);
    }
  } else if (wg == 2) {
    asm volatile("setmaxnreg.dec.sync.aligned.u32 40;");
    const int mw = warp & 3;
    if (mw == 0) {
      const unsigned tag = (ld_relaxed(&gs->rslot[tn][cta]) + 1) & 0xFFF;
#pragma unroll
      for (int i = 0; i < 2; i++)
        if (lane < 28) ((float4*)gs)[cta * 56 + i * 28 + lane] = make_float4(0.f, 0.f, 0.f, 0.f);
      if (lane == 29) gs->block[cta] = blockIdx.x;
      fence_release();
      nb_sync(NB_KEY, 160);
      const uint4 k4 = lds128(sb + OFF_MISC);
      if (lane < 8) st_relaxed(&gs->rslot[lane][cta], max(max(k4.x, k4.y), max(k4.z, k4.w)) | tag);
      if (lane < 16) st_relaxed(&gs->gslot[cta * 16 + lane], lds32(sb + OFF_G + lane * 4) | tag);
      PROF(lane == 0, 20);
      uint4 r4;
      do {
        __nanosleep(RT_SLEEP);
        r4 = ld_relaxed4(&gs->rslot[tn][lane * 4]);
      } while (!__all_sync(~0u, (((r4.x ^ tag) | (r4.y ^ tag) | (r4.z ^ tag) | (r4.w ^ tag)) & 0xFFF) == 0));
      const int c0 = 0xFFF0 - lane * 64;
      unsigned key = max(max((r4.x & 0xFFFF0000u) | (c0 + ((r4.x >> 12) & 15)), (r4.y & 0xFFFF0000u) | (c0 - 16 + ((r4.y >> 12) & 15))),
                         max((r4.z & 0xFFFF0000u) | (c0 - 32 + ((r4.z >> 12) & 15)), (r4.w & 0xFFFF0000u) | (c0 - 48 + ((r4.w >> 12) & 15))));
      key = __reduce_max_sync(~0u, key);
      if (elect()) {
        sts32(sb + OFF_MISC + 16, key);
        sts32(sb + OFF_MISC + 24, tag & 1);
        if (mu < MOD_CTAS) {
          const __nv_bfloat16* row = px + (size_t)(0xFFFF - (key & 0xFFFF)) * D_;
          bulk_load(sb + OFF_XSEL, row, 1024, sb + BAR_MFULL + 16);
          bulk_load(sb + OFF_XSEL + MOD_STEP, row + 512, 1024, sb + BAR_MFULL + 16);
        }
      }
      PROF(lane == 0, 21);
      do {
        r4 = ld_relaxed4(&gs->gslot[tm * 128 + lane * 4]);
      } while (!__all_sync(~0u, (((r4.x ^ tag) | (r4.y ^ tag) | (r4.z ^ tag) | (r4.w ^ tag)) & 0xFFF) == 0));
      sts128(sb + OFF_G + lane * 16, r4.x & 0xFFFF0000u, r4.y & 0xFFFF0000u, r4.z & 0xFFFF0000u, r4.w & 0xFFFF0000u);
      fence_acquire();
      __syncwarp();
    }
    PROF(tid == 256, 22);
    if (mu >= MOD_CTAS) {
      mbar_arrive_warp(sb + BAR_IDX);
    } else {
      const uint32_t wp = sb + OFF_V + (mw >> 1) * 4096 + (mw & 1) * 512 + lane * 16;
      uint32_t mp = sb + OFF_XSEL + (mw & 1) * 64 + (lane >> 2) * 8, mc = 128;
      float acc[8] = {0.f, 0.f, 0.f, 0.f, 0.f, 0.f, 0.f, 0.f};
      uint32_t b = 2, ph = 0;
#pragma unroll 1
      for (int c = 0; c < 24; c++) {
        if (MOD_SLEEP && c >= MOD_S0) __nanosleep(MOD_SLEEP);
        mbar_wait(sb + BAR_MFULL + b * 8, ph);
        PROF_C(tid == 256, 216 + c);
        const uint32_t a = wp + b * MOD_STEP;
        const uint2 m = lds64(mp);
        const uint4 w0 = lds128(a), w1 = lds128(a + 1024), w2 = lds128(a + 2048), w3 = lds128(a + 3072);
        mp += c == 7 ? MOD_STEP - 1024 + 128 : mc;
        const uint32_t m0 = dup_lo(m.x), m1 = dup_hi(m.x), m2 = dup_lo(m.y), m3 = dup_hi(m.y);
        uint4 q = make_uint4(mul_bf2(w0.x, m0), mul_bf2(w0.y, m0), mul_bf2(w0.z, m0), mul_bf2(w0.w, m0));
        q = make_uint4(fma_bf2(w1.x, m1, q.x), fma_bf2(w1.y, m1, q.y), fma_bf2(w1.z, m1, q.z), fma_bf2(w1.w, m1, q.w));
        q = make_uint4(fma_bf2(w2.x, m2, q.x), fma_bf2(w2.y, m2, q.y), fma_bf2(w2.z, m2, q.z), fma_bf2(w2.w, m2, q.w));
        mbar_arrive_warp(sb + BAR_MEMPTY + b * 8 + (w3.x & zero));
        q = make_uint4(fma_bf2(w3.x, m3, q.x), fma_bf2(w3.y, m3, q.y), fma_bf2(w3.z, m3, q.z), fma_bf2(w3.w, m3, q.w));
        if (++b == 5) b = c < 3 ? 0 : 2;
        if (b == 2) ph ^= 1;
        acc[0] += bf_lo(q.x); acc[1] += bf_hi(q.x); acc[2] += bf_lo(q.y); acc[3] += bf_hi(q.y);
        acc[4] += bf_lo(q.z); acc[5] += bf_hi(q.z); acc[6] += bf_lo(q.w); acc[7] += bf_hi(q.w);
        if (c == 15) {
          const uint32_t ft = fresh_tid(), fl = ft & 31;
          sts32(sb + OFF_PART + (ft & 96) * 4 + ((ft & 3) * 8 + (fl >> 2)) * 4, __float_as_uint(butterfly8(acc, fl, 4)));
          nb_sync(NB_MODW, 128);
          const float* part = (const float*)(smem + OFF_PART) + fl;
          const float gp = bf_round(part[0] + part[32]), up = bf_round(part[64] + part[96]);
          *(__nv_bfloat16*)(smem + OFF_PART + 512 + fl * 2) = __float2bfloat16_rn(bf_round(gp * sigmoidf_(gp)) * up);
          __syncwarp();
          mp = sb + OFF_PART + 512; mc = 8;
#pragma unroll
          for (int i = 0; i < 8; i++) acc[i] = 0.f;
          PROF(lane == 0 && mw == 0, 23);
        }
      }
      float4* yacc = gs->y[tn & 1][0] + (fresh_tid() & 127);
      red_add4(yacc, acc[0], acc[1], acc[2], 1.f);
      red_add4(yacc + 128, acc[3], acc[4], acc[5], 1.f);
      red_add4(yacc + 256, acc[6], acc[7], 0.f, 1.f);
      PROF(lane == 0 && mw == 0, 25);
    }
    mbar_wait(sb + BAR_GATE, 0);
    mbar_wait(sb + BAR_IDX, 0);
    verify_tiles<0>(sb, gs, tm, tn, mw, lane);
    const unsigned key = lds32(sb + OFF_MISC + 16);
    const int sel = 0xFFFF - (int)(key & 0xFFFF) - tm * 128;
    if (mw == 0 && sel >= 0 && sel < 128) {
      const unsigned k16 = key >> 16;
      const float rs = bf_round(sigmoidf_(__uint_as_float(((k16 & 0x8000u) ? (k16 & 0x7FFFu) : (~k16 & 0xFFFFu)) << 16)));
      float v[12];
      const float4* yp = gs->y[lane >> 4][0] + tn * 16 + (lane & 15);
      for (;;) {
#pragma unroll
        for (int i = 0; i < 3; i++) {
          const float4 u = ld_relaxed_f4(yp + i * 128);
          v[4 * i] = u.x; v[4 * i + 1] = u.y; v[4 * i + 2] = u.z; v[4 * i + 3] = u.w;
        }
        const float n = v[3] + v[7] + v[11];
        if (__all_sync(~0u, n + __shfl_xor_sync(~0u, n, 16) == 3.f * MOD_CTAS)) break;
        __nanosleep(Y_SLEEP);
      }
#pragma unroll
      for (int i = 0; i < 10; i++) v[i] = bf_round(bf_round(v[i] + __shfl_xor_sync(~0u, v[i], 16)) * rs);
      PROF(lane == 0, 24);
      mbar_wait(sb + BAR_X, 0);
      if (lane < 16) {
        uint4* xp = (uint4*)(smem + OFF_RES + (lane >> 3) * RES_H + sel * 128 + (((lane ^ sel) & 7) << 4));
        const uint4 xv = *xp;
        *xp = make_uint4(pack2(bf_lo(xv.x) + v[0], bf_hi(xv.x) + v[1]), pack2(bf_lo(xv.y) + v[2], bf_hi(xv.y) + v[4]),
                         pack2(bf_lo(xv.z) + v[5], bf_hi(xv.z) + v[6]), pack2(bf_lo(xv.w) + v[8], bf_hi(xv.w) + v[9]));
      }
      __syncwarp();
      mbar_arrive_warp(sb + BAR_Y);
    }
  } else {
    asm volatile("setmaxnreg.inc.sync.aligned.u32 224;");
    const int w = warp & 3, wt = tid & 127;
    const int nb_self = NB_WG0 + wg;
    const uint64_t da0 = mkdesc(sb + OFF_RING, 16, 1024, 1), db0 = mkdesc(sb + OFF_RING, 8192, 1024, 1);

    if (wg == 1) {
      sts128(sb + OFF_ONES - (w >> 1) * 9216 + (w & 1) * 512 + lane * 16, 0x3F803F80u, 0x3F803F80u, 0x3F803F80u, 0x3F803F80u);
      sts32(sb + OFF_MISC + 20, 0x3FB8AA3Bu);
      fence_async_smem();
      float s[8] = {0.f, 0.f, 0.f, 0.f, 0.f, 0.f, 0.f, 0.f};
      uint32_t mask = 0xffff0000u;
#pragma unroll 1
      for (int i = 0; i < 4; i++) {
        const uint32_t u = (i + RT_ROT) & 3;
        mbar_wait(sb + BAR_RT + i * 8, 0);
        const uint4 wr = lds128(sb + OFF_KVB + u * 512 + lane * 16), gw = lds128(sb + OFF_KVB + 2048 + u * 512 + lane * 16);
        uint4 xv[4];
#pragma unroll
        for (int r = 0; r < 4; r++) xv[r] = lds128(sb + OFF_PK + i * 8192 + (i == 3) * 1024 + (w * 4 + r) * 512 + lane * 16);
        const float wf[16] = {bf_lo(wr.x), bf_hi(wr.x), bf_lo(wr.y), bf_hi(wr.y), bf_lo(wr.z), bf_hi(wr.z), bf_lo(wr.w), bf_hi(wr.w),
                              bf_lo(gw.x), bf_hi(gw.x), bf_lo(gw.y), bf_hi(gw.y), bf_lo(gw.z), bf_hi(gw.z), bf_lo(gw.w), bf_hi(gw.w)};
#pragma unroll
        for (int r = 0; r < 4; r++) {
          const uint4 xq = xv[r];
          const float xf[8] = {bf_lo(xq.x), __uint_as_float(xq.x & mask), bf_lo(xq.y), bf_hi(xq.y), bf_lo(xq.z), bf_hi(xq.z), bf_lo(xq.w), bf_hi(xq.w)};
#pragma unroll
          for (int j = 0; j < 8; j++) { s[2 * r] = fmaf(xf[j ^ 1], wf[j ^ 1], s[2 * r]); s[2 * r + 1] = fmaf(xf[j ^ 1], wf[8 + (j ^ 1)], s[2 * r + 1]); }
          mask = ((__float_as_uint(s[2 * r]) | __float_as_uint(s[2 * r + 1])) & zero) | 0xffff0000u;
        }
      }
      mbar_arrive_warp(sb + BAR_RTD);
      float v = butterfly8(s, lane, 1);
      PROF_C(wt == 0 && v != 12345.f, 19);
      v += __shfl_xor_sync(~0u, v, 8);
      v = bf_round(v + __shfl_xor_sync(~0u, v, 16));
      const unsigned rb = __float_as_uint(v) >> 16, row = w * 4 + ((lane & 7) >> 1);
      unsigned key = (lane & 1) ? 0u : ((((rb & 0x8000u) ? (~rb & 0xFFFFu) : (rb | 0x8000u)) << 16) | ((15 - row) << 12));
      key = __reduce_max_sync(~0u, key);
      if (lane == 0) sts32(sb + OFF_MISC + w * 4, key);
      if (lane < 8 && (lane & 1)) sts32(sb + OFF_G + row * 4, __float_as_uint(bf_round(sigmoidf_(v))));
      nb_arrive(NB_KEY, 160);
      nb_sync(NB_ORDER_12, 256);
    }
    uint4* const kvacc = &gs->kv[wg][tn][0][wt];
    float aq[64];
    uint32_t su[9], qe[QE + 1][4];
    {
      float ak[64], av[64], c[36];
      uint32_t pk[8][4];
      PROF_C(wt == 0, 1 + wg * 8);
#pragma unroll 1
      for (int g = 0; g < 16; g++) {
        const uint64_t dx = da0 + (g & 3) * (SLOT >> 4), dw = da0 + ((OFF_W1 >> 4) + (g & 3) * (WQKV_BYTES >> 4));
        mbar_wait(sb + BAR_FULL + (g & 7) * 8, g >> 3);
        if (g == 0) PROF_C(wt == 0, 2 + wg * 8);
        wg_fence();
#pragma unroll
        for (int kk = 0; kk < 4; kk++) mma128<1, 0>(ak, dw + (512 + kk * 128), dx + kk * 2, kk ? 1 : g);
        wg_commit();
        if (G1 == 1) {
          wg_wait<1>();
          if (g) mbar_arrive_warp(sb + BAR_EMPTY + (g - 1 & 7) * 8);
          wg_fence();
        }
#pragma unroll
        for (int kk = 0; kk < 4; kk++) mma128<1, 0>(av, dw + (1024 + kk * 128), dx + kk * 2, kk ? 1 : g);
        wg_commit();
        if (G1 == 2) {
          wg_wait<2>();
          if (g) mbar_arrive_warp(sb + BAR_EMPTY + (g - 1 & 7) * 8);
          wg_fence();
        }
#pragma unroll
        for (int kk = 0; kk < 4; kk++) mma128<1, 0>(aq, dw + kk * 128, dx + kk * 2, kk ? 1 : g);
        wg_commit();
      }
      if (wg == 0) nb_arrive(NB_ORDER_12, 256);
      if (wg == 1 && EARLY_O) nb_arrive(NB_ORDER_3O, 256);
      mbar_wait(sb + BAR_IDX, 0);
      if (wg == 1) nb_sync(NB_STG, 256);
      wg_wait<2>();
      pin(ak);
      PROF_C(wt == 0, 3 + wg * 8);
      const uint32_t va = sb + OFF_V + (w * 16 + (lane & 15)) * 128;
      uint32_t lk[8];
#pragma unroll
      for (int u = 0; u < 8; u++) {
        if (u < VK + KL || !KL) lk[u] = 0x3FB8AA3Bu;
#pragma unroll
        for (int i = 0; i < 4; i++) pk[u][i] = phi2(ak[8 * u + 2 * i], ak[8 * u + 2 * i + 1], __uint_as_float(lk[u]));
        if (u == VK) { wg_wait<1>(); pin(av); }
        if (u == MM) { wg_wait<0>(); mbar_arrive_warp(sb + BAR_EMPTY + 7 * 8); }
        const uint32_t z = mism(pk[u][0], pk[u][1], 0) | mism(pk[u][2], pk[u][3], 0);
#pragma unroll
        for (int t = u < VK ? 8 : (u - VK) * 8 / (8 - VK); t < (u - VK + 1) * 8 / (8 - VK); t++) {
          const float* v = &av[8 * t];
          stsm4(va + (t >> 2) * 9216 + ((((lane >> 4) + 2 * (t & 3)) ^ (lane & 7)) << 4) + (z & zero), pack2(v[0], v[1]), pack2(v[2], v[3]), pack2(v[4], v[5]), pack2(v[6], v[7]));
        }
        if (KL && u >= VK && u + KL < 8) lk[u + KL] = lds32(sb + OFF_MISC + 20);
      }
      fence_async_smem();
      nb_sync(nb_self, 128);
      PROF_C(wt == 0, 8 + wg * 8);
      const uint64_t dv = mkdesc(sb + OFF_V, 16, 1024, 1);
      wg_fence();
#pragma unroll
      for (int kk = 0; kk < 8; kk++) {
        if (kk == KA && wg == 1) nb_arrive(NB_ORDER_3O + EARLY_O * 5, 256);
        mma_ktv(c, pk[kk], dv + ((kk >> 2) * 576 + (kk & 3) * 2), kk ? 1 : 0);
      }
      wg_commit();
      if (KA == 8 && wg == 1) nb_arrive(NB_ORDER_3O + EARLY_O * 5, 256);
      pin(aq);
#pragma unroll
      for (int u = 0; u < QE; u++)
#pragma unroll
        for (int i = 0; i < 4; i++) qe[u][i] = phi2(aq[8 * u + 2 * i], aq[8 * u + 2 * i + 1]);
      if (QE) (void)lds32(sb + OFF_ONES + ((mism(qe[0][0], qe[0][1], 0) | mism(qe[0][2], qe[0][3], 0) | mism(qe[QE - 1][0], qe[QE - 1][1], 0) | mism(qe[QE - 1][2], qe[QE - 1][3], 0)) & zero));
      wg_wait<0>();
      pin(c);
      PROF_C(wt == 0, 4 + wg * 8);
#pragma unroll
      for (int i = 0; i < 8; i++) {
        const int j = (i & 3) * 4 + (i >> 2) * 2;
        su[i] = w >= 2 ? pack2(c[16 + j], c[17 + j]) : pack2(c[j], c[j + 1]);
      }
      su[8] = pack2(c[32], c[34]);
#pragma unroll
      for (int u = 0; u < 3; u++)
        if (u < R0 || wg) red_add_bf(kvacc + u * 128, su[3 * u], su[3 * u + 1], su[3 * u + 2]);
    }
    const uint32_t par = lds32(sb + OFF_MISC + 24);
    {
      const bool paired = PAIRED && ld_relaxed(&gs->block[cta ^ 1]) == (blockIdx.x ^ 1);
      uint4 kv[3];
      int tries = wg ? 0 : TRY_A;
      const uint8_t* gl = smem + OFF_MISC + 20;
      asm volatile("" : "+l"(gl));
      const uint32_t l2e = ld_generic(gl);
    auto stage_kv = [&]() {
      const uint32_t kb = sb + OFF_KVB + w * 256, ka = kb + (lane & 3) * KVB_N + (lane >> 2) * 16;
      sts128(ka, kv[0].x, kv[0].y, kv[0].z, kv[1].x);
      sts128(ka + 128, kv[1].y, kv[1].z, kv[2].x, kv[2].y);
      sts32(kb + 4 * KVB_N + lane * 4, dup_lo(kv[2].z));
      sts32(kb + 4 * KVB_N + 128 + lane * 4, dup_hi(kv[2].z));
      return __all_sync(~0u, (kv[0].w & kv[1].w & kv[2].w) == 0x41804180u && (kv[0].w | kv[1].w | kv[2].w) == 0x41804180u);
    };
      bool have = false;
      const uint32_t qa = sb + OFF_PK + ((lane >> 4) * 8 + (lane & 7)) * 128 + (((2 * w + ((lane >> 3) & 1)) ^ (lane & 7)) << 4);
      uint32_t lq[8];
#pragma unroll
      for (int u = 0; u < QA; u++) lq[u] = l2e;
#pragma unroll
      for (int u = 0; u < 8; u++) {
        uint32_t r[4];
        if (u == KF && wg) {
#pragma unroll
          for (int i = 0; i < 3; i++) kv[i] = ld_relaxed4(kvacc + i * 128);
        }
#pragma unroll
        for (int i = 0; i < 4; i++) r[i] = u < QE ? qe[u][i] : phi2(aq[8 * u + 2 * i], aq[8 * u + 2 * i + 1], __uint_as_float(lq[u]));
        stsm4t(qa + u * 2048, r[0], r[1], r[2], r[3]);
        if (u % RS == RS - 1 && u / RS + R0 < 3 && !wg) red_add_bf(kvacc + (u / RS + R0) * 128, su[3 * (u / RS + R0)], su[3 * (u / RS + R0) + 1], su[3 * (u / RS + R0) + 2]);
        if (u + QA < 8) lq[u + QA] = QD ? ld_generic(gl) : lds32(sb + OFF_MISC + 20);
        if (u == KU && wg) have = stage_kv();
      }
      PROF_C(wt == 0, 34 + wg * 2);
      if (NAP_A && !wg) __nanosleep(NAP_A);
      if (KU > 7 && KF < 8 && wg) have = stage_kv();
      for (; !have; tries++) {
        if (tries > RETRY)
          while (ld_relaxed((const unsigned*)&(kvacc - lane)[256 + 31].w) != 0x41804180u) __nanosleep(wg ? KV_SLEEP : KV_SLEEP_A);
#pragma unroll
        for (int i = 0; i < 3; i++) kv[i] = ld_relaxed4(kvacc + i * 128);
        have = stage_kv();
      }
      PROF_C(wt == 0, 5 + wg * 8);
      fence_async_smem();
      nb_sync(nb_self, 128);
      float o[2][2][20];
      const uint64_t dq = mkdesc(sb + OFF_PK, 16, 1024, 1), dz = mkdesc(sb + OFF_KVB, 128, KVB_N, 0);
      wg_fence();
#pragma unroll
      for (int m = 0; m < 2; m++) {
#pragma unroll
        for (int h = 0; h < 2; h++)
#pragma unroll
          for (int kk = 0; kk < 2; kk++) mma_qkvz(o[m][h], dq + (m * 512 + h * 4 + kk * 2), dz + (h * 32 + kk * 16), kk);
        wg_commit();
      }
      if (HOLD < 8 && HP == 0 && wg) nb_arrive(NB_HOLD, 256);
      if (EF == 3 && wg && elect()) red_add(gs->cnt[16 + tm], 1u << tn * 4);
      uint32_t tag[2][4];
#pragma unroll
      for (int i = 0; i < 8; i++) tag[i >> 2][i & 3] = (lane >> 3) == (i & 3) && ((lane ^ (lane >> 3)) & 1) == (i >> 2);
      uint32_t gr[8];
      const uint8_t* ga = smem + OFF_G + (w * 16 + (lane >> 2)) * 4;
      asm volatile("" : "+l"(ga));
#pragma unroll
      for (int i = 0; i < OA; i++) gr[i] = ld_generic(ga + (i >> 2) * 256 + (i & 1) * 32);
      const uint32_t oo = w * 1024 + (lane >> 2) * 64 + (((lane ^ (lane >> 3)) & 3) << 4);
      uint8_t* const og = (uint8_t*)gs->o[tm][wg * 8 + tn] + oo;
      uint32_t ob[8][4];
#pragma unroll
      for (int m = 0; m < 2; m++) {
        if (m == 0) wg_wait<1>(); else wg_wait<0>();
        pin(o[m][0]); pin(o[m][1]);
        if (EF == 2 - m && wg && elect()) red_add(gs->cnt[16 + tm], 1u << tn * 4);
        if (PB == 2 - m && wg) mbar_arrive_warp(sb + BAR_PUB + 8);
        if (m && !wg) nb_arrive(NB_STG, 256);
        if (HOLD < 8 && HP == 1 && m && wg) nb_arrive(NB_HOLD, 256);
        if (m && wg && paired && elect()) mbar_arrive_peer(peer_addr(sb + BAR_PA));
        if (m == 0) PROF_C(wt == 0, 6 + wg * 8);
#pragma unroll
        for (int u = 0; u < 4; u++) {
          const int h = u >> 1, i = u & 1;
          const float* on = o[m][h];
          const float sc = __uint_as_float(gr[m * 4 + u]) * rcp(on[16 + 2 * i] + 1e-6f);
          const uint32_t sc2 = pack2(sc, sc);
#pragma unroll
          for (int j = 0; j < 4; j++) {
            const uint32_t v = HS ? mul_bf2(pack2(on[4 * j + 2 * i], on[4 * j + 2 * i + 1]), sc2) : pack2(on[4 * j + 2 * i] * sc, on[4 * j + 2 * i + 1] * sc);
            asm("lop3.b32 %0, %1, %2, %3, 0xB8;" : "=r"(ob[m * 4 + u][j]) : "r"(v), "r"(tag[i][j]), "r"(par));
          }
          st_relaxed4(og + (h * 8192 + m * 4096 + i * 512), ob[m * 4 + u]);
          if (OWN1 == 2 && wg) sts128(sb + OFF_V + oo + (h * 8192 + m * 4096 + i * 512), ob[m * 4 + u][0], ob[m * 4 + u][1], ob[m * 4 + u][2], ob[m * 4 + u][3]);
          const int n = m * 4 + u + OA;
          if (n < 8) gr[n] = ld_generic(ga + (n >> 2) * 256 + (n & 1) * 32);
        }
      }
      if ((!EF || !wg) && elect()) red_add(gs->cnt[wg * 16 + tm], 1u << tn * 4);
      if (!PB || !wg) mbar_arrive_warp(sb + BAR_PUB + wg * 8);
      if (HOLD < 8 && HP == 2 && wg) nb_arrive(NB_HOLD, 256);
      PROF(wt == 0, 17 + wg);
      if (wg) {
        auto to_peer = [&]() {
        if (paired) {
          const uint32_t pb = peer_addr(sb);
          mbar_wait(sb + BAR_PA, 0);
#pragma unroll
          for (int u = 0; u < 8; u++) st_async4(pb + OFF_PK + oo + ((u >> 1 & 1) * 8192 + (u >> 2) * 4096 + (u & 1) * 512), ob[u], pb + BAR_PEER);
        }
        };
        if (!OWN1) to_peer();
#pragma unroll
        for (int u = 0, z = 0; u < (OWN1 == 2 ? 0 : 8); u++) {
          sts128(sb + OFF_V + oo + ((u >> 1 & 1) * 8192 + (u >> 2) * 4096 + (u & 1) * 512) + z, ob[u][0], ob[u][1], ob[u][2], ob[u][3]);
          if (PO && u % PO == PO - 1 && u < 7) z = lds32(sb + OFF_ONES) & 16;
        }
        fence_async_smem();
        __syncwarp();
        mbar_arrive_warp(sb + BAR_OWN);
        if (HOLD < 8 && HP == 3) nb_arrive(NB_HOLD, 256);
        PROF(wt == 0, 15);
        if (OWN1) to_peer();
      }
    }
    if (wg == 1) {
      verify_tiles<1>(sb, gs, tm, tn, w, lane);
    } else {
      float acc[2][64];
      nb_sync(NB_ORDER_3O, 256);
      PROF_C(wt == 0, 26);
      uint32_t xr[2][8][4], q[2][2];
      const uint32_t ta = sb + OFF_RES + (uint32_t)(w * 16 + (lane & 15)) * 128;
      const uint64_t do0 = mkdesc(sb + OFF_RING, 16, 512, 2);
      uint64_t xs = OA_SLOTS, ws = OW_SLOTS;
#pragma unroll 1
      for (int g = 0; g < 13 - TL; g++, xs >>= 4, ws >>= 4) {
        const uint32_t r = g * 52 >> 8, s = g - r * 5;
        const uint64_t da = do0 + ((uint32_t)xs & 15) * (SLOT >> 4), db = db0 + ((uint32_t)ws & 15) * (SLOT >> 4);
        if (EARLY_O && g == EARLY_O) nb_sync(NB_ORDER_3O + 5, 256);
        if (g == OWN) mbar_wait(sb + BAR_OWN, 0);
        if (g == PEER) { mbar_wait(sb + BAR_PEER, 0); fence_async_smem(); }
        if (g == HOLD) {
          if (HR) { wg_wait<0>(); mbar_arrive_warp(sb + BAR_OEMPTY + (HOLD + 4) % 5 * 8); }
          nb_sync(NB_HOLD, 256);
        }
        mbar_wait(sb + BAR_OFULL + s * 8, r & 1);
        wg_fence();
#pragma unroll
        for (int kk = 0; kk < 4; kk++)
#pragma unroll
          for (int m = 0; m < 2; m++) mma128<0, 1>(acc[m], da + (m * 256 + (kk >> 1) * 512 + (kk & 1) * 2), db + kk * 128, kk ? 1 : g);
        wg_commit();
        wg_wait<1>();
        if (g && (g != HOLD || !HR)) mbar_arrive_warp(sb + BAR_OEMPTY + (s ? s - 1 : 4) * 8);
      }
      mbar_wait(sb + BAR_X, 0);
      const int selw = ((0xFFFF - (int)(lds32(sb + OFF_MISC + 16) & 0xFFFF)) >> 4) - tm * 8 - w;
#pragma unroll
      for (int u = 0; u < 4; u++) {
        const int m = u >> 1, g = 13 - TL + u;
        const float g1 = 1.f - __uint_as_float(lds32(sb + OFF_G + (m * 64 + w * 16 + (u & 1) * 8 + (lane >> 2)) * 4));
        q[m][u & 1] = pack2(g1, g1);
#pragma unroll
        for (int j = 0; j < 4; j++) ldsm4(ta + (u & 1) * RES_H + m * 8192 + ((((lane >> 4) + 2 * j) ^ (lane & 7)) << 4), xr[m][(u & 1) * 4 + j]);
        if (u == 3) break;
        mbar_wait(sb + BAR_OFULL + g % 5 * 8, g / 5 & 1);
        wg_fence();
#pragma unroll
        for (int kk = 0; kk < 4; kk++)
#pragma unroll
          for (int mm = 0; mm < 2; mm++)
            mma128<0, 1>(acc[mm], do0 + ((OA_SLOTS >> g * 4 & 15) * (SLOT >> 4) + mm * 256 + (kk >> 1) * 512 + (kk & 1) * 2), db0 + ((OW_SLOTS >> g * 4 & 15) * (SLOT >> 4) + kk * 128), 1);
        wg_commit();
        wg_wait<1>();
        if (g <= 11) mbar_arrive_warp(sb + BAR_OEMPTY + (g + 4) % 5 * 8);
      }
#pragma unroll
      for (int m = 0; m < 2; m++) {
#pragma unroll
        for (int g = 16 - TL; g < 16; g++) {
          if (m == 0) { mbar_wait(sb + BAR_OFULL + g % 5 * 8, g / 5 & 1); wg_fence(); }
#pragma unroll
          for (int kk = 0; kk < 4; kk++)
            mma128<0, 1>(acc[m], do0 + ((OA_SLOTS >> g * 4 & 15) * (SLOT >> 4) + m * 256 + (kk >> 1) * 512 + (kk & 1) * 2), db0 + ((OW_SLOTS >> g * 4 & 15) * (SLOT >> 4) + kk * 128), 1);
        }
        wg_commit();
      }
      mbar_arrive_warp(sb + BAR_DONE);
      const uint32_t tb = sb + OFF_RES + w * 2048 + (lane >> 3) * 128 + (((lane ^ (lane >> 3)) & 7) << 4), tx = lane & 4 ? 64 : -64;
      uint8_t* const og = (uint8_t*)pout + (size_t)(tm * 128 + w * 16 + (lane >> 3)) * 2048 + tn * 256 + (lane & 7) * 16;
#pragma unroll
      for (int m = 0; m < 2; m++) {
        if (selw == 4 * m) {
          mbar_wait(sb + BAR_Y, 0);
#pragma unroll
          for (int j = 0; j < 8; j++) ldsm4(ta + (j >> 2) * RES_H + m * 8192 + ((((lane >> 4) + 2 * (j & 3)) ^ (lane & 7)) << 4), xr[m][j]);
        }
        if (m == 0) wg_wait<1>(); else wg_wait<0>();
        if (m) PROF(wt == 0, 31);
#pragma unroll
        for (int h = 0; h < 2; h++) {
#pragma unroll
          for (int j = 4 * h; j < 4 * h + 4; j++) {
            const float* v = &acc[m][8 * j];
            stsm4(ta + h * RES_H + m * 8192 + ((((lane >> 4) + 2 * (j & 3)) ^ (lane & 7)) << 4),
                  fma_bf2(xr[m][j][0], q[m][0], pack2(v[0], v[1])), fma_bf2(xr[m][j][1], q[m][1], pack2(v[2], v[3])),
                  fma_bf2(xr[m][j][2], q[m][0], pack2(v[4], v[5])), fma_bf2(xr[m][j][3], q[m][1], pack2(v[6], v[7])));
          }
          if (FS >> m & 1) {
            __syncwarp();
            uint4 t[4];
#pragma unroll
            for (int j = 0; j < 4; j++) t[j] = lds128(tb + h * RES_H + m * 8192 + j * 512 - (j & 1) * tx);
#pragma unroll
            for (int j = 0; j < 4; j++) *(uint4*)(og + (m * 64 + j * 4) * 2048 + h * 128) = t[j];
          } else {
            fence_async_smem();
            __syncwarp();
            if (elect()) tma2d_store(&p.out, sb + OFF_RES + h * RES_H + m * 8192 + w * 2048, tn * 128 + h * 64, tm * 128 + m * 64 + w * 16);
          }
          if (FS != 3 && m && h && elect()) { bulk_commit(); asm volatile("cp.async.bulk.wait_group.read 0;" ::: "memory"); }
        }
        if (!m) PROF(wt == 0, 33);
      }
      PROF(wt == 0, 32);
    }
  }
}

typedef CUresult (*EncodeFn)(CUtensorMap*, CUtensorMapDataType, cuuint32_t, void*, const cuuint64_t*, const cuuint64_t*, const cuuint32_t*,
                             const cuuint32_t*, CUtensorMapInterleave, CUtensorMapSwizzle, CUtensorMapL2promotion, CUtensorMapFloatOOBfill);

void encode(EncodeFn fn, CUtensorMap* m, const void* ptr, int rank, const cuuint64_t* dims, const cuuint64_t* strides, const cuuint32_t* box,
            CUtensorMapSwizzle sw, CUtensorMapDataType dt = CU_TENSOR_MAP_DATA_TYPE_BFLOAT16) {
  const cuuint32_t es[3] = {1, 1, 1};
  fn(m, dt, rank, const_cast<void*>(ptr), dims, strides, box, es, CU_TENSOR_MAP_INTERLEAVE_NONE, sw,
     CU_TENSOR_MAP_L2_PROMOTION_L2_128B, CU_TENSOR_MAP_FLOAT_OOB_FILL_NONE);
}

}

extern "C" void kernel_launch(void* const* d_in, const int* in_sizes, int n_in, void* d_out, int out_size) {
  (void)in_sizes; (void)n_in; (void)out_size;
  EncodeFn fn = nullptr;
  cudaDriverEntryPointQueryResult qr;
  cudaGetDriverEntryPoint("cuTensorMapEncodeTiled", (void**)&fn, cudaEnableDefault, &qr);

  Params p;
  {
    const cuuint64_t dims[2] = {D_, S_}, str[1] = {D_ * 2};
    const cuuint32_t box[2] = {64, 128}, box_st[2] = {64, 16}, box_r[2] = {256, 16};
    encode(fn, &p.xr, d_in[0], 2, dims, str, box_r, CU_TENSOR_MAP_SWIZZLE_NONE);
    encode(fn, &p.x, d_in[0], 2, dims, str, box, CU_TENSOR_MAP_SWIZZLE_128B);
    encode(fn, &p.out, d_out, 2, dims, str, box_st, CU_TENSOR_MAP_SWIZZLE_128B);
  }
  {
    const cuuint64_t dims[3] = {D_, D_, 3}, str[2] = {3 * D_ * 2, D_ * 2};
    const cuuint32_t box[3] = {64, 64, 3};
    encode(fn, &p.w, d_in[1], 3, dims, str, box, CU_TENSOR_MAP_SWIZZLE_128B);
  }
  {
    const cuuint64_t dims[3] = {64, D_, D_ / 64}, str[2] = {D_ * 2, 128};
    const cuuint32_t box[3] = {64, 64, 2};
    encode(fn, &p.wo, d_in[2], 3, dims, str, box, CU_TENSOR_MAP_SWIZZLE_128B);
  }
  {
    const cuuint64_t dims[3] = {F_, D_ / 4, 4}, str[2] = {F_ * 8, F_ * 2};
    const cuuint32_t box[3] = {32, 16, 4};
    encode(fn, &p.gate, d_in[5], 3, dims, str, box, CU_TENSOR_MAP_SWIZZLE_NONE);
    encode(fn, &p.up, d_in[6], 3, dims, str, box, CU_TENSOR_MAP_SWIZZLE_NONE);
  }
  {
    const cuuint64_t dims[3] = {D_ / 4, F_, 2}, str[2] = {D_ * 2, D_};
    const cuuint32_t box[3] = {256, 4, 2};
    encode(fn, &p.down, d_in[7], 3, dims, str, box, CU_TENSOR_MAP_SWIZZLE_NONE, CU_TENSOR_MAP_DATA_TYPE_UINT32);
  }
  void* gs = nullptr;
  cudaGetSymbolAddress(&gs, g_scratch);
  typedef const __nv_bfloat16* bp;
  int dev = 0, sms = 0;
  cudaGetDevice(&dev);
  cudaDeviceGetAttribute(&sms, cudaDevAttrMultiProcessorCount, dev);
  const bool by_sm = BYSM && sms == NGRID;
  const auto kernel = by_sm ? fused_kernel<true> : fused_kernel<false>;
  cudaFuncSetAttribute(kernel, cudaFuncAttributeMaxDynamicSharedMemorySize, SMEM_BYTES);
  kernel<<<by_sm ? NGRID : NCTA, NTHREADS, SMEM_BYTES, cudaStreamPerThread>>>((bp)d_in[0], (Scratch*)gs, (bp)d_in[5], (bp)d_in[6], (bp)d_in[4], (bp)d_in[8], (bp)d_in[7], (__nv_bfloat16*)d_out, p);
}
```

```cpp
#include <cuda_runtime.h>
#include <cuda.h>
#include <cuda_bf16.h>
#include <stdint.h>
#include <stddef.h>
#include <type_traits>

namespace {

constexpr int S_ = 2048, D_ = 1024, F_ = 3584;
constexpr int NCTA = 128, NGRID = 132, NTHREADS = 512;
#define NOMOD 0
constexpr int MOD_CTAS = NOMOD ? 0 : F_ / 32;

#define PRE 2
#define ST1 700
#define RT_G0 2
#define RT_ROT 1
#define RT_SLEEP 500
#define PF_MOD 7
#define MOD_START 9
#define MM 3
#define PO 2
#define A_SLEEP 128
#define KU 99
#define HS 1
#define HOLD 5
#define OWN1 2
#define KF 5
#define QA 3
#define R0 1
#define OA 3
#define QD 0
#define MOD_SLEEP 0
#define MOD_S0 8
#define Y_SLEEP 200
#define PD 0
#define TRY_A 9
#define NAP_A 0
#define VK 1
#define TR 2
#define Q0 0
#define QS 2
#define QW1 0
#define VK1 2
#define MM1 5
#define KL1 2
#define M0 3
#define HP 1
#define FS 0
#define KL 3
#define RS 2
#define RETRY 1
#define KV_SLEEP_A 64
#define KV_SLEEP 50
#define TL 3
#define EF 2
#define DYN 0
#define FN 0
#define PB 1
#define B_SLEEP 32
#define PW 1
#define HR 0
#define PAIRED 1
#define BYSM 1

constexpr uint32_t SLOT = 16384, WQKV_BYTES = 24576;
constexpr int MOD_BUFS = 3, MOD_BUFS0 = MOD_BUFS + 2;
static_assert(MOD_START + MOD_BUFS0 <= 16, "first FFN round is requested during W1");
constexpr uint32_t OFF_RING = 0, OFF_W1 = 4 * SLOT;
constexpr uint64_t OA_SLOTS = 0x0AB210AB21098210ull, OW_SLOTS = 0x4376543765437654ull;
constexpr uint32_t OFF_RES = OFF_RING + 8 * SLOT, RES_H = SLOT;
constexpr uint32_t OFF_PK = 10 * SLOT;
constexpr uint32_t OFF_V = 11 * SLOT;
constexpr uint32_t OFF_ONES = OFF_V + 9216 + 8192;
constexpr uint32_t MOD_STEP = 9216, OFF_MOD = OFF_V + 2 * MOD_STEP;
constexpr uint32_t OFF_XSEL = OFF_MOD + 8192;
constexpr uint32_t OFF_KVB = OFF_MOD + 2 * MOD_STEP + 8192;
constexpr uint32_t KVB_N = 1056;
constexpr uint32_t OFF_G = OFF_KVB + 4 * KVB_N + 1024;
constexpr uint32_t OFF_PART = OFF_G + 512;
constexpr uint32_t OFF_MISC = OFF_PART + 576;
constexpr uint32_t OFF_BAR = OFF_MISC + 32;
constexpr uint32_t SMEM_BYTES = OFF_BAR + 480;
constexpr uint32_t BAR_FULL = OFF_BAR, BAR_Y = BAR_FULL + 64, BAR_X = BAR_Y + 8, BAR_PEER = BAR_X + 8, BAR_GATE = BAR_PEER + 8, BAR_RT = BAR_GATE + 8,
                   BAR_FIX = BAR_RT,
                   BAR_MFULL = BAR_FIX + 64, BAR_LAND = BAR_FULL,
                   BAR_EMPTY = OFF_BAR + 28 * 8, BAR_OEMPTY = BAR_EMPTY + 64, BAR_RTD = BAR_OEMPTY + 40, BAR_DONE = BAR_RTD + 8,
                   BAR_OWN = BAR_DONE + 8, BAR_PA = BAR_OWN + 8, BAR_PUB = BAR_PA + 8, BAR_MEMPTY = BAR_PUB + 16,
                   BAR_IDX = BAR_MEMPTY + 8,
                   BAR_OFULL = OFF_BAR + 52 * 8;
static_assert(BAR_MFULL + MOD_BUFS0 * 8 <= BAR_EMPTY && BAR_MEMPTY + MOD_BUFS0 * 8 == BAR_OFULL, "barrier groups");
static_assert(SMEM_BYTES <= 232448, "smem");
static_assert(TL == 3 && PRE == 2, "schedule");

constexpr int NB_WG0 = 1, NB_ORDER_12 = 3, NB_ORDER_3O = 4, NB_STG = 5, NB_MODW = 6, NB_KEY = 7, NB_HOLD = 8;

struct Scratch {
  uint4 kv[2][8][3][128];
  float4 y[2][3][128];
  unsigned cnt[32][32];
  unsigned gslot[S_];
  unsigned rslot[8][NCTA];
  unsigned spare[128];
  unsigned block[NCTA];
  uint4 o[16][16][1024];
};
static_assert(offsetof(Scratch, gslot) == NCTA * 56 * 16, "clear size");
__device__ __align__(1024) Scratch g_scratch;

#define PROF(cond, i) do {} while (0)
#define PROF_C(cond, i) do {} while (0)

__device__ __forceinline__ void mbar_init(uint32_t bar, int cnt) { asm volatile("mbarrier.init.shared::cta.b64 [%0], %1;" ::"r"(bar), "r"(cnt)); }
__device__ __forceinline__ void mbar_expect_tx(uint32_t bar, uint32_t bytes) { asm volatile("mbarrier.arrive.expect_tx.shared::cta.b64 _, [%0], %1;" ::"r"(bar), "r"(bytes) : "memory"); }
__device__ __forceinline__ void mbar_arrive(uint32_t bar) { asm volatile("mbarrier.arrive.shared::cta.b64 _, [%0];" ::"r"(bar) : "memory"); }
__device__ __forceinline__ uint32_t peer_addr(uint32_t a) {
  uint32_t r;
  asm volatile("{\n.reg .u32 c;\nmov.u32 c, %%cluster_ctarank;\nxor.b32 c, c, 1;\nmapa.shared::cluster.u32 %0, %1, c;\n}" : "=r"(r) : "r"(a));
  return r;
}
__device__ __forceinline__ void mbar_arrive_peer(uint32_t bar) { asm volatile("mbarrier.arrive.shared::cluster.b64 _, [%0];" ::"r"(bar) : "memory"); }
__device__ __forceinline__ uint32_t mism(uint32_t a, uint32_t b, uint32_t p) {
  uint32_t r; asm("lop3.b32 %0, %1, %2, %3, 0x7E;" : "=r"(r) : "r"(a), "r"(b), "r"(p)); return r;
}
__device__ __forceinline__ bool elect() {
  uint32_t r;
  asm volatile("{\n.reg .pred p;\nelect.sync _|p, 0xffffffff;\nselp.u32 %0, 1, 0, p;\n}" : "=r"(r));
  return r;
}
__device__ __forceinline__ uint32_t fresh_tid() { uint32_t r; asm volatile("mov.u32 %0, %%tid.x;" : "=r"(r)); return r; }
__device__ __forceinline__ void mbar_arrive_warp(uint32_t bar) {
  asm volatile("{\n.reg .pred p;\nelect.sync _|p, 0xffffffff;\n@p mbarrier.arrive.shared::cta.b64 _, [%0];\n}" ::"r"(bar) : "memory");
}
__device__ __forceinline__ void mbar_wait(uint32_t bar, uint32_t parity) {
  asm volatile("{\n.reg .pred p;\nWAIT_L:\nmbarrier.try_wait.parity.shared::cta.b64 p, [%0], %1;\n@p bra DONE_L;\nbra WAIT_L;\nDONE_L:\n}"
               ::"r"(bar), "r"(parity) : "memory");
}
__device__ __forceinline__ uint32_t mbar_try(uint32_t bar, uint32_t parity) {
  uint32_t ok;
  asm volatile("{\n.reg .pred p;\nmbarrier.try_wait.parity.shared::cta.b64 p, [%1], %2;\nselp.u32 %0, 1, 0, p;\n}" : "=r"(ok) : "r"(bar), "r"(parity) : "memory");
  return ok;
}
__device__ __forceinline__ uint32_t mbar_test(uint32_t bar, uint32_t parity) {
  uint32_t ok;
  asm volatile("{\n.reg .pred p;\nmbarrier.test_wait.parity.shared::cta.b64 p, [%1], %2;\nselp.u32 %0, 1, 0, p;\n}" : "=r"(ok) : "r"(bar), "r"(parity) : "memory");
  return ok;
}
constexpr unsigned long long WATCHDOG_NS = 2000000000ull;
__device__ __forceinline__ unsigned long long gtime() { unsigned long long t; asm volatile("mov.u64 %0, %%globaltimer;" : "=l"(t)); return t; }
__device__ __forceinline__ uint32_t clock32() { uint32_t t; asm volatile("mov.u32 %0, %%clock;" : "=r"(t)); return t; }
__device__ __forceinline__ void mbar_wait_bounded(uint32_t bar, uint32_t parity) {
  unsigned long long t0 = 0;
  for (;;) {
    uint32_t ok;
    asm volatile("{\n.reg .pred p;\nmbarrier.try_wait.parity.shared::cta.b64 p, [%1], %2;\nselp.u32 %0, 1, 0, p;\n}" : "=r"(ok) : "r"(bar), "r"(parity) : "memory");
    if (ok) break;
    const unsigned long long t1 = gtime();
    if (t0 == 0) t0 = t1;
    if (t1 - t0 > WATCHDOG_NS) __trap();
  }
}
__device__ __forceinline__ void tma2d(uint32_t dst, const CUtensorMap* m, int c0, int c1, uint32_t bar) {
  asm volatile("cp.async.bulk.tensor.2d.shared::cluster.global.mbarrier::complete_tx::bytes [%0], [%1, {%3, %4}], [%2];"
               ::"r"(dst), "l"(m), "r"(bar), "r"(c0), "r"(c1) : "memory");
}
__device__ __forceinline__ void tma3d(uint32_t dst, const CUtensorMap* m, int c0, int c1, int c2, uint32_t bar) {
  asm volatile("cp.async.bulk.tensor.3d.shared::cluster.global.mbarrier::complete_tx::bytes [%0], [%1, {%3, %4, %5}], [%2];"
               ::"r"(dst), "l"(m), "r"(bar), "r"(c0), "r"(c1), "r"(c2) : "memory");
}
__device__ __forceinline__ void bulk_load(uint32_t dst, const void* src, uint32_t bytes, uint32_t bar) {
  asm volatile("cp.async.bulk.shared::cluster.global.mbarrier::complete_tx::bytes [%0], [%1], %2, [%3];" ::"r"(dst), "l"(src), "r"(bytes), "r"(bar) : "memory");
}
__device__ __forceinline__ void bulk_store(void* dst, uint32_t src, uint32_t bytes) {
  asm volatile("cp.async.bulk.global.shared::cta.bulk_group [%0], [%1], %2;" ::"l"(dst), "r"(src), "r"(bytes) : "memory");
}
__device__ __forceinline__ void st_async4(uint32_t dst, const uint32_t (&v)[4], uint32_t bar) {
  asm volatile("st.async.shared::cluster.mbarrier::complete_tx::bytes.v4.b32 [%0], {%1, %2, %3, %4}, [%5];" ::"r"(dst), "r"(v[0]), "r"(v[1]), "r"(v[2]), "r"(v[3]), "r"(bar) : "memory");
}
__device__ __forceinline__ void bulk_commit() { asm volatile("cp.async.bulk.commit_group;" ::: "memory"); }
__device__ __forceinline__ void bulk_prefetch(const void* p, uint32_t bytes) {
  asm volatile("cp.async.bulk.prefetch.L2.global [%0], %1;" ::"l"(p), "r"(bytes) : "memory");
}
__device__ __forceinline__ void tma2d_store(const CUtensorMap* m, uint32_t src, int c0, int c1) {
  asm volatile("cp.async.bulk.tensor.2d.global.shared::cta.bulk_group [%0, {%2, %3}], [%1];" ::"l"(m), "r"(src), "r"(c0), "r"(c1) : "memory");
}
__device__ __forceinline__ void wg_fence() { asm volatile("wgmma.fence.sync.aligned;" ::: "memory"); }
__device__ __forceinline__ void wg_commit() { asm volatile("wgmma.commit_group.sync.aligned;" ::: "memory"); }
template <int N> __device__ __forceinline__ void wg_wait() { asm volatile("wgmma.wait_group.sync.aligned %0;" ::"n"(N) : "memory"); }
__device__ __forceinline__ void fence_async_smem() { asm volatile("fence.proxy.async.shared::cta;" ::: "memory"); }
__device__ __forceinline__ void fence_async_global() { asm volatile("fence.proxy.async.global;" ::: "memory"); }
__device__ __forceinline__ void fence_release() { asm volatile("fence.release.gpu;" ::: "memory"); }
__device__ __forceinline__ void fence_acquire() { asm volatile("fence.acquire.gpu;" ::: "memory"); }
__device__ __forceinline__ void nb_sync(int id, int n) { asm volatile("bar.sync %0, %1;" ::"r"(id), "r"(n) : "memory"); }
__device__ __forceinline__ void nb_arrive(int id, int n) { asm volatile("bar.arrive %0, %1;" ::"r"(id), "r"(n) : "memory"); }
__device__ __forceinline__ void stsm4(uint32_t addr, uint32_t r0, uint32_t r1, uint32_t r2, uint32_t r3) {
  asm volatile("stmatrix.sync.aligned.m8n8.x4.shared.b16 [%0], {%1, %2, %3, %4};" ::"r"(addr), "r"(r0), "r"(r1), "r"(r2), "r"(r3) : "memory");
}
__device__ __forceinline__ void stsm4t(uint32_t addr, uint32_t r0, uint32_t r1, uint32_t r2, uint32_t r3) {
  asm volatile("stmatrix.sync.aligned.m8n8.x4.trans.shared.b16 [%0], {%1, %2, %3, %4};" ::"r"(addr), "r"(r0), "r"(r1), "r"(r2), "r"(r3) : "memory");
}
__device__ __forceinline__ void st_relaxed4(void* p, const uint32_t (&v)[4]) {
  asm volatile("st.relaxed.gpu.global.v4.u32 [%0], {%1, %2, %3, %4};" ::"l"(p), "r"(v[0]), "r"(v[1]), "r"(v[2]), "r"(v[3]) : "memory");
}
__device__ __forceinline__ void sts128(uint32_t addr, uint32_t a, uint32_t b, uint32_t c, uint32_t d) {
  asm volatile("st.shared.v4.b32 [%0], {%1, %2, %3, %4};" ::"r"(addr), "r"(a), "r"(b), "r"(c), "r"(d) : "memory");
}
__device__ __forceinline__ uint32_t pack2(float lo, float hi) {
  uint32_t r; asm("cvt.rn.bf16x2.f32 %0, %1, %2;" : "=r"(r) : "f"(hi), "f"(lo)); return r;
}
__device__ __forceinline__ float bf_lo(uint32_t v) { return __uint_as_float(v << 16); }
__device__ __forceinline__ float bf_hi(uint32_t v) { return __uint_as_float(v & 0xffff0000u); }
__device__ __forceinline__ float bf_round(float v) { return __bfloat162float(__float2bfloat16_rn(v)); }
__device__ __forceinline__ void ldsm4(uint32_t addr, uint32_t (&r)[4]) {
  asm volatile("ldmatrix.sync.aligned.m8n8.x4.shared.b16 {%0, %1, %2, %3}, [%4];" : "=r"(r[0]), "=r"(r[1]), "=r"(r[2]), "=r"(r[3]) : "r"(addr) : "memory");
}
__device__ __forceinline__ uint4 lds128(uint32_t addr) {
  uint4 v; asm volatile("ld.volatile.shared.v4.u32 {%0, %1, %2, %3}, [%4];" : "=r"(v.x), "=r"(v.y), "=r"(v.z), "=r"(v.w) : "r"(addr) : "memory"); return v;
}
__device__ __forceinline__ uint2 lds64(uint32_t addr) { uint2 v; asm volatile("ld.volatile.shared.v2.u32 {%0, %1}, [%2];" : "=r"(v.x), "=r"(v.y) : "r"(addr) : "memory"); return v; }
__device__ __forceinline__ uint32_t lds32(uint32_t addr) { uint32_t v; asm volatile("ld.volatile.shared.u32 %0, [%1];" : "=r"(v) : "r"(addr) : "memory"); return v; }
__device__ __forceinline__ uint32_t ld_generic(const void* p) { uint32_t v; asm volatile("ld.volatile.u32 %0, [%1];" : "=r"(v) : "l"(p) : "memory"); return v; }
__device__ __forceinline__ void sts32(uint32_t addr, uint32_t v) { asm volatile("st.shared.u32 [%0], %1;" ::"r"(addr), "r"(v) : "memory"); }
__device__ __forceinline__ uint32_t fma_bf2(uint32_t a, uint32_t b, uint32_t c) { uint32_t r; asm("fma.rn.bf16x2 %0, %1, %2, %3;" : "=r"(r) : "r"(a), "r"(b), "r"(c)); return r; }
__device__ __forceinline__ uint32_t mul_bf2(uint32_t a, uint32_t b) { uint32_t r; asm("mul.rn.bf16x2 %0, %1, %2;" : "=r"(r) : "r"(a), "r"(b)); return r; }
__device__ __forceinline__ unsigned ld_relaxed(const unsigned* p) { unsigned v; asm volatile("ld.relaxed.gpu.global.u32 %0, [%1];" : "=r"(v) : "l"(p) : "memory"); return v; }
__device__ __forceinline__ void st_relaxed(unsigned* p, unsigned v) { asm volatile("st.relaxed.gpu.global.u32 [%0], %1;" ::"l"(p), "r"(v) : "memory"); }
__device__ __forceinline__ uint4 ld_relaxed4(const void* p) {
  uint4 v; asm volatile("ld.relaxed.gpu.global.v4.u32 {%0, %1, %2, %3}, [%4];" : "=r"(v.x), "=r"(v.y), "=r"(v.z), "=r"(v.w) : "l"(p) : "memory"); return v;
}
__device__ __forceinline__ float4 ld_relaxed_f4(const void* p) {
  float4 v; asm volatile("ld.relaxed.gpu.global.v4.f32 {%0, %1, %2, %3}, [%4];" : "=f"(v.x), "=f"(v.y), "=f"(v.z), "=f"(v.w) : "l"(p) : "memory"); return v;
}
__device__ __forceinline__ void red_add4(void* p, float a, float b, float c, float d) {
  asm volatile("red.relaxed.gpu.global.add.v4.f32 [%0], {%1, %2, %3, %4};" ::"l"(p), "f"(a), "f"(b), "f"(c), "f"(d) : "memory");
}
__device__ __forceinline__ void red_add_bf(void* p, uint32_t a, uint32_t b, uint32_t c) {
  asm volatile("red.relaxed.gpu.global.add.noftz.v4.bf16x2 [%0], {%1, %2, %3, %4};" ::"l"(p), "r"(a), "r"(b), "r"(c), "r"(0x3F803F80u) : "memory");
}
__device__ __forceinline__ void red_add(unsigned* p, unsigned v) { asm volatile("red.relaxed.gpu.global.add.u32 [%0], %1;" ::"l"(p), "r"(v) : "memory"); }
__device__ __forceinline__ float rcp(float v) { float r; asm("rcp.approx.ftz.f32 %0, %1;" : "=f"(r) : "f"(v)); return r; }
__device__ __forceinline__ float sigmoidf_(float v) { return rcp(1.f + __expf(-v)); }
__device__ __forceinline__ uint32_t phi2(float a, float b, float l2e = 1.4426950408889634f) {
  float ea, eb;
  asm("ex2.approx.ftz.f32 %0, %1;" : "=f"(ea) : "f"(a * l2e));
  asm("ex2.approx.ftz.f32 %0, %1;" : "=f"(eb) : "f"(b * l2e));
  uint32_t t = pack2(a, b), e = pack2(ea, eb), r;
  asm("max.NaN.bf16x2 %0, %0, %1;" : "+r"(t) : "r"(0x35863586u));
  asm("min.bf16x2 %0, %0, %1;" : "+r"(e) : "r"(0x3F803F80u));
  asm("add.rn.bf16x2 %0, %1, %2;" : "=r"(r) : "r"(t), "r"(e));
  return r;
}
__device__ __forceinline__ uint64_t mkdesc(uint32_t addr, uint32_t lbo, uint32_t sbo, uint32_t sw) {
  return (uint64_t)(((addr & 0x3FFFF) >> 4) | ((lbo >> 4) << 16)) | ((uint64_t)((sbo >> 4) | (sw << 30)) << 32);
}

template <int TA, int TB>
__device__ __forceinline__ void mma128(float (&d)[64], uint64_t da, uint64_t db, int sc) {
  asm volatile("{\n.reg .pred p;\nsetp.ne.b32 p, %66, 0;\n"
    "wgmma.mma_async.sync.aligned.m64n128k16.f32.bf16.bf16 "
    "{%0,%1,%2,%3,%4,%5,%6,%7,%8,%9,%10,%11,%12,%13,%14,%15,%16,%17,%18,%19,%20,%21,%22,%23,"
    "%24,%25,%26,%27,%28,%29,%30,%31,%32,%33,%34,%35,%36,%37,%38,%39,%40,%41,%42,%43,%44,%45,%46,%47,"
    "%48,%49,%50,%51,%52,%53,%54,%55,%56,%57,%58,%59,%60,%61,%62,%63}, "
    "%64, %65, p, 1, 1, %67, %68;\n}\n"
    : "+f"(d[0]), "+f"(d[1]), "+f"(d[2]), "+f"(d[3]), "+f"(d[4]), "+f"(d[5]), "+f"(d[6]), "+f"(d[7]),
      "+f"(d[8]), "+f"(d[9]), "+f"(d[10]), "+f"(d[11]), "+f"(d[12]), "+f"(d[13]), "+f"(d[14]), "+f"(d[15]),
      "+f"(d[16]), "+f"(d[17]), "+f"(d[18]), "+f"(d[19]), "+f"(d[20]), "+f"(d[21]), "+f"(d[22]), "+f"(d[23]),
      "+f"(d[24]), "+f"(d[25]), "+f"(d[26]), "+f"(d[27]), "+f"(d[28]), "+f"(d[29]), "+f"(d[30]), "+f"(d[31]),
      "+f"(d[32]), "+f"(d[33]), "+f"(d[34]), "+f"(d[35]), "+f"(d[36]), "+f"(d[37]), "+f"(d[38]), "+f"(d[39]),
      "+f"(d[40]), "+f"(d[41]), "+f"(d[42]), "+f"(d[43]), "+f"(d[44]), "+f"(d[45]), "+f"(d[46]), "+f"(d[47]),
      "+f"(d[48]), "+f"(d[49]), "+f"(d[50]), "+f"(d[51]), "+f"(d[52]), "+f"(d[53]), "+f"(d[54]), "+f"(d[55]),
      "+f"(d[56]), "+f"(d[57]), "+f"(d[58]), "+f"(d[59]), "+f"(d[60]), "+f"(d[61]), "+f"(d[62]), "+f"(d[63])
    : "l"(da), "l"(db), "r"(sc), "n"(TA), "n"(TB));
}

__device__ __forceinline__ void mma_ktv(float (&d)[36], const uint32_t (&a)[4], uint64_t db, int sc) {
  asm volatile("{\n.reg .pred p;\nsetp.ne.b32 p, %41, 0;\n"
    "wgmma.mma_async.sync.aligned.m64n72k16.f32.bf16.bf16 "
    "{%0,%1,%2,%3,%4,%5,%6,%7,%8,%9,%10,%11,%12,%13,%14,%15,%16,%17,%18,%19,%20,%21,%22,%23,"
    "%24,%25,%26,%27,%28,%29,%30,%31,%32,%33,%34,%35}, "
    "{%36,%37,%38,%39}, %40, p, 1, 1, 0;\n}\n"
    : "+f"(d[0]), "+f"(d[1]), "+f"(d[2]), "+f"(d[3]), "+f"(d[4]), "+f"(d[5]), "+f"(d[6]), "+f"(d[7]),
      "+f"(d[8]), "+f"(d[9]), "+f"(d[10]), "+f"(d[11]), "+f"(d[12]), "+f"(d[13]), "+f"(d[14]), "+f"(d[15]),
      "+f"(d[16]), "+f"(d[17]), "+f"(d[18]), "+f"(d[19]), "+f"(d[20]), "+f"(d[21]), "+f"(d[22]), "+f"(d[23]),
      "+f"(d[24]), "+f"(d[25]), "+f"(d[26]), "+f"(d[27]), "+f"(d[28]), "+f"(d[29]), "+f"(d[30]), "+f"(d[31]),
      "+f"(d[32]), "+f"(d[33]), "+f"(d[34]), "+f"(d[35])
    : "r"(a[0]), "r"(a[1]), "r"(a[2]), "r"(a[3]), "l"(db), "r"(sc));
}

__device__ __forceinline__ void mma_qkvz(float (&d)[20], uint64_t da, uint64_t db, int sc) {
  asm volatile("{\n.reg .pred p;\nsetp.ne.b32 p, %22, 0;\n"
    "wgmma.mma_async.sync.aligned.m64n40k16.f32.bf16.bf16 "
    "{%0,%1,%2,%3,%4,%5,%6,%7,%8,%9,%10,%11,%12,%13,%14,%15,%16,%17,%18,%19}, "
    "%20, %21, p, 1, 1, 0, 1;\n}\n"
    : "+f"(d[0]), "+f"(d[1]), "+f"(d[2]), "+f"(d[3]), "+f"(d[4]), "+f"(d[5]), "+f"(d[6]), "+f"(d[7]),
      "+f"(d[8]), "+f"(d[9]), "+f"(d[10]), "+f"(d[11]), "+f"(d[12]), "+f"(d[13]), "+f"(d[14]), "+f"(d[15]),
      "+f"(d[16]), "+f"(d[17]), "+f"(d[18]), "+f"(d[19])
    : "l"(da), "l"(db), "r"(sc));
}

template <int N> __device__ __forceinline__ void pin(float (&d)[N]) {
#pragma unroll
  for (int i = 0; i < N; i++) asm volatile("" : "+f"(d[i])::"memory");
}

struct Params {
  CUtensorMap x, w, xr, gate, up, wo, out, down;
};

__device__ __forceinline__ uint32_t dup_lo(uint32_t v) { uint32_t r; asm("{\n.reg .b16 l, h;\nmov.b32 {l, h}, %1;\nmov.b32 %0, {l, l};\n}" : "=r"(r) : "r"(v)); return r; }
__device__ __forceinline__ uint32_t dup_hi(uint32_t v) { uint32_t r; asm("{\n.reg .b16 l, h;\nmov.b32 {l, h}, %1;\nmov.b32 %0, {h, h};\n}" : "=r"(r) : "r"(v)); return r; }
__device__ __forceinline__ float butterfly8(float (&s)[8], int lane, int o) {
#pragma unroll
  for (int k = 1; k < 8; k <<= 1) {
    const bool up = lane & (o * k);
#pragma unroll
    for (int j = 0; j < 4 / k; j++) s[j] = (up ? s[2 * j + 1] : s[2 * j]) + __shfl_xor_sync(~0u, up ? s[2 * j] : s[2 * j + 1], o * k);
  }
  return s[0];
}
constexpr int OWN = 8, PEER = 9;
static_assert((OA_SLOTS >> OWN * 4 & 15) * SLOT == OFF_V && (OA_SLOTS >> PEER * 4 & 15) * SLOT == OFF_PK, "");
template <int B> __device__ __forceinline__ void verify_tiles(uint32_t sb, Scratch* gs, int tm, int tn, int w, int lane) {
  const uint32_t par = lds32(sb + OFF_MISC + 24), fix = sb + BAR_FIX + (B * 4 + w) * 8;
  uint32_t slots = (uint32_t)(OA_SLOTS >> B * 40);
#pragma unroll 1
  for (int i = 0; i < 8 - 2 * B; i++, slots >>= 4) {
    const uint32_t a = sb + OFF_RING + (slots & 15) * SLOT + w * 1024, cw = a + lane * 32 + (lane >> 2) * 4;
    if (!B && i == 4) mbar_wait(sb + BAR_EMPTY + 7 * 8, 1);
    mbar_wait(sb + BAR_LAND + i * 8, B);
    for (;;) {
      const uint32_t u0 = lds32(cw), u1 = lds32(cw + 4096), u2 = lds32(cw + 8192), u3 = lds32(cw + 12288);
      if (__all_sync(~0u, !(mism(mism(u0, u1, par), mism(u2, u3, par), 0) & 1))) break;
      const uint4* src = gs->o[tm][!B ? i : DYN ? lds32(sb + OFF_MISC + (i & 4)) >> (i & 3) * 8 & 15 : i < (tn & 6) ? i + 8 : i + 10] + w * 64;
      const uint32_t ph = !mbar_test(fix, 1);
      fence_async_smem();
      __syncwarp();
      if (elect()) {
        mbar_expect_tx(fix, 4096);
#pragma unroll 1
        for (int j = 0; j < 4; j++) bulk_load(a + j * 4096, src + j * 256, 1024, fix);
      }
      mbar_wait(fix, ph);
    }
    mbar_arrive_warp(sb + BAR_OFULL + (i < 5 ? i : i - 5) * 8);
  }
}
template <bool BY_SM> struct Tile {
  int sm, tm, tn, mu;
  bool spare;
  __device__ __forceinline__ Tile() {
    if (BY_SM) asm volatile("mov.u32 %0, %%smid;" : "=r"(sm));
    else sm = blockIdx.x + (blockIdx.x >= 120) * 4;
    const int tp = sm >> 1, pr = sm & 1;
    const int v = tp < 32 ? tp : tp < 60 ? (tp * 293 - 928) >> 8 : tp * 8 - 464, g = v & 7, i = v >> 3;
    tm = (v & 6) * 2 + (i & 3); tn = (v & 1) * 4 + (v >> 4 & 2) + pr;
    mu = i == 5 ? 112 : g * 14 + (i - (i > 5)) * 2 + pr;
    spare = (tp | 1) == 61;
  }
};

template <bool BY_SM> __global__ void __cluster_dims__(2, 1, 1) __launch_bounds__(NTHREADS, 1) fused_kernel(const __nv_bfloat16* __restrict__ px, Scratch* gs, const __nv_bfloat16* __restrict__ w_gate,
             const __nv_bfloat16* __restrict__ w_up, const __nv_bfloat16* __restrict__ w_r, const __nv_bfloat16* __restrict__ gate_w, const __nv_bfloat16* __restrict__ w_down, __nv_bfloat16* __restrict__ pout,
             const __grid_constant__ Params p) {
  extern __shared__ __align__(1024) uint8_t smem[];
  const uint32_t sb = __shfl_sync(~0u, (uint32_t)__cvta_generic_to_shared(smem), 0);
  const int tid = threadIdx.x, lane = tid & 31;
  const int warp = __shfl_sync(~0u, tid >> 5, 0), wg = warp >> 2;
  const uint32_t t_start = clock32();
  const Tile<BY_SM> tile;
  const int tm = tile.tm, tn = tile.tn, mu = tile.mu, cta = tm * 8 + tn;
  const uint32_t zero = tile.sm >> 12;
  if (warp == 0) {
#pragma unroll
    for (int s = 0; s < PRE; s++)
      if (elect()) mbar_init(sb + BAR_FULL + s * 8, 1);
    asm volatile("fence.mbarrier_init.release.cluster;" ::: "memory");
    if (!tile.spare) {
#pragma unroll
      for (int s = 0; s < PRE; s++) {
        if (elect()) tma3d(sb + OFF_W1 + s * WQKV_BYTES, &p.w, tn * 64, s * 64, 0, sb + BAR_FULL + s * 8);
        if (elect()) tma2d(sb + OFF_RING + s * SLOT, &p.x, s * 64, tm * 128, sb + BAR_FULL + s * 8);
        PROF(lane == 0, 64 + s);
      }
      if (elect()) {
#pragma unroll
        for (int s = 0; s < PRE; s++) mbar_expect_tx(sb + BAR_FULL + s * 8, SLOT + WQKV_BYTES);
      }
    }
  }
  if (warp) {
    const int wi = warp == 15 ? 0 : warp;
    const int cnt = wi < 7 ? 1 : wi < 13 ? 4 : 5;
#pragma unroll
    for (int i = 0; i < 4; i++)
      if ((i >= PRE || wi) && elect()) mbar_init(sb + OFF_BAR + wi * 32 + i * 8, cnt);
    asm volatile("fence.mbarrier_init.release.cluster;" ::: "memory");
  }
  __syncthreads();
  if (tile.spare) {
    if (warp == 0) {
      const unsigned tag = (ld_relaxed(&gs->spare[tile.sm & 3]) + 1) & 0xFFF;
      const unsigned long long t0 = gtime();
      uint4 r4;
      do {
        __nanosleep(2048);
        if (gtime() - t0 > WATCHDOG_NS) __trap();
        r4 = ld_relaxed4(&gs->rslot[tile.sm & 3][lane * 4]);
      } while (!__all_sync(~0u, (((r4.x ^ tag) | (r4.y ^ tag) | (r4.z ^ tag) | (r4.w ^ tag)) & 0xFFF) == 0));
      if (tid == 0) st_relaxed(&gs->spare[tile.sm & 3], tag);
    }
    return;
  }

  if (wg == 3) {
    asm volatile("setmaxnreg.dec.sync.aligned.u32 24;");
    if (warp == 12) {
      mbar_wait(sb + BAR_PUB, 0);
      while (!__all_sync(~0u, ld_relaxed(gs->cnt[tm]) == 0x44444444u)) __nanosleep(A_SLEEP);
      if (FN) { fence_acquire(); fence_async_global(); }
      PROF(lane == 0, 7);
      mbar_wait(sb + BAR_GATE, 0);
      uint32_t slots = (uint32_t)OA_SLOTS, deps = 0xA9877654u;
#pragma unroll 1
      for (int i = 0; i < 8; i++, deps >>= 4, slots >>= 4) {
        mbar_wait(sb + BAR_EMPTY + (deps & 15) * 8, i < 5);
        if (elect()) bulk_load(sb + OFF_RING + (slots & 15) * SLOT, gs->o[tm][i], SLOT, sb + BAR_LAND + i * 8);
        if (elect()) mbar_expect_tx(sb + BAR_LAND + i * 8, SLOT);
        PROF(lane == 0, 44 + i);
      }
      slots = (uint32_t)(OA_SLOTS >> 40);
      uint32_t ws = (uint32_t)(OW_SLOTS >> 40), todo = 0x44444444u ^ 0x44u << (tn & 6) * 4, seen = 0, st = 0;
      mbar_wait(sb + BAR_PUB + 8, 0);
#pragma unroll 1
      for (int i = 0; i < 6; i++, slots >>= 4, ws >>= 4) {
        const uint32_t need = DYN ? todo : todo & -todo;
        if (!(seen & need)) {
          while (!((seen = __shfl_sync(~0u, ld_relaxed(gs->cnt[16 + tm]), 0)) & need)) __nanosleep(B_SLEEP);
          if (FN) { fence_acquire(); fence_async_global(); }
        }
        const uint32_t bit = seen & need & -(seen & need), slab = 8 + ((31 - __clz(bit)) >> 2);
        todo ^= bit;
        if (DYN && elect()) asm volatile("st.shared.u8 [%0], %1;" ::"r"(sb + OFF_MISC + i), "r"(slab) : "memory");
        mbar_wait(sb + BAR_OEMPTY + st * 8, i < 5);
        if (elect()) bulk_load(sb + OFF_RING + (slots & 15) * SLOT, gs->o[tm][slab], SLOT, sb + BAR_LAND + i * 8);
        if (DYN && elect()) tma3d(sb + OFF_RING + (ws & 15) * SLOT, &p.wo, 0, slab * 64, tn * 2, sb + BAR_OFULL + st * 8);
        if (elect()) mbar_expect_tx(sb + BAR_LAND + i * 8, SLOT);
        if (DYN && elect()) mbar_expect_tx(sb + BAR_OFULL + st * 8, SLOT);
        PROF(lane == 0, 54 + i);
        st = st == 4 ? 0 : st + 1;
      }
    } else if (warp == 13) {
#pragma unroll 1
      for (int g = PRE; g < 32; g++) {
        const bool reuse = (g >> 2) == 4;
        const uint32_t s = g & 3, full = sb + BAR_FULL + (g & 7) * 8, c0 = tn * 64 + (g & 16) * 32, c1 = (g < 16 ? g : g - 4 & 15) * 64;
        if (g < 4) while ((int)(clock32() - t_start) < g * ST1) {}
        mbar_wait(sb + BAR_EMPTY + (g + 4 & 7) * 8, (g + 4 >> 3 & 1) ^ 1);
        if (!reuse && elect()) tma2d(sb + OFF_RING + s * SLOT, &p.x, c1, tm * 128, full);
        if (elect()) tma3d(sb + OFF_W1 + s * WQKV_BYTES, &p.w, c0, c1, 0, full);
        if (elect()) mbar_expect_tx(full, reuse ? WQKV_BYTES : SLOT + WQKV_BYTES);
        PROF(lane == 0, 64 + g);
        const uint32_t i = g - RT_G0;
        if (i < 4 && elect()) {
          mbar_expect_tx(sb + BAR_RT + i * 8, i ? 8192 : 8192 + 4096);
          tma2d(sb + OFF_PK + i * 8192 + (i == 3) * 1024, &p.xr, ((i + RT_ROT) & 3) * 256, cta * 16, sb + BAR_RT + i * 8);
          if (i == 0) { bulk_load(sb + OFF_KVB, w_r, 2048, sb + BAR_RT); bulk_load(sb + OFF_KVB + 2048, gate_w, 2048, sb + BAR_RT); }
        }
        const uint32_t c = g - MOD_START;
        if (c == MOD_BUFS) mbar_wait(sb + BAR_RTD, 0);
        if (c < MOD_BUFS0 && mu < MOD_CTAS && elect()) {
          PROF(true, 192 + c);
          const uint32_t mb = c < MOD_BUFS ? c + 2 : c - MOD_BUFS, mfull = sb + BAR_MFULL + mb * 8, mdst = sb + OFF_V + mb * MOD_STEP;
          mbar_expect_tx(mfull, c ? 8192 : 8192 + 2048);
          tma3d(mdst, &p.gate, mu * 32, c * 16, 0, mfull); tma3d(mdst + 4096, &p.up, mu * 32, c * 16, 0, mfull);
        }
        const uint32_t pc = g - PF_MOD;
        if (pc < 16 && elect()) bulk_prefetch((cta & 64 ? w_up : w_gate) + (size_t)(pc * 64 + (cta & 63)) * F_, F_ * 2);
      }
      mbar_arrive_warp(sb + BAR_GATE);
      const uint32_t lowb = (1u << (tn & 6) * 4) - 1;
      uint64_t slabs = (uint64_t)((0xFEDCBA98u & lowb) | (0xFEDCBAu & ~lowb)) << 40 | (uint64_t)(8 + (tn ^ 1)) << 36 | (uint64_t)(8 + tn) << 32 | 0x76543210u;
      uint64_t deps = 0x8CBA98CBA9876554ull, ws = OW_SLOTS;
      uint32_t full = sb + BAR_OFULL, ph = 1;
#pragma unroll 1
      for (int g = 0; g < (DYN ? 10 : 16); g++, slabs >>= 4, deps >>= 4, ws >>= 4) {
        mbar_wait(sb + BAR_EMPTY + ((uint32_t)deps & 15) * 8, ph);
        if (elect()) tma3d(sb + OFF_RING + ((uint32_t)ws & 15) * SLOT, &p.wo, 0, ((uint32_t)slabs & 15) * 64, tn * 2, full);
        if (elect()) mbar_expect_tx(full, SLOT);
        PROF(lane == 0, 96 + g);
        if (g >> 1 == OWN / 2 && lane < 4) mbar_arrive(full);
        if (DYN && g == PW && tm < 8 && elect())
          asm volatile("cp.async.bulk.prefetch.tensor.3d.L2.global [%0, {%1, %2, %3}];" ::"l"(&p.wo), "r"(0), "r"((8 + tm) * 64), "r"(tn * 2) : "memory");
        full += 8;
        if (full == sb + BAR_OFULL + 40) { full -= 40; ph ^= 1; }
      }
    } else if (warp == 14) {
      if (mu < MOD_CTAS) {
        uint32_t full = sb + BAR_MFULL + 16, dst = sb + OFF_MOD, ph = 0;
#pragma unroll 1
        for (int c = MOD_BUFS0; c < 24; c++) {
          mbar_wait(full + (BAR_MEMPTY - BAR_MFULL), ph);
          PROF(lane == 0, 192 + c);
          if (c < 16) {
            if (elect()) { tma3d(dst, &p.gate, mu * 32, c * 16, 0, full); tma3d(dst + 4096, &p.up, mu * 32, c * 16, 0, full); }
          } else if (elect()) tma3d(dst, &p.down, 0, mu * 32 + (c - 16) * 4, 0, full);
          if (elect()) mbar_expect_tx(full, 8192);
          if (PD && (uint32_t)(c + PD - 16) < 8 && elect()) bulk_prefetch(w_down + (size_t)(mu * 32 + (c + PD - 16) * 4) * D_, 8192);
          full += 8; dst += MOD_STEP;
          if (full == sb + BAR_MFULL + MOD_BUFS0 * 8) { full -= MOD_BUFS * 8; dst = sb + OFF_MOD; ph ^= 1; }
        }
      }
      if (elect()) {
      mbar_wait(sb + BAR_IDX, 0);
      const bool paired = PAIRED && ld_relaxed(&gs->block[cta ^ 1]) == (blockIdx.x ^ 1);
      if (paired) mbar_expect_tx(sb + BAR_PEER, SLOT);
      mbar_expect_tx(sb + BAR_X, 32768);
      mbar_wait(sb + BAR_OEMPTY + 3 * 8, 0);
      tma2d(sb + OFF_RES, &p.x, tn * 128, tm * 128, sb + BAR_X);
      mbar_wait(sb + BAR_OEMPTY + 4 * 8, 0);
      tma2d(sb + OFF_RES + RES_H, &p.x, tn * 128 + 64, tm * 128, sb + BAR_X);
      if (!paired) {
        mbar_wait(sb + BAR_OWN, 0);
        while (!(ld_relaxed(gs->cnt[16 + tm]) & 4u << (tn ^ 1) * 4)) __nanosleep(32);
        fence_acquire();
        fence_async_global();
        const uint32_t par = lds32(sb + OFF_MISC + 24);
        for (uint32_t ph = !mbar_test(sb + BAR_MFULL, 1), bad = 1; bad & 1; ph ^= 1) {
          fence_async_smem();
          mbar_expect_tx(sb + BAR_MFULL, SLOT);
          bulk_load(sb + OFF_PK, gs->o[tm][8 + (tn ^ 1)], SLOT, sb + BAR_MFULL);
          mbar_wait(sb + BAR_MFULL, ph);
          bad = 0;
#pragma unroll 1
          for (int i = 0; i < 512; i++) bad |= lds32(sb + OFF_PK + i * 32 + (i & 28)) ^ par;
        }
        mbar_arrive(sb + BAR_PEER);
      }
      }
    } else {
#pragma unroll 1
      for (int i = 2; i < 8; i++)
        if (elect()) asm volatile("prefetch.tensormap [%0];" ::"l"(&p.x + i) : "memory");
      mbar_wait_bounded(sb + BAR_DONE, 0);
    }
  } else if (wg == 2) {
    asm volatile("setmaxnreg.dec.sync.aligned.u32 40;");
    const int mw = warp & 3;
    if (mw == 0) {
      const unsigned tag = (ld_relaxed(&gs->rslot[tn][cta]) + 1) & 0xFFF;
#pragma unroll
      for (int i = 0; i < 2; i++)
        if (lane < 28) ((float4*)gs)[cta * 56 + i * 28 + lane] = make_float4(0.f, 0.f, 0.f, 0.f);
      if (lane == 29) gs->block[cta] = blockIdx.x;
      fence_release();
      nb_sync(NB_KEY, 160);
      const uint4 k4 = lds128(sb + OFF_MISC);
      if (lane < 8) st_relaxed(&gs->rslot[lane][cta], max(max(k4.x, k4.y), max(k4.z, k4.w)) | tag);
      if (lane < 16) st_relaxed(&gs->gslot[cta * 16 + lane], lds32(sb + OFF_G + lane * 4) | tag);
      PROF(lane == 0, 20);
      uint4 r4;
      do {
        __nanosleep(RT_SLEEP);
        r4 = ld_relaxed4(&gs->rslot[tn][lane * 4]);
      } while (!__all_sync(~0u, (((r4.x ^ tag) | (r4.y ^ tag) | (r4.z ^ tag) | (r4.w ^ tag)) & 0xFFF) == 0));
      const int c0 = 0xFFF0 - lane * 64;
      unsigned key = max(max((r4.x & 0xFFFF0000u) | (c0 + ((r4.x >> 12) & 15)), (r4.y & 0xFFFF0000u) | (c0 - 16 + ((r4.y >> 12) & 15))),
                         max((r4.z & 0xFFFF0000u) | (c0 - 32 + ((r4.z >> 12) & 15)), (r4.w & 0xFFFF0000u) | (c0 - 48 + ((r4.w >> 12) & 15))));
      key = __reduce_max_sync(~0u, key);
      if (elect()) {
        sts32(sb + OFF_MISC + 16, key);
        sts32(sb + OFF_MISC + 24, tag & 1);
        if (mu < MOD_CTAS) {
          const __nv_bfloat16* row = px + (size_t)(0xFFFF - (key & 0xFFFF)) * D_;
          bulk_load(sb + OFF_XSEL, row, 1024, sb + BAR_MFULL + 16);
          bulk_load(sb + OFF_XSEL + MOD_STEP, row + 512, 1024, sb + BAR_MFULL + 16);
        }
      }
      PROF(lane == 0, 21);
      do {
        r4 = ld_relaxed4(&gs->gslot[tm * 128 + lane * 4]);
      } while (!__all_sync(~0u, (((r4.x ^ tag) | (r4.y ^ tag) | (r4.z ^ tag) | (r4.w ^ tag)) & 0xFFF) == 0));
      sts128(sb + OFF_G + lane * 16, r4.x & 0xFFFF0000u, r4.y & 0xFFFF0000u, r4.z & 0xFFFF0000u, r4.w & 0xFFFF0000u);
      fence_acquire();
      __syncwarp();
    }
    PROF(tid == 256, 22);
    if (mu >= MOD_CTAS) {
      mbar_arrive_warp(sb + BAR_IDX);
    } else {
      const uint32_t wp = sb + OFF_V + (mw >> 1) * 4096 + (mw & 1) * 512 + lane * 16;
      uint32_t mp = sb + OFF_XSEL + (mw & 1) * 64 + (lane >> 2) * 8, mc = 128;
      float acc[8] = {0.f, 0.f, 0.f, 0.f, 0.f, 0.f, 0.f, 0.f};
      uint32_t b = 2, ph = 0;
#pragma unroll 1
      for (int c = 0; c < 24; c++) {
        if (MOD_SLEEP && c >= MOD_S0) __nanosleep(MOD_SLEEP);
        mbar_wait(sb + BAR_MFULL + b * 8, ph);
        PROF_C(tid == 256, 216 + c);
        const uint32_t a = wp + b * MOD_STEP;
        const uint2 m = lds64(mp);
        const uint4 w0 = lds128(a), w1 = lds128(a + 1024), w2 = lds128(a + 2048), w3 = lds128(a + 3072);
        mp += c == 7 ? MOD_STEP - 1024 + 128 : mc;
        const uint32_t m0 = dup_lo(m.x), m1 = dup_hi(m.x), m2 = dup_lo(m.y), m3 = dup_hi(m.y);
        uint4 q = make_uint4(mul_bf2(w0.x, m0), mul_bf2(w0.y, m0), mul_bf2(w0.z, m0), mul_bf2(w0.w, m0));
        q = make_uint4(fma_bf2(w1.x, m1, q.x), fma_bf2(w1.y, m1, q.y), fma_bf2(w1.z, m1, q.z), fma_bf2(w1.w, m1, q.w));
        q = make_uint4(fma_bf2(w2.x, m2, q.x), fma_bf2(w2.y, m2, q.y), fma_bf2(w2.z, m2, q.z), fma_bf2(w2.w, m2, q.w));
        mbar_arrive_warp(sb + BAR_MEMPTY + b * 8 + (w3.x & zero));
        q = make_uint4(fma_bf2(w3.x, m3, q.x), fma_bf2(w3.y, m3, q.y), fma_bf2(w3.z, m3, q.z), fma_bf2(w3.w, m3, q.w));
        if (++b == 5) b = c < 3 ? 0 : 2;
        if (b == 2) ph ^= 1;
        acc[0] += bf_lo(q.x); acc[1] += bf_hi(q.x); acc[2] += bf_lo(q.y); acc[3] += bf_hi(q.y);
        acc[4] += bf_lo(q.z); acc[5] += bf_hi(q.z); acc[6] += bf_lo(q.w); acc[7] += bf_hi(q.w);
        if (c == 15) {
          const uint32_t ft = fresh_tid(), fl = ft & 31;
          sts32(sb + OFF_PART + (ft & 96) * 4 + ((ft & 3) * 8 + (fl >> 2)) * 4, __float_as_uint(butterfly8(acc, fl, 4)));
          nb_sync(NB_MODW, 128);
          const float* part = (const float*)(smem + OFF_PART) + fl;
          const float gp = bf_round(part[0] + part[32]), up = bf_round(part[64] + part[96]);
          *(__nv_bfloat16*)(smem + OFF_PART + 512 + fl * 2) = __float2bfloat16_rn(bf_round(gp * sigmoidf_(gp)) * up);
          __syncwarp();
          mp = sb + OFF_PART + 512; mc = 8;
#pragma unroll
          for (int i = 0; i < 8; i++) acc[i] = 0.f;
          PROF(lane == 0 && mw == 0, 23);
        }
      }
      float4* yacc = gs->y[tn & 1][0] + (fresh_tid() & 127);
      red_add4(yacc, acc[0], acc[1], acc[2], 1.f);
      red_add4(yacc + 128, acc[3], acc[4], acc[5], 1.f);
      red_add4(yacc + 256, acc[6], acc[7], 0.f, 1.f);
      PROF(lane == 0 && mw == 0, 25);
    }
    mbar_wait(sb + BAR_GATE, 0);
    mbar_wait(sb + BAR_IDX, 0);
    verify_tiles<0>(sb, gs, tm, tn, mw, lane);
    const unsigned key = lds32(sb + OFF_MISC + 16);
    const int sel = 0xFFFF - (int)(key & 0xFFFF) - tm * 128;
    if (mw == 0 && sel >= 0 && sel < 128) {
      const unsigned k16 = key >> 16;
      const float rs = bf_round(sigmoidf_(__uint_as_float(((k16 & 0x8000u) ? (k16 & 0x7FFFu) : (~k16 & 0xFFFFu)) << 16)));
      float v[12];
      const float4* yp = gs->y[lane >> 4][0] + tn * 16 + (lane & 15);
      for (;;) {
#pragma unroll
        for (int i = 0; i < 3; i++) {
          const float4 u = ld_relaxed_f4(yp + i * 128);
          v[4 * i] = u.x; v[4 * i + 1] = u.y; v[4 * i + 2] = u.z; v[4 * i + 3] = u.w;
        }
        const float n = v[3] + v[7] + v[11];
        if (__all_sync(~0u, n + __shfl_xor_sync(~0u, n, 16) == 3.f * MOD_CTAS)) break;
        __nanosleep(Y_SLEEP);
      }
#pragma unroll
      for (int i = 0; i < 10; i++) v[i] = bf_round(bf_round(v[i] + __shfl_xor_sync(~0u, v[i], 16)) * rs);
      PROF(lane == 0, 24);
      mbar_wait(sb + BAR_X, 0);
      if (lane < 16) {
        uint4* xp = (uint4*)(smem + OFF_RES + (lane >> 3) * RES_H + sel * 128 + (((lane ^ sel) & 7) << 4));
        const uint4 xv = *xp;
        *xp = make_uint4(pack2(bf_lo(xv.x) + v[0], bf_hi(xv.x) + v[1]), pack2(bf_lo(xv.y) + v[2], bf_hi(xv.y) + v[4]),
                         pack2(bf_lo(xv.z) + v[5], bf_hi(xv.z) + v[6]), pack2(bf_lo(xv.w) + v[8], bf_hi(xv.w) + v[9]));
      }
      __syncwarp();
      mbar_arrive_warp(sb + BAR_Y);
    }
  } else {
    asm volatile("setmaxnreg.inc.sync.aligned.u32 224;");
    const int w = warp & 3, wt = tid & 127;
    const int nb_self = NB_WG0 + wg;
    const uint64_t da0 = mkdesc(sb + OFF_RING, 16, 1024, 1), db0 = mkdesc(sb + OFF_RING, 8192, 1024, 1);

    if (wg == 1) {
      sts128(sb + OFF_ONES - (w >> 1) * 9216 + (w & 1) * 512 + lane * 16, 0x3F803F80u, 0x3F803F80u, 0x3F803F80u, 0x3F803F80u);
      sts32(sb + OFF_MISC + 20, 0x3FB8AA3Bu);
      fence_async_smem();
      float s[8] = {0.f, 0.f, 0.f, 0.f, 0.f, 0.f, 0.f, 0.f};
      uint32_t mask = 0xffff0000u;
#pragma unroll 1
      for (int i = 0; i < 4; i++) {
        const uint32_t u = (i + RT_ROT) & 3;
        mbar_wait(sb + BAR_RT + i * 8, 0);
        const uint4 wr = lds128(sb + OFF_KVB + u * 512 + lane * 16), gw = lds128(sb + OFF_KVB + 2048 + u * 512 + lane * 16);
        uint4 xv[4];
#pragma unroll
        for (int r = 0; r < 4; r++) xv[r] = lds128(sb + OFF_PK + i * 8192 + (i == 3) * 1024 + (w * 4 + r) * 512 + lane * 16);
        const float wf[16] = {bf_lo(wr.x), bf_hi(wr.x), bf_lo(wr.y), bf_hi(wr.y), bf_lo(wr.z), bf_hi(wr.z), bf_lo(wr.w), bf_hi(wr.w),
                              bf_lo(gw.x), bf_hi(gw.x), bf_lo(gw.y), bf_hi(gw.y), bf_lo(gw.z), bf_hi(gw.z), bf_lo(gw.w), bf_hi(gw.w)};
#pragma unroll
        for (int r = 0; r < 4; r++) {
          const uint4 xq = xv[r];
          const float xf[8] = {bf_lo(xq.x), __uint_as_float(xq.x & mask), bf_lo(xq.y), bf_hi(xq.y), bf_lo(xq.z), bf_hi(xq.z), bf_lo(xq.w), bf_hi(xq.w)};
#pragma unroll
          for (int j = 0; j < 8; j++) { s[2 * r] = fmaf(xf[j ^ 1], wf[j ^ 1], s[2 * r]); s[2 * r + 1] = fmaf(xf[j ^ 1], wf[8 + (j ^ 1)], s[2 * r + 1]); }
          mask = ((__float_as_uint(s[2 * r]) | __float_as_uint(s[2 * r + 1])) & zero) | 0xffff0000u;
        }
      }
      mbar_arrive_warp(sb + BAR_RTD);
      float v = butterfly8(s, lane, 1);
      PROF_C(wt == 0 && v != 12345.f, 19);
      v += __shfl_xor_sync(~0u, v, 8);
      v = bf_round(v + __shfl_xor_sync(~0u, v, 16));
      const unsigned rb = __float_as_uint(v) >> 16, row = w * 4 + ((lane & 7) >> 1);
      unsigned key = (lane & 1) ? 0u : ((((rb & 0x8000u) ? (~rb & 0xFFFFu) : (rb | 0x8000u)) << 16) | ((15 - row) << 12));
      key = __reduce_max_sync(~0u, key);
      if (lane == 0) sts32(sb + OFF_MISC + w * 4, key);
      if (lane < 8 && (lane & 1)) sts32(sb + OFF_G + row * 4, __float_as_uint(bf_round(sigmoidf_(v))));
      nb_arrive(NB_KEY, 160);
      nb_sync(NB_ORDER_12, 256);
    }
    uint4* const kvacc = &gs->kv[wg][tn][0][wt];
    float aq[64];
    uint32_t su[9];
    float pq[64], ak[64], av[64];
    auto proj = [&](float (&d)[64], int j, uint32_t s, int sc) {
#pragma unroll
      for (int kk = 0; kk < 4; kk++)
        mma128<1, 0>(d, da0 + ((OFF_W1 >> 4) + s * (WQKV_BYTES >> 4) + j * 512 + kk * 128), da0 + (s * (SLOT >> 4) + kk * 2), kk ? 1 : sc);
    };
    PROF_C(wt == 0, 1 + wg * 8);
#pragma unroll 1
    for (int g = 0; g < 15; g++) {
      mbar_wait(sb + BAR_FULL + (g & 7) * 8, g >> 3);
      if (g == 0) PROF_C(wt == 0, 2 + wg * 8);
      wg_fence();
      proj(ak, 1, g & 3, g);
      wg_commit();
      wg_wait<1>();
      if (g) mbar_arrive_warp(sb + BAR_EMPTY + (g - 1 & 7) * 8);
      if (g == 14) break;
      wg_fence();
      proj(av, 2, g & 3, g);
      proj(pq, 0, g & 3, g);
      wg_commit();
    }
    auto finish = [&](auto reorder) {
      constexpr int re = decltype(reorder)::value, vk = re ? VK1 : VK, mm = re ? MM1 : MM, kl = re ? KL1 : KL, qw = re ? QW1 : 0;
      float c[36];
      uint32_t pk[8][4];
      if (!re) {
        wg_fence();
        proj(av, 2, 2, 1);
        proj(pq, 0, 2, 1);
        wg_commit();
      }
      mbar_wait(sb + BAR_FULL + 7 * 8, 1);
      wg_fence();
      proj(ak, 1, 3, 1);
      wg_commit();
      if (!re) {
        wg_wait<1>();
        mbar_arrive_warp(sb + BAR_EMPTY + 6 * 8);
      }
      wg_fence();
      if (re) proj(av, 2, 2, 1);
      proj(av, 2, 3, 1);
      wg_commit();
      if (!re) {
        proj(pq, 0, 3, 1);
        wg_commit();
        if (wg == 0) nb_arrive(NB_ORDER_12, 256);
      }
      mbar_wait(sb + BAR_IDX, 0);
      if (wg == 1) nb_sync(NB_STG, 256);
      wg_wait<2 - re>();
      pin(ak);
      PROF_C(wt == 0, 3 + wg * 8);
      const uint32_t va = sb + OFF_V + (w * 16 + (lane & 15)) * 128;
      uint32_t lk[8];
#pragma unroll
      for (int u = 0; u < kl; u++) lk[u] = 0x3FB8AA3Bu;
#pragma unroll
      for (int u = 0; u < 8; u++) {
        if (re && (u == Q0 || u == Q0 + QS)) {
          wg_fence();
          proj(pq, 0, u == Q0 ? 3 - re : 3, 1);
          wg_commit();
          if (wg == 0 && u != Q0) nb_arrive(NB_ORDER_12, 256);
          if (qw) {
            wg_wait<7>();
            const uint32_t l = lds32(sb + OFF_MISC + 20);
#pragma unroll
            for (int t = u; t < u + kl && t < 8; t++) lk[t] = l;
          }
        }
#pragma unroll
        for (int i = 0; i < 4; i++) pk[u][i] = phi2(ak[8 * u + 2 * i], ak[8 * u + 2 * i + 1], __uint_as_float(lk[u]));
        if (u == vk) { wg_wait<re ? (vk >= Q0) + (vk >= Q0 + QS) : 1>(); pin(av); }
        if (u == M0 && re) { wg_wait<(M0 >= Q0 + QS)>(); mbar_arrive_warp(sb + BAR_EMPTY + 6 * 8); }
        if (u == mm) { wg_wait<0>(); mbar_arrive_warp(sb + BAR_EMPTY + 7 * 8); }
        const uint32_t z = mism(pk[u][0], pk[u][1], 0) | mism(pk[u][2], pk[u][3], 0);
#pragma unroll
        for (int t = u < vk ? 8 : (u - vk) * 8 / (8 - vk); t < (u - vk + 1) * 8 / (8 - vk); t++) {
          const float* v = &av[8 * t];
          stsm4(va + (t >> 2) * 9216 + ((((lane >> 4) + 2 * (t & 3)) ^ (lane & 7)) << 4) + (z & zero), pack2(v[0], v[1]), pack2(v[2], v[3]), pack2(v[4], v[5]), pack2(v[6], v[7]));
        }
        if (u + kl < 8) lk[u + kl] = lds32(sb + OFF_MISC + 20 + (u < vk ? z & zero : 0));
      }
      fence_async_smem();
      nb_sync(nb_self, 128);
      PROF_C(wt == 0, 8 + wg * 8);
      const uint64_t dv = mkdesc(sb + OFF_V, 16, 1024, 1);
      wg_fence();
#pragma unroll
      for (int kk = 0; kk < 8; kk++) mma_ktv(c, pk[kk], dv + ((kk >> 2) * 576 + (kk & 3) * 2), kk ? 1 : 0);
      wg_commit();
      if (wg == 1) nb_arrive(NB_ORDER_3O, 256);
      wg_wait<0>();
      pin(c); pin(pq);
#pragma unroll
      for (int i = 0; i < 64; i++) aq[i] = pq[i];
      PROF_C(wt == 0, 4 + wg * 8);
#pragma unroll
      for (int i = 0; i < 8; i++) {
        const int j = (i & 3) * 4 + (i >> 2) * 2;
        su[i] = w >= 2 ? pack2(c[16 + j], c[17 + j]) : pack2(c[j], c[j + 1]);
      }
      su[8] = pack2(c[32], c[34]);
#pragma unroll
      for (int u = 0; u < 3; u++)
        if (u < R0 || wg) red_add_bf(kvacc + u * 128, su[3 * u], su[3 * u + 1], su[3 * u + 2]);
    };
    if (TR == 2) {
      if (wg == 0) finish(std::integral_constant<int, 0>());
      else finish(std::integral_constant<int, 1>());
    } else finish(std::integral_constant<int, TR>());
    const uint32_t par = lds32(sb + OFF_MISC + 24);
    {
      const bool paired = PAIRED && ld_relaxed(&gs->block[cta ^ 1]) == (blockIdx.x ^ 1);
      uint4 kv[3];
      int tries = wg ? 0 : TRY_A;
      const uint8_t* gl = smem + OFF_MISC + 20;
      asm volatile("" : "+l"(gl));
      const uint32_t l2e = ld_generic(gl);
    auto stage_kv = [&]() {
      const uint32_t kb = sb + OFF_KVB + w * 256, ka = kb + (lane & 3) * KVB_N + (lane >> 2) * 16;
      sts128(ka, kv[0].x, kv[0].y, kv[0].z, kv[1].x);
      sts128(ka + 128, kv[1].y, kv[1].z, kv[2].x, kv[2].y);
      sts32(kb + 4 * KVB_N + lane * 4, dup_lo(kv[2].z));
      sts32(kb + 4 * KVB_N + 128 + lane * 4, dup_hi(kv[2].z));
      return __all_sync(~0u, (kv[0].w & kv[1].w & kv[2].w) == 0x41804180u && (kv[0].w | kv[1].w | kv[2].w) == 0x41804180u);
    };
      bool have = false;
      const uint32_t qa = sb + OFF_PK + ((lane >> 4) * 8 + (lane & 7)) * 128 + (((2 * w + ((lane >> 3) & 1)) ^ (lane & 7)) << 4);
      uint32_t lq[8];
#pragma unroll
      for (int u = 0; u < QA; u++) lq[u] = l2e;
#pragma unroll
      for (int u = 0; u < 8; u++) {
        uint32_t r[4];
        if (u == KF && wg) {
#pragma unroll
          for (int i = 0; i < 3; i++) kv[i] = ld_relaxed4(kvacc + i * 128);
        }
#pragma unroll
        for (int i = 0; i < 4; i++) r[i] = phi2(aq[8 * u + 2 * i], aq[8 * u + 2 * i + 1], __uint_as_float(lq[u]));
        stsm4t(qa + u * 2048, r[0], r[1], r[2], r[3]);
        if (u % RS == RS - 1 && u / RS + R0 < 3 && !wg) red_add_bf(kvacc + (u / RS + R0) * 128, su[3 * (u / RS + R0)], su[3 * (u / RS + R0) + 1], su[3 * (u / RS + R0) + 2]);
        if (u + QA < 8) lq[u + QA] = QD ? ld_generic(gl) : lds32(sb + OFF_MISC + 20);
        if (u == KU && wg) have = stage_kv();
      }
      PROF_C(wt == 0, 34 + wg * 2);
      if (NAP_A && !wg) __nanosleep(NAP_A);
      if (KU > 7 && KF < 8 && wg) have = stage_kv();
      for (; !have; tries++) {
        if (tries > RETRY)
          while (ld_relaxed((const unsigned*)&(kvacc - lane)[256 + 31].w) != 0x41804180u) __nanosleep(wg ? KV_SLEEP : KV_SLEEP_A);
#pragma unroll
        for (int i = 0; i < 3; i++) kv[i] = ld_relaxed4(kvacc + i * 128);
        have = stage_kv();
      }
      PROF_C(wt == 0, 5 + wg * 8);
      fence_async_smem();
      nb_sync(nb_self, 128);
      float o[2][2][20];
      const uint64_t dq = mkdesc(sb + OFF_PK, 16, 1024, 1), dz = mkdesc(sb + OFF_KVB, 128, KVB_N, 0);
      wg_fence();
#pragma unroll
      for (int m = 0; m < 2; m++) {
#pragma unroll
        for (int h = 0; h < 2; h++)
#pragma unroll
          for (int kk = 0; kk < 2; kk++) mma_qkvz(o[m][h], dq + (m * 512 + h * 4 + kk * 2), dz + (h * 32 + kk * 16), kk);
        wg_commit();
      }
      if (HOLD < 8 && HP == 0 && wg) nb_arrive(NB_HOLD, 256);
      if (EF == 3 && wg && elect()) red_add(gs->cnt[16 + tm], 1u << tn * 4);
      uint32_t tag[2][4];
#pragma unroll
      for (int i = 0; i < 8; i++) tag[i >> 2][i & 3] = (lane >> 3) == (i & 3) && ((lane ^ (lane >> 3)) & 1) == (i >> 2);
      uint32_t gr[8];
      const uint8_t* ga = smem + OFF_G + (w * 16 + (lane >> 2)) * 4;
      asm volatile("" : "+l"(ga));
#pragma unroll
      for (int i = 0; i < OA; i++) gr[i] = ld_generic(ga + (i >> 2) * 256 + (i & 1) * 32);
      const uint32_t oo = w * 1024 + (lane >> 2) * 64 + (((lane ^ (lane >> 3)) & 3) << 4);
      uint8_t* const og = (uint8_t*)gs->o[tm][wg * 8 + tn] + oo;
      uint32_t ob[8][4];
#pragma unroll
      for (int m = 0; m < 2; m++) {
        if (m == 0) wg_wait<1>(); else wg_wait<0>();
        pin(o[m][0]); pin(o[m][1]);
        if (EF == 2 - m && wg && elect()) red_add(gs->cnt[16 + tm], 1u << tn * 4);
        if (PB == 2 - m && wg) mbar_arrive_warp(sb + BAR_PUB + 8);
        if (m && !wg) nb_arrive(NB_STG, 256);
        if (HOLD < 8 && HP == 1 && m && wg) nb_arrive(NB_HOLD, 256);
        if (m && wg && paired && elect()) mbar_arrive_peer(peer_addr(sb + BAR_PA));
        if (m == 0) PROF_C(wt == 0, 6 + wg * 8);
#pragma unroll
        for (int u = 0; u < 4; u++) {
          const int h = u >> 1, i = u & 1;
          const float* on = o[m][h];
          const float sc = __uint_as_float(gr[m * 4 + u]) * rcp(on[16 + 2 * i] + 1e-6f);
          const uint32_t sc2 = pack2(sc, sc);
#pragma unroll
          for (int j = 0; j < 4; j++) {
            const uint32_t v = HS ? mul_bf2(pack2(on[4 * j + 2 * i], on[4 * j + 2 * i + 1]), sc2) : pack2(on[4 * j + 2 * i] * sc, on[4 * j + 2 * i + 1] * sc);
            asm("lop3.b32 %0, %1, %2, %3, 0xB8;" : "=r"(ob[m * 4 + u][j]) : "r"(v), "r"(tag[i][j]), "r"(par));
          }
          st_relaxed4(og + (h * 8192 + m * 4096 + i * 512), ob[m * 4 + u]);
          if (OWN1 == 2 && wg) sts128(sb + OFF_V + oo + (h * 8192 + m * 4096 + i * 512), ob[m * 4 + u][0], ob[m * 4 + u][1], ob[m * 4 + u][2], ob[m * 4 + u][3]);
          if (HOLD < 8 && HP == 10 + m * 4 + u && wg) nb_arrive(NB_HOLD, 256);
          const int n = m * 4 + u + OA;
          if (n < 8) gr[n] = ld_generic(ga + (n >> 2) * 256 + (n & 1) * 32);
        }
      }
      if ((!EF || !wg) && elect()) red_add(gs->cnt[wg * 16 + tm], 1u << tn * 4);
      if (!PB || !wg) mbar_arrive_warp(sb + BAR_PUB + wg * 8);
      if (HOLD < 8 && HP == 2 && wg) nb_arrive(NB_HOLD, 256);
      PROF(wt == 0, 17 + wg);
      if (wg) {
        auto to_peer = [&]() {
        if (paired) {
          const uint32_t pb = peer_addr(sb);
          mbar_wait(sb + BAR_PA, 0);
#pragma unroll
          for (int u = 0; u < 8; u++) st_async4(pb + OFF_PK + oo + ((u >> 1 & 1) * 8192 + (u >> 2) * 4096 + (u & 1) * 512), ob[u], pb + BAR_PEER);
        }
        };
        if (!OWN1) to_peer();
#pragma unroll
        for (int u = 0, z = 0; u < (OWN1 == 2 ? 0 : 8); u++) {
          sts128(sb + OFF_V + oo + ((u >> 1 & 1) * 8192 + (u >> 2) * 4096 + (u & 1) * 512) + z, ob[u][0], ob[u][1], ob[u][2], ob[u][3]);
          if (PO && u % PO == PO - 1 && u < 7) z = lds32(sb + OFF_ONES) & 16;
        }
        fence_async_smem();
        __syncwarp();
        mbar_arrive_warp(sb + BAR_OWN);
        if (HOLD < 8 && HP == 3) nb_arrive(NB_HOLD, 256);
        PROF(wt == 0, 15);
        if (OWN1) to_peer();
      }
    }
    if (wg == 1) {
      verify_tiles<1>(sb, gs, tm, tn, w, lane);
    } else {
      float acc[2][64];
      nb_sync(NB_ORDER_3O, 256);
      PROF_C(wt == 0, 26);
      uint32_t xr[2][8][4], q[2][2];
      const uint32_t ta = sb + OFF_RES + (uint32_t)(w * 16 + (lane & 15)) * 128;
      const uint64_t do0 = mkdesc(sb + OFF_RING, 16, 512, 2);
      uint64_t xs = OA_SLOTS, ws = OW_SLOTS;
#pragma unroll 1
      for (int g = 0; g < 13 - TL; g++, xs >>= 4, ws >>= 4) {
        const uint32_t r = g * 52 >> 8, s = g - r * 5;
        const uint64_t da = do0 + ((uint32_t)xs & 15) * (SLOT >> 4), db = db0 + ((uint32_t)ws & 15) * (SLOT >> 4);
        if (g == OWN) mbar_wait(sb + BAR_OWN, 0);
        if (g == PEER) { mbar_wait(sb + BAR_PEER, 0); fence_async_smem(); }
        if (g == HOLD) {
          if (HR) { wg_wait<0>(); mbar_arrive_warp(sb + BAR_OEMPTY + (HOLD + 4) % 5 * 8); }
          nb_sync(NB_HOLD, 256);
        }
        mbar_wait(sb + BAR_OFULL + s * 8, r & 1);
        wg_fence();
#pragma unroll
        for (int kk = 0; kk < 4; kk++)
#pragma unroll
          for (int m = 0; m < 2; m++) mma128<0, 1>(acc[m], da + (m * 256 + (kk >> 1) * 512 + (kk & 1) * 2), db + kk * 128, kk ? 1 : g);
        wg_commit();
        wg_wait<1>();
        if (g && (g != HOLD || !HR)) mbar_arrive_warp(sb + BAR_OEMPTY + (s ? s - 1 : 4) * 8);
      }
      mbar_wait(sb + BAR_X, 0);
      const int selw = ((0xFFFF - (int)(lds32(sb + OFF_MISC + 16) & 0xFFFF)) >> 4) - tm * 8 - w;
#pragma unroll
      for (int u = 0; u < 4; u++) {
        const int m = u >> 1, g = 13 - TL + u;
        const float g1 = 1.f - __uint_as_float(lds32(sb + OFF_G + (m * 64 + w * 16 + (u & 1) * 8 + (lane >> 2)) * 4));
        q[m][u & 1] = pack2(g1, g1);
#pragma unroll
        for (int j = 0; j < 4; j++) ldsm4(ta + (u & 1) * RES_H + m * 8192 + ((((lane >> 4) + 2 * j) ^ (lane & 7)) << 4), xr[m][(u & 1) * 4 + j]);
        if (u == 3) break;
        mbar_wait(sb + BAR_OFULL + g % 5 * 8, g / 5 & 1);
        wg_fence();
#pragma unroll
        for (int kk = 0; kk < 4; kk++)
#pragma unroll
          for (int mm = 0; mm < 2; mm++)
            mma128<0, 1>(acc[mm], do0 + ((OA_SLOTS >> g * 4 & 15) * (SLOT >> 4) + mm * 256 + (kk >> 1) * 512 + (kk & 1) * 2), db0 + ((OW_SLOTS >> g * 4 & 15) * (SLOT >> 4) + kk * 128), 1);
        wg_commit();
        wg_wait<1>();
        if (g <= 11) mbar_arrive_warp(sb + BAR_OEMPTY + (g + 4) % 5 * 8);
      }
#pragma unroll
      for (int m = 0; m < 2; m++) {
#pragma unroll
        for (int g = 16 - TL; g < 16; g++) {
          if (m == 0) { mbar_wait(sb + BAR_OFULL + g % 5 * 8, g / 5 & 1); wg_fence(); }
#pragma unroll
          for (int kk = 0; kk < 4; kk++)
            mma128<0, 1>(acc[m], do0 + ((OA_SLOTS >> g * 4 & 15) * (SLOT >> 4) + m * 256 + (kk >> 1) * 512 + (kk & 1) * 2), db0 + ((OW_SLOTS >> g * 4 & 15) * (SLOT >> 4) + kk * 128), 1);
        }
        wg_commit();
      }
      mbar_arrive_warp(sb + BAR_DONE);
      const uint32_t tb = sb + OFF_RES + w * 2048 + (lane >> 3) * 128 + (((lane ^ (lane >> 3)) & 7) << 4), tx = lane & 4 ? 64 : -64;
      uint8_t* const og = (uint8_t*)pout + (size_t)(tm * 128 + w * 16 + (lane >> 3)) * 2048 + tn * 256 + (lane & 7) * 16;
#pragma unroll
      for (int m = 0; m < 2; m++) {
        if (selw == 4 * m) {
          mbar_wait(sb + BAR_Y, 0);
#pragma unroll
          for (int j = 0; j < 8; j++) ldsm4(ta + (j >> 2) * RES_H + m * 8192 + ((((lane >> 4) + 2 * (j & 3)) ^ (lane & 7)) << 4), xr[m][j]);
        }
        if (m == 0) wg_wait<1>(); else wg_wait<0>();
        if (m) PROF(wt == 0, 31);
#pragma unroll
        for (int h = 0; h < 2; h++) {
#pragma unroll
          for (int j = 4 * h; j < 4 * h + 4; j++) {
            const float* v = &acc[m][8 * j];
            stsm4(ta + h * RES_H + m * 8192 + ((((lane >> 4) + 2 * (j & 3)) ^ (lane & 7)) << 4),
                  fma_bf2(xr[m][j][0], q[m][0], pack2(v[0], v[1])), fma_bf2(xr[m][j][1], q[m][1], pack2(v[2], v[3])),
                  fma_bf2(xr[m][j][2], q[m][0], pack2(v[4], v[5])), fma_bf2(xr[m][j][3], q[m][1], pack2(v[6], v[7])));
          }
          if (FS >> m & 1) {
            __syncwarp();
            uint4 t[4];
#pragma unroll
            for (int j = 0; j < 4; j++) t[j] = lds128(tb + h * RES_H + m * 8192 + j * 512 - (j & 1) * tx);
#pragma unroll
            for (int j = 0; j < 4; j++) *(uint4*)(og + (m * 64 + j * 4) * 2048 + h * 128) = t[j];
          } else {
            fence_async_smem();
            __syncwarp();
            if (elect()) tma2d_store(&p.out, sb + OFF_RES + h * RES_H + m * 8192 + w * 2048, tn * 128 + h * 64, tm * 128 + m * 64 + w * 16);
          }
          if (FS != 3 && m && h && elect()) { bulk_commit(); asm volatile("cp.async.bulk.wait_group.read 0;" ::: "memory"); }
        }
        if (!m) PROF(wt == 0, 33);
      }
      PROF(wt == 0, 32);
    }
  }
}

typedef CUresult (*EncodeFn)(CUtensorMap*, CUtensorMapDataType, cuuint32_t, void*, const cuuint64_t*, const cuuint64_t*, const cuuint32_t*,
                             const cuuint32_t*, CUtensorMapInterleave, CUtensorMapSwizzle, CUtensorMapL2promotion, CUtensorMapFloatOOBfill);

void encode(EncodeFn fn, CUtensorMap* m, const void* ptr, int rank, const cuuint64_t* dims, const cuuint64_t* strides, const cuuint32_t* box,
            CUtensorMapSwizzle sw, CUtensorMapDataType dt = CU_TENSOR_MAP_DATA_TYPE_BFLOAT16) {
  const cuuint32_t es[3] = {1, 1, 1};
  fn(m, dt, rank, const_cast<void*>(ptr), dims, strides, box, es, CU_TENSOR_MAP_INTERLEAVE_NONE, sw,
     CU_TENSOR_MAP_L2_PROMOTION_L2_128B, CU_TENSOR_MAP_FLOAT_OOB_FILL_NONE);
}

}

extern "C" void kernel_launch(void* const* d_in, const int* in_sizes, int n_in, void* d_out, int out_size) {
  (void)in_sizes; (void)n_in; (void)out_size;
  EncodeFn fn = nullptr;
  cudaDriverEntryPointQueryResult qr;
  cudaGetDriverEntryPoint("cuTensorMapEncodeTiled", (void**)&fn, cudaEnableDefault, &qr);

  Params p;
  {
    const cuuint64_t dims[2] = {D_, S_}, str[1] = {D_ * 2};
    const cuuint32_t box[2] = {64, 128}, box_st[2] = {64, 16}, box_r[2] = {256, 16};
    encode(fn, &p.xr, d_in[0], 2, dims, str, box_r, CU_TENSOR_MAP_SWIZZLE_NONE);
    encode(fn, &p.x, d_in[0], 2, dims, str, box, CU_TENSOR_MAP_SWIZZLE_128B);
    encode(fn, &p.out, d_out, 2, dims, str, box_st, CU_TENSOR_MAP_SWIZZLE_128B);
  }
  {
    const cuuint64_t dims[3] = {D_, D_, 3}, str[2] = {3 * D_ * 2, D_ * 2};
    const cuuint32_t box[3] = {64, 64, 3};
    encode(fn, &p.w, d_in[1], 3, dims, str, box, CU_TENSOR_MAP_SWIZZLE_128B);
  }
  {
    const cuuint64_t dims[3] = {64, D_, D_ / 64}, str[2] = {D_ * 2, 128};
    const cuuint32_t box[3] = {64, 64, 2};
    encode(fn, &p.wo, d_in[2], 3, dims, str, box, CU_TENSOR_MAP_SWIZZLE_128B);
  }
  {
    const cuuint64_t dims[3] = {F_, D_ / 4, 4}, str[2] = {F_ * 8, F_ * 2};
    const cuuint32_t box[3] = {32, 16, 4};
    encode(fn, &p.gate, d_in[5], 3, dims, str, box, CU_TENSOR_MAP_SWIZZLE_NONE);
    encode(fn, &p.up, d_in[6], 3, dims, str, box, CU_TENSOR_MAP_SWIZZLE_NONE);
  }
  {
    const cuuint64_t dims[3] = {D_ / 4, F_, 2}, str[2] = {D_ * 2, D_};
    const cuuint32_t box[3] = {256, 4, 2};
    encode(fn, &p.down, d_in[7], 3, dims, str, box, CU_TENSOR_MAP_SWIZZLE_NONE, CU_TENSOR_MAP_DATA_TYPE_UINT32);
  }
  void* gs = nullptr;
  cudaGetSymbolAddress(&gs, g_scratch);
  typedef const __nv_bfloat16* bp;
  int dev = 0, sms = 0;
  cudaGetDevice(&dev);
  cudaDeviceGetAttribute(&sms, cudaDevAttrMultiProcessorCount, dev);
  const bool by_sm = BYSM && sms == NGRID;
  const auto kernel = by_sm ? fused_kernel<true> : fused_kernel<false>;
  cudaFuncSetAttribute(kernel, cudaFuncAttributeMaxDynamicSharedMemorySize, SMEM_BYTES);
  kernel<<<by_sm ? NGRID : NCTA, NTHREADS, SMEM_BYTES, cudaStreamPerThread>>>((bp)d_in[0], (Scratch*)gs, (bp)d_in[5], (bp)d_in[6], (bp)d_in[4], (bp)d_in[8], (bp)d_in[7], (__nv_bfloat16*)d_out, p);
}
```

```cpp
#include <cuda_runtime.h>
#include <cuda.h>
#include <cuda_bf16.h>
#include <stdint.h>
#include <stddef.h>
#include <type_traits>

namespace {

constexpr int S_ = 2048, D_ = 1024, F_ = 3584;
constexpr int NCTA = 128, NGRID = 132, NTHREADS = 512;
#define NOMOD 0
constexpr int MOD_CTAS = NOMOD ? 0 : F_ / 32;

#define PRE 2
#define ST1 600
#define RT_G0 2
#define RT_ROT 1
#define RT_SLEEP 500
#define PF_MOD 7
#define MOD_START 9
#define MM 3
#define PO 2
#define A_SLEEP 128
#define KU 99
#define HS 1
#define HOLD 5
#define OWN1 2
#define KF 5
#define QA 3
#define R0 1
#define OA 3
#define QD 0
#define MOD_SLEEP 0
#define MOD_S0 8
#define Y_SLEEP 200
#define PD 0
#define TRY_A 9
#define NAP_A 0
#define VK 1
#define TR 2
#define Q0 0
#define QS 2
#define QW1 0
#define VK1 2
#define MM1 5
#define KL1 2
#define M0 3
#define HP 1
#define FS 0
#define RH 0
#define SP 1
#define KL 3
#define RS 2
#define RETRY 1
#define KV_SLEEP_A 64
#define KV_SLEEP 50
#define TL 3
#define EF 2
#define DYN 0
#define FN 0
#define PB 1
#define B_SLEEP 32
#define PW 1
#define HR 0
#define PAIRED 1
#define BYSM 1

constexpr uint32_t SLOT = 16384, WQKV_BYTES = 24576;
constexpr int MOD_BUFS = 3, MOD_BUFS0 = MOD_BUFS + 2;
static_assert(MOD_START + MOD_BUFS0 <= 16, "first FFN round is requested during W1");
constexpr uint32_t OFF_RING = 0, OFF_W1 = 4 * SLOT;
constexpr uint64_t OA_SLOTS = 0x0AB210AB21098210ull, OW_SLOTS = 0x4376543765437654ull;
constexpr uint32_t OFF_RES = OFF_RING + 8 * SLOT, RES_H = SLOT;
constexpr uint32_t OFF_PK = 10 * SLOT;
constexpr uint32_t OFF_V = 11 * SLOT;
constexpr uint32_t OFF_ONES = OFF_V + 9216 + 8192;
constexpr uint32_t MOD_STEP = 9216, OFF_MOD = OFF_V + 2 * MOD_STEP;
constexpr uint32_t OFF_XSEL = OFF_MOD + 8192;
constexpr uint32_t OFF_KVB = OFF_MOD + 2 * MOD_STEP + 8192;
constexpr uint32_t KVB_N = 1056;
constexpr uint32_t OFF_G = OFF_KVB + 4 * KVB_N + 1024;
constexpr uint32_t OFF_PART = OFF_G + 512;
constexpr uint32_t OFF_MISC = OFF_PART + 576;
constexpr uint32_t OFF_BAR = OFF_MISC + 32;
constexpr uint32_t SMEM_BYTES = OFF_BAR + 488;
constexpr uint32_t BAR_FULL = OFF_BAR, BAR_Y = BAR_FULL + 64, BAR_X = BAR_Y + 8, BAR_PEER = BAR_X + 8, BAR_GATE = BAR_PEER + 8, BAR_RT = BAR_GATE + 8,
                   BAR_FIX = BAR_RT,
                   BAR_MFULL = BAR_FIX + 64, BAR_LAND = BAR_FULL,
                   BAR_EMPTY = OFF_BAR + 28 * 8, BAR_OEMPTY = BAR_EMPTY + 64, BAR_RTD = BAR_OEMPTY + 40, BAR_DONE = BAR_RTD + 8,
                   BAR_OWN = BAR_DONE + 8, BAR_PA = BAR_OWN + 8, BAR_PUB = BAR_PA + 8, BAR_MEMPTY = BAR_PUB + 16,
                   BAR_IDX = BAR_MEMPTY + 8,
                   BAR_OFULL = OFF_BAR + 52 * 8, BAR_SP = OFF_BAR + 60 * 8;
static_assert(BAR_MFULL + MOD_BUFS0 * 8 <= BAR_EMPTY && BAR_MEMPTY + MOD_BUFS0 * 8 == BAR_OFULL, "barrier groups");
static_assert(SMEM_BYTES <= 232448, "smem");
static_assert(TL == 3 && PRE == 2, "schedule");

constexpr int NB_WG0 = 1, NB_ORDER_12 = 3, NB_ORDER_3O = 4, NB_STG = 5, NB_MODW = 6, NB_KEY = 7, NB_HOLD = 8;

struct Scratch {
  uint4 kv[2][8][3][128];
  float4 y[2][3][128];
  unsigned cnt[32][32];
  unsigned gslot[S_];
  unsigned rslot[8][NCTA];
  unsigned spare[128];
  unsigned block[NCTA];
  uint4 o[16][16][1024];
};
static_assert(offsetof(Scratch, gslot) == NCTA * 56 * 16, "clear size");
__device__ __align__(1024) Scratch g_scratch;

#define PROF(cond, i) do {} while (0)
#define PROF_C(cond, i) do {} while (0)

__device__ __forceinline__ void mbar_init(uint32_t bar, int cnt) { asm volatile("mbarrier.init.shared::cta.b64 [%0], %1;" ::"r"(bar), "r"(cnt)); }
__device__ __forceinline__ void mbar_expect_tx(uint32_t bar, uint32_t bytes) { asm volatile("mbarrier.arrive.expect_tx.shared::cta.b64 _, [%0], %1;" ::"r"(bar), "r"(bytes) : "memory"); }
__device__ __forceinline__ void mbar_arrive(uint32_t bar) { asm volatile("mbarrier.arrive.shared::cta.b64 _, [%0];" ::"r"(bar) : "memory"); }
__device__ __forceinline__ uint32_t peer_addr(uint32_t a) {
  uint32_t r;
  asm volatile("{\n.reg .u32 c;\nmov.u32 c, %%cluster_ctarank;\nxor.b32 c, c, 1;\nmapa.shared::cluster.u32 %0, %1, c;\n}" : "=r"(r) : "r"(a));
  return r;
}
__device__ __forceinline__ void mbar_arrive_peer(uint32_t bar) { asm volatile("mbarrier.arrive.shared::cluster.b64 _, [%0];" ::"r"(bar) : "memory"); }
__device__ __forceinline__ uint32_t mism(uint32_t a, uint32_t b, uint32_t p) {
  uint32_t r; asm("lop3.b32 %0, %1, %2, %3, 0x7E;" : "=r"(r) : "r"(a), "r"(b), "r"(p)); return r;
}
__device__ __forceinline__ bool elect() {
  uint32_t r;
  asm volatile("{\n.reg .pred p;\nelect.sync _|p, 0xffffffff;\nselp.u32 %0, 1, 0, p;\n}" : "=r"(r));
  return r;
}
__device__ __forceinline__ uint32_t fresh_tid() { uint32_t r; asm volatile("mov.u32 %0, %%tid.x;" : "=r"(r)); return r; }
__device__ __forceinline__ void mbar_arrive_warp(uint32_t bar) {
  asm volatile("{\n.reg .pred p;\nelect.sync _|p, 0xffffffff;\n@p mbarrier.arrive.shared::cta.b64 _, [%0];\n}" ::"r"(bar) : "memory");
}
__device__ __forceinline__ void mbar_wait(uint32_t bar, uint32_t parity) {
  asm volatile("{\n.reg .pred p;\nWAIT_L:\nmbarrier.try_wait.parity.shared::cta.b64 p, [%0], %1;\n@p bra DONE_L;\nbra WAIT_L;\nDONE_L:\n}"
               ::"r"(bar), "r"(parity) : "memory");
}
__device__ __forceinline__ uint32_t mbar_try(uint32_t bar, uint32_t parity) {
  uint32_t ok;
  asm volatile("{\n.reg .pred p;\nmbarrier.try_wait.parity.shared::cta.b64 p, [%1], %2;\nselp.u32 %0, 1, 0, p;\n}" : "=r"(ok) : "r"(bar), "r"(parity) : "memory");
  return ok;
}
__device__ __forceinline__ uint32_t mbar_test(uint32_t bar, uint32_t parity) {
  uint32_t ok;
  asm volatile("{\n.reg .pred p;\nmbarrier.test_wait.parity.shared::cta.b64 p, [%1], %2;\nselp.u32 %0, 1, 0, p;\n}" : "=r"(ok) : "r"(bar), "r"(parity) : "memory");
  return ok;
}
constexpr unsigned long long WATCHDOG_NS = 2000000000ull;
__device__ __forceinline__ unsigned long long gtime() { unsigned long long t; asm volatile("mov.u64 %0, %%globaltimer;" : "=l"(t)); return t; }
__device__ __forceinline__ uint32_t clock32() { uint32_t t; asm volatile("mov.u32 %0, %%clock;" : "=r"(t)); return t; }
__device__ __forceinline__ void mbar_wait_bounded(uint32_t bar, uint32_t parity) {
  unsigned long long t0 = 0;
  for (;;) {
    uint32_t ok;
    asm volatile("{\n.reg .pred p;\nmbarrier.try_wait.parity.shared::cta.b64 p, [%1], %2;\nselp.u32 %0, 1, 0, p;\n}" : "=r"(ok) : "r"(bar), "r"(parity) : "memory");
    if (ok) break;
    const unsigned long long t1 = gtime();
    if (t0 == 0) t0 = t1;
    if (t1 - t0 > WATCHDOG_NS) __trap();
  }
}
__device__ __forceinline__ void tma2d(uint32_t dst, const CUtensorMap* m, int c0, int c1, uint32_t bar) {
  asm volatile("cp.async.bulk.tensor.2d.shared::cluster.global.mbarrier::complete_tx::bytes [%0], [%1, {%3, %4}], [%2];"
               ::"r"(dst), "l"(m), "r"(bar), "r"(c0), "r"(c1) : "memory");
}
__device__ __forceinline__ void tma3d(uint32_t dst, const CUtensorMap* m, int c0, int c1, int c2, uint32_t bar) {
  asm volatile("cp.async.bulk.tensor.3d.shared::cluster.global.mbarrier::complete_tx::bytes [%0], [%1, {%3, %4, %5}], [%2];"
               ::"r"(dst), "l"(m), "r"(bar), "r"(c0), "r"(c1), "r"(c2) : "memory");
}
__device__ __forceinline__ void bulk_load(uint32_t dst, const void* src, uint32_t bytes, uint32_t bar) {
  asm volatile("cp.async.bulk.shared::cluster.global.mbarrier::complete_tx::bytes [%0], [%1], %2, [%3];" ::"r"(dst), "l"(src), "r"(bytes), "r"(bar) : "memory");
}
__device__ __forceinline__ void bulk_store(void* dst, uint32_t src, uint32_t bytes) {
  asm volatile("cp.async.bulk.global.shared::cta.bulk_group [%0], [%1], %2;" ::"l"(dst), "r"(src), "r"(bytes) : "memory");
}
__device__ __forceinline__ void st_async4(uint32_t dst, const uint32_t (&v)[4], uint32_t bar) {
  asm volatile("st.async.shared::cluster.mbarrier::complete_tx::bytes.v4.b32 [%0], {%1, %2, %3, %4}, [%5];" ::"r"(dst), "r"(v[0]), "r"(v[1]), "r"(v[2]), "r"(v[3]), "r"(bar) : "memory");
}
__device__ __forceinline__ void bulk_commit() { asm volatile("cp.async.bulk.commit_group;" ::: "memory"); }
__device__ __forceinline__ void bulk_prefetch(const void* p, uint32_t bytes) {
  asm volatile("cp.async.bulk.prefetch.L2.global [%0], %1;" ::"l"(p), "r"(bytes) : "memory");
}
__device__ __forceinline__ void tma2d_store(const CUtensorMap* m, uint32_t src, int c0, int c1) {
  asm volatile("cp.async.bulk.tensor.2d.global.shared::cta.bulk_group [%0, {%2, %3}], [%1];" ::"l"(m), "r"(src), "r"(c0), "r"(c1) : "memory");
}
__device__ __forceinline__ void wg_fence() { asm volatile("wgmma.fence.sync.aligned;" ::: "memory"); }
__device__ __forceinline__ void wg_commit() { asm volatile("wgmma.commit_group.sync.aligned;" ::: "memory"); }
template <int N> __device__ __forceinline__ void wg_wait() { asm volatile("wgmma.wait_group.sync.aligned %0;" ::"n"(N) : "memory"); }
__device__ __forceinline__ void fence_async_smem() { asm volatile("fence.proxy.async.shared::cta;" ::: "memory"); }
__device__ __forceinline__ void fence_async_global() { asm volatile("fence.proxy.async.global;" ::: "memory"); }
__device__ __forceinline__ void fence_release() { asm volatile("fence.release.gpu;" ::: "memory"); }
__device__ __forceinline__ void fence_acquire() { asm volatile("fence.acquire.gpu;" ::: "memory"); }
__device__ __forceinline__ void nb_sync(int id, int n) { asm volatile("bar.sync %0, %1;" ::"r"(id), "r"(n) : "memory"); }
__device__ __forceinline__ void nb_arrive(int id, int n) { asm volatile("bar.arrive %0, %1;" ::"r"(id), "r"(n) : "memory"); }
__device__ __forceinline__ void stsm4(uint32_t addr, uint32_t r0, uint32_t r1, uint32_t r2, uint32_t r3) {
  asm volatile("stmatrix.sync.aligned.m8n8.x4.shared.b16 [%0], {%1, %2, %3, %4};" ::"r"(addr), "r"(r0), "r"(r1), "r"(r2), "r"(r3) : "memory");
}
__device__ __forceinline__ void stsm4t(uint32_t addr, uint32_t r0, uint32_t r1, uint32_t r2, uint32_t r3) {
  asm volatile("stmatrix.sync.aligned.m8n8.x4.trans.shared.b16 [%0], {%1, %2, %3, %4};" ::"r"(addr), "r"(r0), "r"(r1), "r"(r2), "r"(r3) : "memory");
}
__device__ __forceinline__ void st_relaxed4(void* p, const uint32_t (&v)[4]) {
  asm volatile("st.relaxed.gpu.global.v4.u32 [%0], {%1, %2, %3, %4};" ::"l"(p), "r"(v[0]), "r"(v[1]), "r"(v[2]), "r"(v[3]) : "memory");
}
__device__ __forceinline__ void sts128(uint32_t addr, uint32_t a, uint32_t b, uint32_t c, uint32_t d) {
  asm volatile("st.shared.v4.b32 [%0], {%1, %2, %3, %4};" ::"r"(addr), "r"(a), "r"(b), "r"(c), "r"(d) : "memory");
}
__device__ __forceinline__ uint32_t pack2(float lo, float hi) {
  uint32_t r; asm("cvt.rn.bf16x2.f32 %0, %1, %2;" : "=r"(r) : "f"(hi), "f"(lo)); return r;
}
__device__ __forceinline__ float bf_lo(uint32_t v) { return __uint_as_float(v << 16); }
__device__ __forceinline__ float bf_hi(uint32_t v) { return __uint_as_float(v & 0xffff0000u); }
__device__ __forceinline__ float bf_round(float v) { return __bfloat162float(__float2bfloat16_rn(v)); }
__device__ __forceinline__ void ldsm4(uint32_t addr, uint32_t (&r)[4]) {
  asm volatile("ldmatrix.sync.aligned.m8n8.x4.shared.b16 {%0, %1, %2, %3}, [%4];" : "=r"(r[0]), "=r"(r[1]), "=r"(r[2]), "=r"(r[3]) : "r"(addr) : "memory");
}
__device__ __forceinline__ uint4 lds128(uint32_t addr) {
  uint4 v; asm volatile("ld.volatile.shared.v4.u32 {%0, %1, %2, %3}, [%4];" : "=r"(v.x), "=r"(v.y), "=r"(v.z), "=r"(v.w) : "r"(addr) : "memory"); return v;
}
__device__ __forceinline__ uint2 lds64(uint32_t addr) { uint2 v; asm volatile("ld.volatile.shared.v2.u32 {%0, %1}, [%2];" : "=r"(v.x), "=r"(v.y) : "r"(addr) : "memory"); return v; }
__device__ __forceinline__ uint32_t lds32(uint32_t addr) { uint32_t v; asm volatile("ld.volatile.shared.u32 %0, [%1];" : "=r"(v) : "r"(addr) : "memory"); return v; }
__device__ __forceinline__ uint32_t ld_generic(const void* p) { uint32_t v; asm volatile("ld.volatile.u32 %0, [%1];" : "=r"(v) : "l"(p) : "memory"); return v; }
__device__ __forceinline__ void sts32(uint32_t addr, uint32_t v) { asm volatile("st.shared.u32 [%0], %1;" ::"r"(addr), "r"(v) : "memory"); }
__device__ __forceinline__ uint32_t fma_bf2(uint32_t a, uint32_t b, uint32_t c) { uint32_t r; asm("fma.rn.bf16x2 %0, %1, %2, %3;" : "=r"(r) : "r"(a), "r"(b), "r"(c)); return r; }
__device__ __forceinline__ uint32_t mul_bf2(uint32_t a, uint32_t b) { uint32_t r; asm("mul.rn.bf16x2 %0, %1, %2;" : "=r"(r) : "r"(a), "r"(b)); return r; }
__device__ __forceinline__ unsigned ld_relaxed(const unsigned* p) { unsigned v; asm volatile("ld.relaxed.gpu.global.u32 %0, [%1];" : "=r"(v) : "l"(p) : "memory"); return v; }
__device__ __forceinline__ void st_relaxed(unsigned* p, unsigned v) { asm volatile("st.relaxed.gpu.global.u32 [%0], %1;" ::"l"(p), "r"(v) : "memory"); }
__device__ __forceinline__ uint4 ld_relaxed4(const void* p) {
  uint4 v; asm volatile("ld.relaxed.gpu.global.v4.u32 {%0, %1, %2, %3}, [%4];" : "=r"(v.x), "=r"(v.y), "=r"(v.z), "=r"(v.w) : "l"(p) : "memory"); return v;
}
__device__ __forceinline__ float4 ld_relaxed_f4(const void* p) {
  float4 v; asm volatile("ld.relaxed.gpu.global.v4.f32 {%0, %1, %2, %3}, [%4];" : "=f"(v.x), "=f"(v.y), "=f"(v.z), "=f"(v.w) : "l"(p) : "memory"); return v;
}
__device__ __forceinline__ void red_add4(void* p, float a, float b, float c, float d) {
  asm volatile("red.relaxed.gpu.global.add.v4.f32 [%0], {%1, %2, %3, %4};" ::"l"(p), "f"(a), "f"(b), "f"(c), "f"(d) : "memory");
}
__device__ __forceinline__ void red_add_bf(void* p, uint32_t a, uint32_t b, uint32_t c) {
  asm volatile("red.relaxed.gpu.global.add.noftz.v4.bf16x2 [%0], {%1, %2, %3, %4};" ::"l"(p), "r"(a), "r"(b), "r"(c), "r"(0x3F803F80u) : "memory");
}
__device__ __forceinline__ void red_add(unsigned* p, unsigned v) { asm volatile("red.relaxed.gpu.global.add.u32 [%0], %1;" ::"l"(p), "r"(v) : "memory"); }
__device__ __forceinline__ float rcp(float v) { float r; asm("rcp.approx.ftz.f32 %0, %1;" : "=f"(r) : "f"(v)); return r; }
__device__ __forceinline__ float sigmoidf_(float v) { return rcp(1.f + __expf(-v)); }
__device__ __forceinline__ uint32_t phi2(float a, float b, float l2e = 1.4426950408889634f) {
  float ea, eb;
  asm("ex2.approx.ftz.f32 %0, %1;" : "=f"(ea) : "f"(a * l2e));
  asm("ex2.approx.ftz.f32 %0, %1;" : "=f"(eb) : "f"(b * l2e));
  uint32_t t = pack2(a, b), e = pack2(ea, eb), r;
  asm("max.NaN.bf16x2 %0, %0, %1;" : "+r"(t) : "r"(0x35863586u));
  asm("min.bf16x2 %0, %0, %1;" : "+r"(e) : "r"(0x3F803F80u));
  asm("add.rn.bf16x2 %0, %1, %2;" : "=r"(r) : "r"(t), "r"(e));
  return r;
}
__device__ __forceinline__ uint64_t mkdesc(uint32_t addr, uint32_t lbo, uint32_t sbo, uint32_t sw) {
  return (uint64_t)(((addr & 0x3FFFF) >> 4) | ((lbo >> 4) << 16)) | ((uint64_t)((sbo >> 4) | (sw << 30)) << 32);
}

template <int TA, int TB>
__device__ __forceinline__ void mma128(float (&d)[64], uint64_t da, uint64_t db, int sc) {
  asm volatile("{\n.reg .pred p;\nsetp.ne.b32 p, %66, 0;\n"
    "wgmma.mma_async.sync.aligned.m64n128k16.f32.bf16.bf16 "
    "{%0,%1,%2,%3,%4,%5,%6,%7,%8,%9,%10,%11,%12,%13,%14,%15,%16,%17,%18,%19,%20,%21,%22,%23,"
    "%24,%25,%26,%27,%28,%29,%30,%31,%32,%33,%34,%35,%36,%37,%38,%39,%40,%41,%42,%43,%44,%45,%46,%47,"
    "%48,%49,%50,%51,%52,%53,%54,%55,%56,%57,%58,%59,%60,%61,%62,%63}, "
    "%64, %65, p, 1, 1, %67, %68;\n}\n"
    : "+f"(d[0]), "+f"(d[1]), "+f"(d[2]), "+f"(d[3]), "+f"(d[4]), "+f"(d[5]), "+f"(d[6]), "+f"(d[7]),
      "+f"(d[8]), "+f"(d[9]), "+f"(d[10]), "+f"(d[11]), "+f"(d[12]), "+f"(d[13]), "+f"(d[14]), "+f"(d[15]),
      "+f"(d[16]), "+f"(d[17]), "+f"(d[18]), "+f"(d[19]), "+f"(d[20]), "+f"(d[21]), "+f"(d[22]), "+f"(d[23]),
      "+f"(d[24]), "+f"(d[25]), "+f"(d[26]), "+f"(d[27]), "+f"(d[28]), "+f"(d[29]), "+f"(d[30]), "+f"(d[31]),
      "+f"(d[32]), "+f"(d[33]), "+f"(d[34]), "+f"(d[35]), "+f"(d[36]), "+f"(d[37]), "+f"(d[38]), "+f"(d[39]),
      "+f"(d[40]), "+f"(d[41]), "+f"(d[42]), "+f"(d[43]), "+f"(d[44]), "+f"(d[45]), "+f"(d[46]), "+f"(d[47]),
      "+f"(d[48]), "+f"(d[49]), "+f"(d[50]), "+f"(d[51]), "+f"(d[52]), "+f"(d[53]), "+f"(d[54]), "+f"(d[55]),
      "+f"(d[56]), "+f"(d[57]), "+f"(d[58]), "+f"(d[59]), "+f"(d[60]), "+f"(d[61]), "+f"(d[62]), "+f"(d[63])
    : "l"(da), "l"(db), "r"(sc), "n"(TA), "n"(TB));
}

__device__ __forceinline__ void mma_ktv(float (&d)[36], const uint32_t (&a)[4], uint64_t db, int sc) {
  asm volatile("{\n.reg .pred p;\nsetp.ne.b32 p, %41, 0;\n"
    "wgmma.mma_async.sync.aligned.m64n72k16.f32.bf16.bf16 "
    "{%0,%1,%2,%3,%4,%5,%6,%7,%8,%9,%10,%11,%12,%13,%14,%15,%16,%17,%18,%19,%20,%21,%22,%23,"
    "%24,%25,%26,%27,%28,%29,%30,%31,%32,%33,%34,%35}, "
    "{%36,%37,%38,%39}, %40, p, 1, 1, 0;\n}\n"
    : "+f"(d[0]), "+f"(d[1]), "+f"(d[2]), "+f"(d[3]), "+f"(d[4]), "+f"(d[5]), "+f"(d[6]), "+f"(d[7]),
      "+f"(d[8]), "+f"(d[9]), "+f"(d[10]), "+f"(d[11]), "+f"(d[12]), "+f"(d[13]), "+f"(d[14]), "+f"(d[15]),
      "+f"(d[16]), "+f"(d[17]), "+f"(d[18]), "+f"(d[19]), "+f"(d[20]), "+f"(d[21]), "+f"(d[22]), "+f"(d[23]),
      "+f"(d[24]), "+f"(d[25]), "+f"(d[26]), "+f"(d[27]), "+f"(d[28]), "+f"(d[29]), "+f"(d[30]), "+f"(d[31]),
      "+f"(d[32]), "+f"(d[33]), "+f"(d[34]), "+f"(d[35])
    : "r"(a[0]), "r"(a[1]), "r"(a[2]), "r"(a[3]), "l"(db), "r"(sc));
}

__device__ __forceinline__ void mma_qkvz(float (&d)[20], uint64_t da, uint64_t db, int sc) {
  asm volatile("{\n.reg .pred p;\nsetp.ne.b32 p, %22, 0;\n"
    "wgmma.mma_async.sync.aligned.m64n40k16.f32.bf16.bf16 "
    "{%0,%1,%2,%3,%4,%5,%6,%7,%8,%9,%10,%11,%12,%13,%14,%15,%16,%17,%18,%19}, "
    "%20, %21, p, 1, 1, 0, 1;\n}\n"
    : "+f"(d[0]), "+f"(d[1]), "+f"(d[2]), "+f"(d[3]), "+f"(d[4]), "+f"(d[5]), "+f"(d[6]), "+f"(d[7]),
      "+f"(d[8]), "+f"(d[9]), "+f"(d[10]), "+f"(d[11]), "+f"(d[12]), "+f"(d[13]), "+f"(d[14]), "+f"(d[15]),
      "+f"(d[16]), "+f"(d[17]), "+f"(d[18]), "+f"(d[19])
    : "l"(da), "l"(db), "r"(sc));
}

template <int N> __device__ __forceinline__ void pin(float (&d)[N]) {
#pragma unroll
  for (int i = 0; i < N; i++) asm volatile("" : "+f"(d[i])::"memory");
}

struct Params {
  CUtensorMap x, w, w1, xr, gate, up, wo, out, down;
};

__device__ __forceinline__ uint32_t dup_lo(uint32_t v) { uint32_t r; asm("{\n.reg .b16 l, h;\nmov.b32 {l, h}, %1;\nmov.b32 %0, {l, l};\n}" : "=r"(r) : "r"(v)); return r; }
__device__ __forceinline__ uint32_t dup_hi(uint32_t v) { uint32_t r; asm("{\n.reg .b16 l, h;\nmov.b32 {l, h}, %1;\nmov.b32 %0, {h, h};\n}" : "=r"(r) : "r"(v)); return r; }
__device__ __forceinline__ float butterfly8(float (&s)[8], int lane, int o) {
#pragma unroll
  for (int k = 1; k < 8; k <<= 1) {
    const bool up = lane & (o * k);
#pragma unroll
    for (int j = 0; j < 4 / k; j++) s[j] = (up ? s[2 * j + 1] : s[2 * j]) + __shfl_xor_sync(~0u, up ? s[2 * j] : s[2 * j + 1], o * k);
  }
  return s[0];
}
constexpr int OWN = 8, PEER = 9;
static_assert((OA_SLOTS >> OWN * 4 & 15) * SLOT == OFF_V && (OA_SLOTS >> PEER * 4 & 15) * SLOT == OFF_PK, "");
template <int B> __device__ __forceinline__ void verify_tiles(uint32_t sb, Scratch* gs, int tm, int tn, int w, int lane) {
  const uint32_t par = lds32(sb + OFF_MISC + 24), fix = sb + BAR_FIX + (B * 4 + w) * 8;
  uint32_t slots = (uint32_t)(OA_SLOTS >> B * 40);
#pragma unroll 1
  for (int i = 0; i < 8 - 2 * B; i++, slots >>= 4) {
    const uint32_t a = sb + OFF_RING + (slots & 15) * SLOT + w * 1024, cw = a + lane * 32 + (lane >> 2) * 4;
    if (!B && i == 4) mbar_wait(sb + BAR_EMPTY + 7 * 8, 1);
    mbar_wait(sb + BAR_LAND + i * 8, B);
    for (;;) {
      const uint32_t u0 = lds32(cw), u1 = lds32(cw + 4096), u2 = lds32(cw + 8192), u3 = lds32(cw + 12288);
      if (__all_sync(~0u, !(mism(mism(u0, u1, par), mism(u2, u3, par), 0) & 1))) break;
      const uint4* src = gs->o[tm][!B ? i : DYN ? lds32(sb + OFF_MISC + (i & 4)) >> (i & 3) * 8 & 15 : i < (tn & 6) ? i + 8 : i + 10] + w * 64;
      const uint32_t ph = !mbar_test(fix, 1);
      fence_async_smem();
      __syncwarp();
      if (elect()) {
        mbar_expect_tx(fix, 4096);
#pragma unroll 1
        for (int j = 0; j < 4; j++) bulk_load(a + j * 4096, src + j * 256, 1024, fix);
      }
      mbar_wait(fix, ph);
    }
    mbar_arrive_warp(sb + BAR_OFULL + (i < 5 ? i : i - 5) * 8);
  }
}
template <bool BY_SM> struct Tile {
  int sm, tm, tn, mu;
  bool spare;
  __device__ __forceinline__ Tile() {
    if (BY_SM) asm volatile("mov.u32 %0, %%smid;" : "=r"(sm));
    else sm = blockIdx.x + (blockIdx.x >= 120) * 4;
    const int tp = sm >> 1, pr = sm & 1;
    const int v = tp < 32 ? tp : tp < 60 ? (tp * 293 - 928) >> 8 : tp * 8 - 464, g = v & 7, i = v >> 3;
    tm = (v & 6) * 2 + (i & 3); tn = (v & 1) * 4 + (v >> 4 & 2) + pr;
    mu = i == 5 ? 112 : g * 14 + (i - (i > 5)) * 2 + pr;
    spare = (tp | 1) == 61;
  }
};

template <bool BY_SM> __global__ void __cluster_dims__(2, 1, 1) __launch_bounds__(NTHREADS, 1) fused_kernel(const __nv_bfloat16* __restrict__ px, Scratch* gs, const __nv_bfloat16* __restrict__ w_gate,
             const __nv_bfloat16* __restrict__ w_up, const __nv_bfloat16* __restrict__ w_r, const __nv_bfloat16* __restrict__ gate_w, const __nv_bfloat16* __restrict__ w_down, __nv_bfloat16* __restrict__ pout,
             const __grid_constant__ Params p) {
  extern __shared__ __align__(1024) uint8_t smem[];
  const uint32_t sb = __shfl_sync(~0u, (uint32_t)__cvta_generic_to_shared(smem), 0);
  const int tid = threadIdx.x, lane = tid & 31;
  const int warp = __shfl_sync(~0u, tid >> 5, 0), wg = warp >> 2;
  const uint32_t t_start = clock32();
  const Tile<BY_SM> tile;
  const int tm = tile.tm, tn = tile.tn, mu = tile.mu, cta = tm * 8 + tn;
  const uint32_t zero = tile.sm >> 12;
  if (warp == 0) {
#pragma unroll
    for (int s = 0; s < PRE; s++)
      if (elect()) mbar_init(sb + BAR_FULL + s * 8, 1);
    if (SP && elect()) mbar_init(sb + BAR_SP, 1);
    asm volatile("fence.mbarrier_init.release.cluster;" ::: "memory");
    if (!tile.spare) {
      if (SP) {
        if (elect()) tma3d(sb + OFF_W1 + 8192, &p.w1, tn * 64, 0, 1, sb + BAR_FULL);
        if (elect()) tma2d(sb + OFF_RING, &p.x, 0, tm * 128, sb + BAR_FULL);
        if (elect()) tma3d(sb + OFF_W1 + 16384, &p.w1, tn * 64, 0, 2, sb + BAR_SP);
        if (elect()) tma3d(sb + OFF_W1, &p.w1, tn * 64, 0, 0, sb + BAR_SP);
        PROF(lane == 0, 64);
      }
#pragma unroll
      for (int s = SP; s < PRE; s++) {
        if (elect()) tma3d(sb + OFF_W1 + s * WQKV_BYTES, &p.w, tn * 64, s * 64, 0, sb + BAR_FULL + s * 8);
        if (elect()) tma2d(sb + OFF_RING + s * SLOT, &p.x, s * 64, tm * 128, sb + BAR_FULL + s * 8);
        PROF(lane == 0, 64 + s);
      }
      if (elect()) {
#pragma unroll
        for (int s = 0; s < PRE; s++) mbar_expect_tx(sb + BAR_FULL + s * 8, s || !SP ? SLOT + WQKV_BYTES : SLOT + 8192);
        if (SP) mbar_expect_tx(sb + BAR_SP, 16384);
      }
    }
  }
  if (warp) {
    const int wi = warp == 15 ? 0 : warp;
    const int cnt = wi < 7 ? 1 : wi < 13 ? 4 : 5;
#pragma unroll
    for (int i = 0; i < 4; i++)
      if ((i >= PRE || wi) && elect()) mbar_init(sb + OFF_BAR + wi * 32 + i * 8, cnt);
    asm volatile("fence.mbarrier_init.release.cluster;" ::: "memory");
  }
  __syncthreads();
  if (tile.spare) {
    if (warp == 0) {
      const unsigned tag = (ld_relaxed(&gs->spare[tile.sm & 3]) + 1) & 0xFFF;
      const unsigned long long t0 = gtime();
      uint4 r4;
      do {
        __nanosleep(2048);
        if (gtime() - t0 > WATCHDOG_NS) __trap();
        r4 = ld_relaxed4(&gs->rslot[tile.sm & 3][lane * 4]);
      } while (!__all_sync(~0u, (((r4.x ^ tag) | (r4.y ^ tag) | (r4.z ^ tag) | (r4.w ^ tag)) & 0xFFF) == 0));
      if (tid == 0) st_relaxed(&gs->spare[tile.sm & 3], tag);
    }
    return;
  }

  if (wg == 3) {
    asm volatile("setmaxnreg.dec.sync.aligned.u32 24;");
    if (warp == 12) {
      mbar_wait(sb + BAR_PUB, 0);
      while (!__all_sync(~0u, ld_relaxed(gs->cnt[tm]) == 0x44444444u)) __nanosleep(A_SLEEP);
      if (FN) { fence_acquire(); fence_async_global(); }
      PROF(lane == 0, 7);
      mbar_wait(sb + BAR_GATE, 0);
      uint32_t slots = (uint32_t)OA_SLOTS, deps = 0xA9877654u;
#pragma unroll 1
      for (int i = 0; i < 8; i++, deps >>= 4, slots >>= 4) {
        mbar_wait(sb + BAR_EMPTY + (deps & 15) * 8, i < 5);
        if (elect()) bulk_load(sb + OFF_RING + (slots & 15) * SLOT, gs->o[tm][i], SLOT, sb + BAR_LAND + i * 8);
        if (elect()) mbar_expect_tx(sb + BAR_LAND + i * 8, SLOT);
        PROF(lane == 0, 44 + i);
      }
      slots = (uint32_t)(OA_SLOTS >> 40);
      uint32_t ws = (uint32_t)(OW_SLOTS >> 40), todo = 0x44444444u ^ 0x44u << (tn & 6) * 4, seen = 0, st = 0;
      mbar_wait(sb + BAR_PUB + 8, 0);
#pragma unroll 1
      for (int i = 0; i < 6; i++, slots >>= 4, ws >>= 4) {
        const uint32_t need = DYN ? todo : todo & -todo;
        if (!(seen & need)) {
          while (!((seen = __shfl_sync(~0u, ld_relaxed(gs->cnt[16 + tm]), 0)) & need)) __nanosleep(B_SLEEP);
          if (FN) { fence_acquire(); fence_async_global(); }
        }
        const uint32_t bit = seen & need & -(seen & need), slab = 8 + ((31 - __clz(bit)) >> 2);
        todo ^= bit;
        if (DYN && elect()) asm volatile("st.shared.u8 [%0], %1;" ::"r"(sb + OFF_MISC + i), "r"(slab) : "memory");
        mbar_wait(sb + BAR_OEMPTY + st * 8, i < 5);
        if (elect()) bulk_load(sb + OFF_RING + (slots & 15) * SLOT, gs->o[tm][slab], SLOT, sb + BAR_LAND + i * 8);
        if (DYN && elect()) tma3d(sb + OFF_RING + (ws & 15) * SLOT, &p.wo, 0, slab * 64, tn * 2, sb + BAR_OFULL + st * 8);
        if (elect()) mbar_expect_tx(sb + BAR_LAND + i * 8, SLOT);
        if (DYN && elect()) mbar_expect_tx(sb + BAR_OFULL + st * 8, SLOT);
        PROF(lane == 0, 54 + i);
        st = st == 4 ? 0 : st + 1;
      }
    } else if (warp == 13) {
#pragma unroll 1
      for (int g = PRE; g < 32; g++) {
        const bool reuse = (g >> 2) == 4;
        const uint32_t s = g & 3, full = sb + BAR_FULL + (g & 7) * 8, c0 = tn * 64 + (g & 16) * 32, c1 = (g < 16 ? g : g - 4 & 15) * 64;
        if (g < 4) while ((int)(clock32() - t_start) < g * ST1) {}
        mbar_wait(sb + BAR_EMPTY + (g + 4 & 7) * 8, (g + 4 >> 3 & 1) ^ 1);
        if (!reuse && elect()) tma2d(sb + OFF_RING + s * SLOT, &p.x, c1, tm * 128, full);
        if (elect()) tma3d(sb + OFF_W1 + s * WQKV_BYTES, &p.w, c0, c1, 0, full);
        if (elect()) mbar_expect_tx(full, reuse ? WQKV_BYTES : SLOT + WQKV_BYTES);
        PROF(lane == 0, 64 + g);
        const uint32_t i = g - RT_G0;
        if (i < 4 && elect()) {
          mbar_expect_tx(sb + BAR_RT + i * 8, i ? 8192 : 8192 + 4096);
          tma2d(sb + OFF_PK + i * 8192 + (i == 3) * 1024, &p.xr, ((i + RT_ROT) & 3) * 256, cta * 16, sb + BAR_RT + i * 8);
          if (i == 0) { bulk_load(sb + OFF_KVB, w_r, 2048, sb + BAR_RT); bulk_load(sb + OFF_KVB + 2048, gate_w, 2048, sb + BAR_RT); }
        }
        const uint32_t c = g - MOD_START;
        if (c == MOD_BUFS) mbar_wait(sb + BAR_RTD, 0);
        if (c < MOD_BUFS0 && mu < MOD_CTAS && elect()) {
          PROF(true, 192 + c);
          const uint32_t mb = c < MOD_BUFS ? c + 2 : c - MOD_BUFS, mfull = sb + BAR_MFULL + mb * 8, mdst = sb + OFF_V + mb * MOD_STEP;
          mbar_expect_tx(mfull, c ? 8192 : 8192 + 2048);
          tma3d(mdst, &p.gate, mu * 32, c * 16, 0, mfull); tma3d(mdst + 4096, &p.up, mu * 32, c * 16, 0, mfull);
        }
        const uint32_t pc = g - PF_MOD;
        if (pc < 16 && elect()) bulk_prefetch((cta & 64 ? w_up : w_gate) + (size_t)(pc * 64 + (cta & 63)) * F_, F_ * 2);
      }
      mbar_arrive_warp(sb + BAR_GATE);
      const uint32_t lowb = (1u << (tn & 6) * 4) - 1;
      uint64_t slabs = (uint64_t)((0xFEDCBA98u & lowb) | (0xFEDCBAu & ~lowb)) << 40 | (uint64_t)(8 + (tn ^ 1)) << 36 | (uint64_t)(8 + tn) << 32 | 0x76543210u;
      uint64_t deps = 0x8CBA98CBA9876554ull, ws = OW_SLOTS;
      uint32_t full = sb + BAR_OFULL, ph = 1;
#pragma unroll 1
      for (int g = 0; g < (DYN ? 10 : 16); g++, slabs >>= 4, deps >>= 4, ws >>= 4) {
        mbar_wait(sb + BAR_EMPTY + ((uint32_t)deps & 15) * 8, ph);
        if (elect()) tma3d(sb + OFF_RING + ((uint32_t)ws & 15) * SLOT, &p.wo, 0, ((uint32_t)slabs & 15) * 64, tn * 2, full);
        if (elect()) mbar_expect_tx(full, SLOT);
        PROF(lane == 0, 96 + g);
        if (g >> 1 == OWN / 2 && lane < 4) mbar_arrive(full);
        if (DYN && g == PW && tm < 8 && elect())
          asm volatile("cp.async.bulk.prefetch.tensor.3d.L2.global [%0, {%1, %2, %3}];" ::"l"(&p.wo), "r"(0), "r"((8 + tm) * 64), "r"(tn * 2) : "memory");
        full += 8;
        if (full == sb + BAR_OFULL + 40) { full -= 40; ph ^= 1; }
      }
    } else if (warp == 14) {
      if (mu < MOD_CTAS) {
        uint32_t full = sb + BAR_MFULL + 16, dst = sb + OFF_MOD, ph = 0;
#pragma unroll 1
        for (int c = MOD_BUFS0; c < 24; c++) {
          mbar_wait(full + (BAR_MEMPTY - BAR_MFULL), ph);
          PROF(lane == 0, 192 + c);
          if (c < 16) {
            if (elect()) { tma3d(dst, &p.gate, mu * 32, c * 16, 0, full); tma3d(dst + 4096, &p.up, mu * 32, c * 16, 0, full); }
          } else if (elect()) tma3d(dst, &p.down, 0, mu * 32 + (c - 16) * 4, 0, full);
          if (elect()) mbar_expect_tx(full, 8192);
          if (PD && (uint32_t)(c + PD - 16) < 8 && elect()) bulk_prefetch(w_down + (size_t)(mu * 32 + (c + PD - 16) * 4) * D_, 8192);
          full += 8; dst += MOD_STEP;
          if (full == sb + BAR_MFULL + MOD_BUFS0 * 8) { full -= MOD_BUFS * 8; dst = sb + OFF_MOD; ph ^= 1; }
        }
      }
      if (elect()) {
      mbar_wait(sb + BAR_IDX, 0);
      const bool paired = PAIRED && ld_relaxed(&gs->block[cta ^ 1]) == (blockIdx.x ^ 1);
      if (paired) mbar_expect_tx(sb + BAR_PEER, SLOT);
      mbar_expect_tx(sb + BAR_X, 32768);
      mbar_wait(sb + BAR_OEMPTY + 3 * 8, 0);
      tma2d(sb + OFF_RES, &p.x, tn * 128, tm * 128, sb + BAR_X);
      mbar_wait(sb + BAR_OEMPTY + 4 * 8, 0);
      tma2d(sb + OFF_RES + RES_H, &p.x, tn * 128 + 64, tm * 128, sb + BAR_X);
      if (!paired) {
        mbar_wait(sb + BAR_OWN, 0);
        while (!(ld_relaxed(gs->cnt[16 + tm]) & 4u << (tn ^ 1) * 4)) __nanosleep(32);
        fence_acquire();
        fence_async_global();
        const uint32_t par = lds32(sb + OFF_MISC + 24);
        for (uint32_t ph = !mbar_test(sb + BAR_MFULL, 1), bad = 1; bad & 1; ph ^= 1) {
          fence_async_smem();
          mbar_expect_tx(sb + BAR_MFULL, SLOT);
          bulk_load(sb + OFF_PK, gs->o[tm][8 + (tn ^ 1)], SLOT, sb + BAR_MFULL);
          mbar_wait(sb + BAR_MFULL, ph);
          bad = 0;
#pragma unroll 1
          for (int i = 0; i < 512; i++) bad |= lds32(sb + OFF_PK + i * 32 + (i & 28)) ^ par;
        }
        mbar_arrive(sb + BAR_PEER);
      }
      }
    } else {
#pragma unroll 1
      for (int i = 3; i < 9; i++)
        if (elect()) asm volatile("prefetch.tensormap [%0];" ::"l"(&p.x + i) : "memory");
      mbar_wait_bounded(sb + BAR_DONE, 0);
    }
  } else if (wg == 2) {
    asm volatile("setmaxnreg.dec.sync.aligned.u32 40;");
    const int mw = warp & 3;
    if (mw == 0) {
      const unsigned tag = (ld_relaxed(&gs->rslot[tn][cta]) + 1) & 0xFFF;
#pragma unroll
      for (int i = 0; i < 2; i++)
        if (lane < 28) ((float4*)gs)[cta * 56 + i * 28 + lane] = make_float4(0.f, 0.f, 0.f, 0.f);
      if (lane == 29) gs->block[cta] = blockIdx.x;
      fence_release();
      nb_sync(NB_KEY, 160);
      const uint4 k4 = lds128(sb + OFF_MISC);
      if (lane < 8) st_relaxed(&gs->rslot[lane][cta], max(max(k4.x, k4.y), max(k4.z, k4.w)) | tag);
      if (lane < 16) st_relaxed(&gs->gslot[cta * 16 + lane], lds32(sb + OFF_G + lane * 4) | tag);
      PROF(lane == 0, 20);
      uint4 r4;
      do {
        __nanosleep(RT_SLEEP);
        r4 = ld_relaxed4(&gs->rslot[tn][lane * 4]);
      } while (!__all_sync(~0u, (((r4.x ^ tag) | (r4.y ^ tag) | (r4.z ^ tag) | (r4.w ^ tag)) & 0xFFF) == 0));
      const int c0 = 0xFFF0 - lane * 64;
      unsigned key = max(max((r4.x & 0xFFFF0000u) | (c0 + ((r4.x >> 12) & 15)), (r4.y & 0xFFFF0000u) | (c0 - 16 + ((r4.y >> 12) & 15))),
                         max((r4.z & 0xFFFF0000u) | (c0 - 32 + ((r4.z >> 12) & 15)), (r4.w & 0xFFFF0000u) | (c0 - 48 + ((r4.w >> 12) & 15))));
      key = __reduce_max_sync(~0u, key);
      if (elect()) {
        sts32(sb + OFF_MISC + 16, key);
        sts32(sb + OFF_MISC + 24, tag & 1);
        if (mu < MOD_CTAS) {
          const __nv_bfloat16* row = px + (size_t)(0xFFFF - (key & 0xFFFF)) * D_;
          bulk_load(sb + OFF_XSEL, row, 1024, sb + BAR_MFULL + 16);
          bulk_load(sb + OFF_XSEL + MOD_STEP, row + 512, 1024, sb + BAR_MFULL + 16);
        }
      }
      PROF(lane == 0, 21);
      do {
        r4 = ld_relaxed4(&gs->gslot[tm * 128 + lane * 4]);
      } while (!__all_sync(~0u, (((r4.x ^ tag) | (r4.y ^ tag) | (r4.z ^ tag) | (r4.w ^ tag)) & 0xFFF) == 0));
      sts128(sb + OFF_G + lane * 16, r4.x & 0xFFFF0000u, r4.y & 0xFFFF0000u, r4.z & 0xFFFF0000u, r4.w & 0xFFFF0000u);
      fence_acquire();
      __syncwarp();
    }
    PROF(tid == 256, 22);
    if (mu >= MOD_CTAS) {
      mbar_arrive_warp(sb + BAR_IDX);
    } else {
      const uint32_t wp = sb + OFF_V + (mw >> 1) * 4096 + (mw & 1) * 512 + lane * 16;
      uint32_t mp = sb + OFF_XSEL + (mw & 1) * 64 + (lane >> 2) * 8, mc = 128;
      float acc[8] = {0.f, 0.f, 0.f, 0.f, 0.f, 0.f, 0.f, 0.f};
      uint32_t b = 2, ph = 0;
#pragma unroll 1
      for (int c = 0; c < 24; c++) {
        if (MOD_SLEEP && c >= MOD_S0) __nanosleep(MOD_SLEEP);
        mbar_wait(sb + BAR_MFULL + b * 8, ph);
        PROF_C(tid == 256, 216 + c);
        const uint32_t a = wp + b * MOD_STEP;
        const uint2 m = lds64(mp);
        const uint4 w0 = lds128(a), w1 = lds128(a + 1024), w2 = lds128(a + 2048), w3 = lds128(a + 3072);
        mp += c == 7 ? MOD_STEP - 1024 + 128 : mc;
        const uint32_t m0 = dup_lo(m.x), m1 = dup_hi(m.x), m2 = dup_lo(m.y), m3 = dup_hi(m.y);
        uint4 q = make_uint4(mul_bf2(w0.x, m0), mul_bf2(w0.y, m0), mul_bf2(w0.z, m0), mul_bf2(w0.w, m0));
        q = make_uint4(fma_bf2(w1.x, m1, q.x), fma_bf2(w1.y, m1, q.y), fma_bf2(w1.z, m1, q.z), fma_bf2(w1.w, m1, q.w));
        q = make_uint4(fma_bf2(w2.x, m2, q.x), fma_bf2(w2.y, m2, q.y), fma_bf2(w2.z, m2, q.z), fma_bf2(w2.w, m2, q.w));
        mbar_arrive_warp(sb + BAR_MEMPTY + b * 8 + (w3.x & zero));
        q = make_uint4(fma_bf2(w3.x, m3, q.x), fma_bf2(w3.y, m3, q.y), fma_bf2(w3.z, m3, q.z), fma_bf2(w3.w, m3, q.w));
        if (++b == 5) b = c < 3 ? 0 : 2;
        if (b == 2) ph ^= 1;
        acc[0] += bf_lo(q.x); acc[1] += bf_hi(q.x); acc[2] += bf_lo(q.y); acc[3] += bf_hi(q.y);
        acc[4] += bf_lo(q.z); acc[5] += bf_hi(q.z); acc[6] += bf_lo(q.w); acc[7] += bf_hi(q.w);
        if (c == 15) {
          const uint32_t ft = fresh_tid(), fl = ft & 31;
          sts32(sb + OFF_PART + (ft & 96) * 4 + ((ft & 3) * 8 + (fl >> 2)) * 4, __float_as_uint(butterfly8(acc, fl, 4)));
          nb_sync(NB_MODW, 128);
          const float* part = (const float*)(smem + OFF_PART) + fl;
          const float gp = bf_round(part[0] + part[32]), up = bf_round(part[64] + part[96]);
          *(__nv_bfloat16*)(smem + OFF_PART + 512 + fl * 2) = __float2bfloat16_rn(bf_round(gp * sigmoidf_(gp)) * up);
          __syncwarp();
          mp = sb + OFF_PART + 512; mc = 8;
#pragma unroll
          for (int i = 0; i < 8; i++) acc[i] = 0.f;
          PROF(lane == 0 && mw == 0, 23);
        }
      }
      float4* yacc = gs->y[tn & 1][0] + (fresh_tid() & 127);
      red_add4(yacc, acc[0], acc[1], acc[2], 1.f);
      red_add4(yacc + 128, acc[3], acc[4], acc[5], 1.f);
      red_add4(yacc + 256, acc[6], acc[7], 0.f, 1.f);
      PROF(lane == 0 && mw == 0, 25);
    }
    mbar_wait(sb + BAR_GATE, 0);
    mbar_wait(sb + BAR_IDX, 0);
    verify_tiles<0>(sb, gs, tm, tn, mw, lane);
    const unsigned key = lds32(sb + OFF_MISC + 16);
    const int sel = 0xFFFF - (int)(key & 0xFFFF) - tm * 128;
    if (mw == 0 && sel >= 0 && sel < 128) {
      const unsigned k16 = key >> 16;
      const float rs = bf_round(sigmoidf_(__uint_as_float(((k16 & 0x8000u) ? (k16 & 0x7FFFu) : (~k16 & 0xFFFFu)) << 16)));
      float v[12];
      const float4* yp = gs->y[lane >> 4][0] + tn * 16 + (lane & 15);
      for (;;) {
#pragma unroll
        for (int i = 0; i < 3; i++) {
          const float4 u = ld_relaxed_f4(yp + i * 128);
          v[4 * i] = u.x; v[4 * i + 1] = u.y; v[4 * i + 2] = u.z; v[4 * i + 3] = u.w;
        }
        const float n = v[3] + v[7] + v[11];
        if (__all_sync(~0u, n + __shfl_xor_sync(~0u, n, 16) == 3.f * MOD_CTAS)) break;
        __nanosleep(Y_SLEEP);
      }
#pragma unroll
      for (int i = 0; i < 10; i++) v[i] = bf_round(bf_round(v[i] + __shfl_xor_sync(~0u, v[i], 16)) * rs);
      PROF(lane == 0, 24);
      mbar_wait(sb + BAR_X, 0);
      if (lane < 16) {
        uint4* xp = (uint4*)(smem + OFF_RES + (lane >> 3) * RES_H + sel * 128 + (((lane ^ sel) & 7) << 4));
        const uint4 xv = *xp;
        *xp = make_uint4(pack2(bf_lo(xv.x) + v[0], bf_hi(xv.x) + v[1]), pack2(bf_lo(xv.y) + v[2], bf_hi(xv.y) + v[4]),
                         pack2(bf_lo(xv.z) + v[5], bf_hi(xv.z) + v[6]), pack2(bf_lo(xv.w) + v[8], bf_hi(xv.w) + v[9]));
      }
      __syncwarp();
      mbar_arrive_warp(sb + BAR_Y);
    }
  } else {
    asm volatile("setmaxnreg.inc.sync.aligned.u32 224;");
    const int w = warp & 3, wt = tid & 127;
    const int nb_self = NB_WG0 + wg;
    const uint64_t da0 = mkdesc(sb + OFF_RING, 16, 1024, 1), db0 = mkdesc(sb + OFF_RING, 8192, 1024, 1);

    if (wg == 1) {
      sts128(sb + OFF_ONES - (w >> 1) * 9216 + (w & 1) * 512 + lane * 16, 0x3F803F80u, 0x3F803F80u, 0x3F803F80u, 0x3F803F80u);
      sts32(sb + OFF_MISC + 20, 0x3FB8AA3Bu);
      fence_async_smem();
      float s[8] = {0.f, 0.f, 0.f, 0.f, 0.f, 0.f, 0.f, 0.f};
      uint32_t mask = 0xffff0000u;
#pragma unroll 1
      for (int i = 0; i < 4; i++) {
        const uint32_t u = (i + RT_ROT) & 3;
        mbar_wait(sb + BAR_RT + i * 8, 0);
        const uint4 wr = lds128(sb + OFF_KVB + u * 512 + lane * 16), gw = lds128(sb + OFF_KVB + 2048 + u * 512 + lane * 16);
        uint4 xv[4];
#pragma unroll
        for (int r = 0; r < 4; r++) xv[r] = lds128(sb + OFF_PK + i * 8192 + (i == 3) * 1024 + (w * 4 + r) * 512 + lane * 16);
        const float wf[16] = {bf_lo(wr.x), bf_hi(wr.x), bf_lo(wr.y), bf_hi(wr.y), bf_lo(wr.z), bf_hi(wr.z), bf_lo(wr.w), bf_hi(wr.w),
                              bf_lo(gw.x), bf_hi(gw.x), bf_lo(gw.y), bf_hi(gw.y), bf_lo(gw.z), bf_hi(gw.z), bf_lo(gw.w), bf_hi(gw.w)};
#pragma unroll
        for (int r = 0; r < 4; r++) {
          const uint4 xq = xv[r];
          const float xf[8] = {bf_lo(xq.x), __uint_as_float(xq.x & mask), bf_lo(xq.y), bf_hi(xq.y), bf_lo(xq.z), bf_hi(xq.z), bf_lo(xq.w), bf_hi(xq.w)};
#pragma unroll
          for (int j = 0; j < 8; j++) { s[2 * r] = fmaf(xf[j ^ 1], wf[j ^ 1], s[2 * r]); s[2 * r + 1] = fmaf(xf[j ^ 1], wf[8 + (j ^ 1)], s[2 * r + 1]); }
          mask = ((__float_as_uint(s[2 * r]) | __float_as_uint(s[2 * r + 1])) & zero) | 0xffff0000u;
        }
      }
      mbar_arrive_warp(sb + BAR_RTD + (__float_as_uint(s[6]) & zero));
      float v = butterfly8(s, lane, 1);
      PROF_C(wt == 0 && v != 12345.f, 19);
      v += __shfl_xor_sync(~0u, v, 8);
      v = bf_round(v + __shfl_xor_sync(~0u, v, 16));
      const unsigned rb = __float_as_uint(v) >> 16, row = w * 4 + ((lane & 7) >> 1);
      unsigned key = (lane & 1) ? 0u : ((((rb & 0x8000u) ? (~rb & 0xFFFFu) : (rb | 0x8000u)) << 16) | ((15 - row) << 12));
      key = __reduce_max_sync(~0u, key);
      if (lane == 0) sts32(sb + OFF_MISC + w * 4, key);
      if (lane < 8 && (lane & 1)) sts32(sb + OFF_G + row * 4, __float_as_uint(bf_round(sigmoidf_(v))));
      nb_arrive(NB_KEY, 160);
      nb_sync(NB_ORDER_12, 256);
    }
    uint4* const kvacc = &gs->kv[wg][tn][0][wt];
    float aq[64];
    uint32_t su[9];
    float pq[64], ak[64], av[64];
    auto proj = [&](float (&d)[64], int j, uint32_t s, int sc) {
#pragma unroll
      for (int kk = 0; kk < 4; kk++)
        mma128<1, 0>(d, da0 + ((OFF_W1 >> 4) + s * (WQKV_BYTES >> 4) + j * 512 + kk * 128), da0 + (s * (SLOT >> 4) + kk * 2), kk ? 1 : sc);
    };
    PROF_C(wt == 0, 1 + wg * 8);
#pragma unroll 1
    for (int g = 0; g < 15; g++) {
      mbar_wait(sb + BAR_FULL + (g & 7) * 8, g >> 3);
      if (g == 0) PROF_C(wt == 0, 2 + wg * 8);
      wg_fence();
      proj(ak, 1, g & 3, g);
      wg_commit();
      wg_wait<1>();
      if (g) mbar_arrive_warp(sb + BAR_EMPTY + (g - 1 & 7) * 8);
      if (g == 14) break;
      if (SP && g == 0) mbar_wait(sb + BAR_SP, 0);
      wg_fence();
      proj(av, 2, g & 3, g);
      proj(pq, 0, g & 3, g);
      wg_commit();
    }
    auto finish = [&](auto reorder) {
      constexpr int re = decltype(reorder)::value, vk = re ? VK1 : VK, mm = re ? MM1 : MM, kl = re ? KL1 : KL, qw = re ? QW1 : 0;
      float c[36];
      uint32_t pk[8][4];
      if (!re) {
        wg_fence();
        proj(av, 2, 2, 1);
        proj(pq, 0, 2, 1);
        wg_commit();
      }
      mbar_wait(sb + BAR_FULL + 7 * 8, 1);
      wg_fence();
      proj(ak, 1, 3, 1);
      wg_commit();
      if (!re) {
        wg_wait<1>();
        mbar_arrive_warp(sb + BAR_EMPTY + 6 * 8);
      }
      wg_fence();
      if (re) proj(av, 2, 2, 1);
      proj(av, 2, 3, 1);
      wg_commit();
      if (!re) {
        proj(pq, 0, 3, 1);
        wg_commit();
        if (wg == 0) nb_arrive(NB_ORDER_12, 256);
      }
      mbar_wait(sb + BAR_IDX, 0);
      if (wg == 1) nb_sync(NB_STG, 256);
      wg_wait<2 - re>();
      pin(ak);
      PROF_C(wt == 0, 3 + wg * 8);
      const uint32_t va = sb + OFF_V + (w * 16 + (lane & 15)) * 128;
      uint32_t lk[8];
#pragma unroll
      for (int u = 0; u < kl; u++) lk[u] = 0x3FB8AA3Bu;
#pragma unroll
      for (int u = 0; u < 8; u++) {
        if (re && (u == Q0 || u == Q0 + QS)) {
          wg_fence();
          proj(pq, 0, u == Q0 ? 3 - re : 3, 1);
          wg_commit();
          if (wg == 0 && u != Q0) nb_arrive(NB_ORDER_12, 256);
          if (qw) {
            wg_wait<7>();
            const uint32_t l = lds32(sb + OFF_MISC + 20);
#pragma unroll
            for (int t = u; t < u + kl && t < 8; t++) lk[t] = l;
          }
        }
#pragma unroll
        for (int i = 0; i < 4; i++) pk[u][i] = phi2(ak[8 * u + 2 * i], ak[8 * u + 2 * i + 1], __uint_as_float(lk[u]));
        if (u == vk) { wg_wait<re ? (vk >= Q0) + (vk >= Q0 + QS) : 1>(); pin(av); }
        if (u == M0 && re) { wg_wait<(M0 >= Q0 + QS)>(); mbar_arrive_warp(sb + BAR_EMPTY + 6 * 8); }
        if (u == mm) { wg_wait<0>(); mbar_arrive_warp(sb + BAR_EMPTY + 7 * 8); }
        const uint32_t z = mism(pk[u][0], pk[u][1], 0) | mism(pk[u][2], pk[u][3], 0);
#pragma unroll
        for (int t = u < vk ? 8 : (u - vk) * 8 / (8 - vk); t < (u - vk + 1) * 8 / (8 - vk); t++) {
          const float* v = &av[8 * t];
          stsm4(va + (t >> 2) * 9216 + ((((lane >> 4) + 2 * (t & 3)) ^ (lane & 7)) << 4) + (z & zero), pack2(v[0], v[1]), pack2(v[2], v[3]), pack2(v[4], v[5]), pack2(v[6], v[7]));
        }
        if (u + kl < 8) lk[u + kl] = lds32(sb + OFF_MISC + 20 + (u < vk ? z & zero : 0));
      }
      fence_async_smem();
      nb_sync(nb_self, 128);
      PROF_C(wt == 0, 8 + wg * 8);
      const uint64_t dv = mkdesc(sb + OFF_V, 16, 1024, 1);
      wg_fence();
#pragma unroll
      for (int kk = 0; kk < 8; kk++) mma_ktv(c, pk[kk], dv + ((kk >> 2) * 576 + (kk & 3) * 2), kk ? 1 : 0);
      wg_commit();
      if (wg == 1) nb_arrive(NB_ORDER_3O, 256);
      wg_wait<0>();
      pin(c); pin(pq);
#pragma unroll
      for (int i = 0; i < 64; i++) aq[i] = pq[i];
      PROF_C(wt == 0, 4 + wg * 8);
#pragma unroll
      for (int i = 0; i < 8; i++) {
        const int j = (i & 3) * 4 + (i >> 2) * 2;
        su[i] = w >= 2 ? pack2(c[16 + j], c[17 + j]) : pack2(c[j], c[j + 1]);
      }
      su[8] = pack2(c[32], c[34]);
#pragma unroll
      for (int u = 0; u < 3; u++)
        if (u < R0 || wg) red_add_bf(kvacc + u * 128, su[3 * u], su[3 * u + 1], su[3 * u + 2]);
    };
    if (TR == 2) {
      if (wg == 0) finish(std::integral_constant<int, 0>());
      else finish(std::integral_constant<int, 1>());
    } else finish(std::integral_constant<int, TR>());
    const uint32_t par = lds32(sb + OFF_MISC + 24);
    {
      const bool paired = PAIRED && ld_relaxed(&gs->block[cta ^ 1]) == (blockIdx.x ^ 1);
      uint4 kv[3];
      int tries = wg ? 0 : TRY_A;
      const uint8_t* gl = smem + OFF_MISC + 20;
      asm volatile("" : "+l"(gl));
      const uint32_t l2e = ld_generic(gl);
    auto stage_kv = [&]() {
      const uint32_t kb = sb + OFF_KVB + w * 256, ka = kb + (lane & 3) * KVB_N + (lane >> 2) * 16;
      sts128(ka, kv[0].x, kv[0].y, kv[0].z, kv[1].x);
      sts128(ka + 128, kv[1].y, kv[1].z, kv[2].x, kv[2].y);
      sts32(kb + 4 * KVB_N + lane * 4, dup_lo(kv[2].z));
      sts32(kb + 4 * KVB_N + 128 + lane * 4, dup_hi(kv[2].z));
      return __all_sync(~0u, (kv[0].w & kv[1].w & kv[2].w) == 0x41804180u && (kv[0].w | kv[1].w | kv[2].w) == 0x41804180u);
    };
      bool have = false;
      const uint32_t qa = sb + OFF_PK + ((lane >> 4) * 8 + (lane & 7)) * 128 + (((2 * w + ((lane >> 3) & 1)) ^ (lane & 7)) << 4);
      uint32_t lq[8];
#pragma unroll
      for (int u = 0; u < QA; u++) lq[u] = l2e;
#pragma unroll
      for (int u = 0; u < 8; u++) {
        uint32_t r[4];
        if (u == KF && wg) {
#pragma unroll
          for (int i = 0; i < 3; i++) kv[i] = ld_relaxed4(kvacc + i * 128);
        }
#pragma unroll
        for (int i = 0; i < 4; i++) r[i] = phi2(aq[8 * u + 2 * i], aq[8 * u + 2 * i + 1], __uint_as_float(lq[u]));
        stsm4t(qa + u * 2048, r[0], r[1], r[2], r[3]);
        if (u % RS == RS - 1 && u / RS + R0 < 3 && !wg) red_add_bf(kvacc + (u / RS + R0) * 128, su[3 * (u / RS + R0)], su[3 * (u / RS + R0) + 1], su[3 * (u / RS + R0) + 2]);
        if (u + QA < 8) lq[u + QA] = QD ? ld_generic(gl) : lds32(sb + OFF_MISC + 20);
        if (u == KU && wg) have = stage_kv();
      }
      PROF_C(wt == 0, 34 + wg * 2);
      if (NAP_A && !wg) __nanosleep(NAP_A);
      if (KU > 7 && KF < 8 && wg) have = stage_kv();
      for (; !have; tries++) {
        if (tries > RETRY)
          while (ld_relaxed((const unsigned*)&(kvacc - lane)[256 + 31].w) != 0x41804180u) __nanosleep(wg ? KV_SLEEP : KV_SLEEP_A);
#pragma unroll
        for (int i = 0; i < 3; i++) kv[i] = ld_relaxed4(kvacc + i * 128);
        have = stage_kv();
      }
      PROF_C(wt == 0, 5 + wg * 8);
      fence_async_smem();
      nb_sync(nb_self, 128);
      float o[2][2][20];
      const uint64_t dq = mkdesc(sb + OFF_PK, 16, 1024, 1), dz = mkdesc(sb + OFF_KVB, 128, KVB_N, 0);
      wg_fence();
#pragma unroll
      for (int m = 0; m < 2; m++) {
#pragma unroll
        for (int h = 0; h < 2; h++)
#pragma unroll
          for (int kk = 0; kk < 2; kk++) mma_qkvz(o[m][h], dq + (m * 512 + h * 4 + kk * 2), dz + (h * 32 + kk * 16), kk);
        wg_commit();
      }
      if (HOLD < 8 && HP == 0 && wg) nb_arrive(NB_HOLD, 256);
      if (EF == 3 && wg && elect()) red_add(gs->cnt[16 + tm], 1u << tn * 4);
      uint32_t tag[2][4];
#pragma unroll
      for (int i = 0; i < 8; i++) tag[i >> 2][i & 3] = (lane >> 3) == (i & 3) && ((lane ^ (lane >> 3)) & 1) == (i >> 2);
      uint32_t gr[8];
      const uint8_t* ga = smem + OFF_G + (w * 16 + (lane >> 2)) * 4;
      asm volatile("" : "+l"(ga));
#pragma unroll
      for (int i = 0; i < OA; i++) gr[i] = ld_generic(ga + (i >> 2) * 256 + (i & 1) * 32);
      const uint32_t oo = w * 1024 + (lane >> 2) * 64 + (((lane ^ (lane >> 3)) & 3) << 4);
      uint8_t* const og = (uint8_t*)gs->o[tm][wg * 8 + tn] + oo;
      uint32_t ob[8][4];
#pragma unroll
      for (int m = 0; m < 2; m++) {
        if (m == 0) wg_wait<1>(); else wg_wait<0>();
        pin(o[m][0]); pin(o[m][1]);
        if (EF == 2 - m && wg && elect()) red_add(gs->cnt[16 + tm], 1u << tn * 4);
        if (PB == 2 - m && wg) mbar_arrive_warp(sb + BAR_PUB + 8);
        if (m && !wg) nb_arrive(NB_STG, 256);
        if (HOLD < 8 && HP == 1 && m && wg) nb_arrive(NB_HOLD, 256);
        if (m && wg && paired && elect()) mbar_arrive_peer(peer_addr(sb + BAR_PA));
        if (m == 0) PROF_C(wt == 0, 6 + wg * 8);
#pragma unroll
        for (int u = 0; u < 4; u++) {
          const int h = u >> 1, i = u & 1;
          const float* on = o[m][h];
          const float sc = __uint_as_float(gr[m * 4 + u]) * rcp(on[16 + 2 * i] + 1e-6f);
          const uint32_t sc2 = pack2(sc, sc);
#pragma unroll
          for (int j = 0; j < 4; j++) {
            const uint32_t v = HS ? mul_bf2(pack2(on[4 * j + 2 * i], on[4 * j + 2 * i + 1]), sc2) : pack2(on[4 * j + 2 * i] * sc, on[4 * j + 2 * i + 1] * sc);
            asm("lop3.b32 %0, %1, %2, %3, 0xB8;" : "=r"(ob[m * 4 + u][j]) : "r"(v), "r"(tag[i][j]), "r"(par));
          }
          st_relaxed4(og + (h * 8192 + m * 4096 + i * 512), ob[m * 4 + u]);
          if (OWN1 == 2 && wg) sts128(sb + OFF_V + oo + (h * 8192 + m * 4096 + i * 512), ob[m * 4 + u][0], ob[m * 4 + u][1], ob[m * 4 + u][2], ob[m * 4 + u][3]);
          if (HOLD < 8 && HP == 10 + m * 4 + u && wg) nb_arrive(NB_HOLD, 256);
          const int n = m * 4 + u + OA;
          if (n < 8) gr[n] = ld_generic(ga + (n >> 2) * 256 + (n & 1) * 32);
        }
      }
      if ((!EF || !wg) && elect()) red_add(gs->cnt[wg * 16 + tm], 1u << tn * 4);
      if (!PB || !wg) mbar_arrive_warp(sb + BAR_PUB + wg * 8);
      if (HOLD < 8 && HP == 2 && wg) nb_arrive(NB_HOLD, 256);
      PROF(wt == 0, 17 + wg);
      if (wg) {
        auto to_peer = [&]() {
        if (paired) {
          const uint32_t pb = peer_addr(sb);
          mbar_wait(sb + BAR_PA, 0);
#pragma unroll
          for (int u = 0; u < 8; u++) st_async4(pb + OFF_PK + oo + ((u >> 1 & 1) * 8192 + (u >> 2) * 4096 + (u & 1) * 512), ob[u], pb + BAR_PEER);
        }
        };
        if (!OWN1) to_peer();
#pragma unroll
        for (int u = 0, z = 0; u < (OWN1 == 2 ? 0 : 8); u++) {
          sts128(sb + OFF_V + oo + ((u >> 1 & 1) * 8192 + (u >> 2) * 4096 + (u & 1) * 512) + z, ob[u][0], ob[u][1], ob[u][2], ob[u][3]);
          if (PO && u % PO == PO - 1 && u < 7) z = lds32(sb + OFF_ONES) & 16;
        }
        fence_async_smem();
        __syncwarp();
        mbar_arrive_warp(sb + BAR_OWN);
        if (HOLD < 8 && HP == 3) nb_arrive(NB_HOLD, 256);
        PROF(wt == 0, 15);
        if (OWN1) to_peer();
      }
    }
    if (wg == 1) {
      verify_tiles<1>(sb, gs, tm, tn, w, lane);
    } else {
      float acc[2][64];
      nb_sync(NB_ORDER_3O, 256);
      PROF_C(wt == 0, 26);
      uint32_t xr[2][8][4], q[2][2];
      const uint32_t ta = sb + OFF_RES + (uint32_t)(w * 16 + (lane & 15)) * 128;
      const uint64_t do0 = mkdesc(sb + OFF_RING, 16, 512, 2);
      uint64_t xs = OA_SLOTS, ws = OW_SLOTS;
#pragma unroll 1
      for (int g = 0; g < 13 - TL; g++, xs >>= 4, ws >>= 4) {
        const uint32_t r = g * 52 >> 8, s = g - r * 5;
        const uint64_t da = do0 + ((uint32_t)xs & 15) * (SLOT >> 4), db = db0 + ((uint32_t)ws & 15) * (SLOT >> 4);
        if (g == OWN) mbar_wait(sb + BAR_OWN, 0);
        if (g == PEER) { mbar_wait(sb + BAR_PEER, 0); fence_async_smem(); }
        if (g == HOLD) {
          if (HR) { wg_wait<0>(); mbar_arrive_warp(sb + BAR_OEMPTY + (HOLD + 4) % 5 * 8); }
          nb_sync(NB_HOLD, 256);
        }
        mbar_wait(sb + BAR_OFULL + s * 8, r & 1);
        wg_fence();
#pragma unroll
        for (int kk = 0; kk < 4; kk++)
#pragma unroll
          for (int m = 0; m < 2; m++) mma128<0, 1>(acc[m], da + (m * 256 + (kk >> 1) * 512 + (kk & 1) * 2), db + kk * 128, kk ? 1 : g);
        wg_commit();
        wg_wait<1>();
        if (g && (g != HOLD || !HR)) mbar_arrive_warp(sb + BAR_OEMPTY + (s ? s - 1 : 4) * 8);
      }
      mbar_wait(sb + BAR_X, 0);
      const int selw = ((0xFFFF - (int)(lds32(sb + OFF_MISC + 16) & 0xFFFF)) >> 4) - tm * 8 - w;
#pragma unroll
      for (int u = 0; u < 4; u++) {
        const int m = u >> 1, g = 13 - TL + u;
        const float g1 = 1.f - __uint_as_float(lds32(sb + OFF_G + (m * 64 + w * 16 + (u & 1) * 8 + (lane >> 2)) * 4));
        q[m][u & 1] = pack2(g1, g1);
#pragma unroll
        for (int j = 0; j < 4; j++) ldsm4(ta + (u & 1) * RES_H + m * 8192 + ((((lane >> 4) + 2 * j) ^ (lane & 7)) << 4), xr[m][(u & 1) * 4 + j]);
        if (u == 3) break;
        mbar_wait(sb + BAR_OFULL + g % 5 * 8, g / 5 & 1);
        wg_fence();
#pragma unroll
        for (int kk = 0; kk < 4; kk++)
#pragma unroll
          for (int mm = 0; mm < 2; mm++)
            mma128<0, 1>(acc[mm], do0 + ((OA_SLOTS >> g * 4 & 15) * (SLOT >> 4) + mm * 256 + (kk >> 1) * 512 + (kk & 1) * 2), db0 + ((OW_SLOTS >> g * 4 & 15) * (SLOT >> 4) + kk * 128), 1);
        wg_commit();
        wg_wait<1>();
        if (g <= 11) mbar_arrive_warp(sb + BAR_OEMPTY + (g + 4) % 5 * 8);
      }
#pragma unroll
      for (int m = 0; m < 2; m++) {
#pragma unroll
        for (int g = 16 - TL; g < 16; g++) {
          if (m == 0) { mbar_wait(sb + BAR_OFULL + g % 5 * 8, g / 5 & 1); wg_fence(); }
#pragma unroll
          for (int kk = 0; kk < 4; kk++)
            mma128<0, 1>(acc[m], do0 + ((OA_SLOTS >> g * 4 & 15) * (SLOT >> 4) + m * 256 + (kk >> 1) * 512 + (kk & 1) * 2), db0 + ((OW_SLOTS >> g * 4 & 15) * (SLOT >> 4) + kk * 128), 1);
        }
        wg_commit();
      }
      mbar_arrive_warp(sb + BAR_DONE);
      const uint32_t tb = sb + OFF_RES + w * 2048 + (lane >> 3) * 128 + (((lane ^ (lane >> 3)) & 7) << 4), tx = lane & 4 ? 64 : -64;
      uint8_t* const og = (uint8_t*)pout + (size_t)(tm * 128 + w * 16 + (lane >> 3)) * 2048 + tn * 256 + (lane & 7) * 16;
#pragma unroll
      for (int m = 0; m < 2; m++) {
        if (selw == 4 * m) {
          mbar_wait(sb + BAR_Y, 0);
#pragma unroll
          for (int j = 0; j < 8; j++) ldsm4(ta + (j >> 2) * RES_H + m * 8192 + ((((lane >> 4) + 2 * (j & 3)) ^ (lane & 7)) << 4), xr[m][j]);
        }
        if (m == 0) wg_wait<1>(); else wg_wait<0>();
        if (m) PROF(wt == 0, 31);
#pragma unroll
        for (int h = 0; h < 2; h++) {
#pragma unroll
          for (int j = 4 * h; j < 4 * h + 4; j++) {
            const float* v = &acc[m][8 * j];
            stsm4(ta + h * RES_H + m * 8192 + ((((lane >> 4) + 2 * (j & 3)) ^ (lane & 7)) << 4),
                  fma_bf2(xr[m][j][0], q[m][0], pack2(v[0], v[1])), fma_bf2(xr[m][j][1], q[m][1], pack2(v[2], v[3])),
                  fma_bf2(xr[m][j][2], q[m][0], pack2(v[4], v[5])), fma_bf2(xr[m][j][3], q[m][1], pack2(v[6], v[7])));
          }
          if (FS >> m & 1) {
            __syncwarp();
            uint4 t[4];
#pragma unroll
            for (int j = 0; j < 4; j++) t[j] = lds128(tb + h * RES_H + m * 8192 + j * 512 - (j & 1) * tx);
#pragma unroll
            for (int j = 0; j < 4; j++) *(uint4*)(og + (m * 64 + j * 4) * 2048 + h * 128) = t[j];
          } else {
            fence_async_smem();
            __syncwarp();
            if (elect()) tma2d_store(&p.out, sb + OFF_RES + h * RES_H + m * 8192 + w * 2048, tn * 128 + h * 64, tm * 128 + m * 64 + w * 16);
          }
          if (FS != 3 && m && h && elect()) { bulk_commit(); asm volatile("cp.async.bulk.wait_group.read 0;" ::: "memory"); }
        }
        if (!m) PROF(wt == 0, 33);
      }
      PROF(wt == 0, 32);
    }
  }
}

typedef CUresult (*EncodeFn)(CUtensorMap*, CUtensorMapDataType, cuuint32_t, void*, const cuuint64_t*, const cuuint64_t*, const cuuint32_t*,
                             const cuuint32_t*, CUtensorMapInterleave, CUtensorMapSwizzle, CUtensorMapL2promotion, CUtensorMapFloatOOBfill);

void encode(EncodeFn fn, CUtensorMap* m, const void* ptr, int rank, const cuuint64_t* dims, const cuuint64_t* strides, const cuuint32_t* box,
            CUtensorMapSwizzle sw, CUtensorMapDataType dt = CU_TENSOR_MAP_DATA_TYPE_BFLOAT16) {
  const cuuint32_t es[3] = {1, 1, 1};
  fn(m, dt, rank, const_cast<void*>(ptr), dims, strides, box, es, CU_TENSOR_MAP_INTERLEAVE_NONE, sw,
     CU_TENSOR_MAP_L2_PROMOTION_L2_128B, CU_TENSOR_MAP_FLOAT_OOB_FILL_NONE);
}

}

extern "C" void kernel_launch(void* const* d_in, const int* in_sizes, int n_in, void* d_out, int out_size) {
  (void)in_sizes; (void)n_in; (void)out_size;
  EncodeFn fn = nullptr;
  cudaDriverEntryPointQueryResult qr;
  cudaGetDriverEntryPoint("cuTensorMapEncodeTiled", (void**)&fn, cudaEnableDefault, &qr);

  Params p;
  {
    const cuuint64_t dims[2] = {D_, S_}, str[1] = {D_ * 2};
    const cuuint32_t box[2] = {64, 128}, box_st[2] = {64, 16}, box_r[2] = {256, 16};
    encode(fn, &p.xr, d_in[0], 2, dims, str, box_r, CU_TENSOR_MAP_SWIZZLE_NONE);
    encode(fn, &p.x, d_in[0], 2, dims, str, box, CU_TENSOR_MAP_SWIZZLE_128B);
    encode(fn, &p.out, d_out, 2, dims, str, box_st, CU_TENSOR_MAP_SWIZZLE_128B);
  }
  {
    const cuuint64_t dims[3] = {D_, D_, 3}, str[2] = {3 * D_ * 2, D_ * 2};
    const cuuint32_t box[3] = {64, 64, 3};
    encode(fn, &p.w, d_in[1], 3, dims, str, box, CU_TENSOR_MAP_SWIZZLE_128B);
    const cuuint32_t box1[3] = {64, 64, 1};
    encode(fn, &p.w1, d_in[1], 3, dims, str, box1, CU_TENSOR_MAP_SWIZZLE_128B);
  }
  {
    const cuuint64_t dims[3] = {64, D_, D_ / 64}, str[2] = {D_ * 2, 128};
    const cuuint32_t box[3] = {64, 64, 2};
    encode(fn, &p.wo, d_in[2], 3, dims, str, box, CU_TENSOR_MAP_SWIZZLE_128B);
  }
  {
    const cuuint64_t dims[3] = {F_, D_ / 4, 4}, str[2] = {F_ * 8, F_ * 2};
    const cuuint32_t box[3] = {32, 16, 4};
    encode(fn, &p.gate, d_in[5], 3, dims, str, box, CU_TENSOR_MAP_SWIZZLE_NONE);
    encode(fn, &p.up, d_in[6], 3, dims, str, box, CU_TENSOR_MAP_SWIZZLE_NONE);
  }
  {
    const cuuint64_t dims[3] = {D_ / 4, F_, 2}, str[2] = {D_ * 2, D_};
    const cuuint32_t box[3] = {256, 4, 2};
    encode(fn, &p.down, d_in[7], 3, dims, str, box, CU_TENSOR_MAP_SWIZZLE_NONE, CU_TENSOR_MAP_DATA_TYPE_UINT32);
  }
  void* gs = nullptr;
  cudaGetSymbolAddress(&gs, g_scratch);
  typedef const __nv_bfloat16* bp;
  int dev = 0, sms = 0;
  cudaGetDevice(&dev);
  cudaDeviceGetAttribute(&sms, cudaDevAttrMultiProcessorCount, dev);
  const bool by_sm = BYSM && sms == NGRID;
  const auto kernel = by_sm ? fused_kernel<true> : fused_kernel<false>;
  cudaFuncSetAttribute(kernel, cudaFuncAttributeMaxDynamicSharedMemorySize, SMEM_BYTES);
  kernel<<<by_sm ? NGRID : NCTA, NTHREADS, SMEM_BYTES, cudaStreamPerThread>>>((bp)d_in[0], (Scratch*)gs, (bp)d_in[5], (bp)d_in[6], (bp)d_in[4], (bp)d_in[8], (bp)d_in[7], (__nv_bfloat16*)d_out, p);
}
```

```cpp
#include <cuda_runtime.h>
#include <cuda.h>
#include <cuda_bf16.h>
#include <stdint.h>
#include <stddef.h>
#include <type_traits>

namespace {

constexpr int S_ = 2048, D_ = 1024, F_ = 3584;
constexpr int NCTA = 128, NGRID = 132, NTHREADS = 512;
#define NOMOD 0
constexpr int MOD_CTAS = NOMOD ? 0 : F_ / 32;

#define PRE 2
#define ST1 700
#define RT_G0 2
#define RT_ROT 1
#define RT_SLEEP 500
#define PF_MOD 7
#define MOD_START 9
#define MM 3
#define PO 2
#define A_SLEEP 128
#define KU 99
#define HS 1
#define HOLD 5
#define OWN1 2
#define KF 5
#define QA 3
#define R0 1
#define OA 3
#define QD 0
#define MOD_SLEEP 0
#define MOD_S0 8
#define Y_SLEEP 200
#define PD 0
#define TRY_A 9
#define NAP_A 0
#define VK 1
#define TR 2
#define Q0 0
#define QS 2
#define QW1 0
#define VK1 2
#define MM1 5
#define KL1 2
#define M0 3
#define HP 1
#define FS 0
#define RH 0
#define SP 1
#define D1 0
#define E7 1
#define ST0 1600
#define KL 3
#define RS 2
#define RETRY 1
#define KV_SLEEP_A 64
#define KV_SLEEP 50
#define TL 3
#define EF 2
#define DYN 0
#define FN 0
#define PB 1
#define B_SLEEP 32
#define PW 1
#define HR 0
#define PAIRED 1
#define BYSM 1

constexpr uint32_t SLOT = 16384, WQKV_BYTES = 24576;
constexpr int MOD_BUFS = 3, MOD_BUFS0 = MOD_BUFS + 2;
static_assert(MOD_START + MOD_BUFS0 <= 16, "first FFN round is requested during W1");
constexpr uint32_t OFF_RING = 0, OFF_W1 = 4 * SLOT;
constexpr uint64_t OA_SLOTS = 0x0AB210AB21098210ull, OW_SLOTS = 0x4376543765437654ull;
constexpr uint32_t OFF_RES = OFF_RING + 8 * SLOT, RES_H = SLOT;
constexpr uint32_t OFF_PK = 10 * SLOT;
constexpr uint32_t OFF_V = 11 * SLOT;
constexpr uint32_t OFF_ONES = OFF_V + 9216 + 8192;
constexpr uint32_t MOD_STEP = 9216, OFF_MOD = OFF_V + 2 * MOD_STEP;
constexpr uint32_t OFF_XSEL = OFF_MOD + 8192;
constexpr uint32_t OFF_KVB = OFF_MOD + 2 * MOD_STEP + 8192;
constexpr uint32_t KVB_N = 1056;
constexpr uint32_t OFF_G = OFF_KVB + 4 * KVB_N + 1024;
constexpr uint32_t OFF_PART = OFF_G + 512;
constexpr uint32_t OFF_MISC = OFF_PART + 576;
constexpr uint32_t OFF_BAR = OFF_MISC + 32;
constexpr uint32_t SMEM_BYTES = OFF_BAR + 488;
constexpr uint32_t BAR_FULL = OFF_BAR, BAR_Y = BAR_FULL + 64, BAR_X = BAR_Y + 8, BAR_PEER = BAR_X + 8, BAR_GATE = BAR_PEER + 8, BAR_RT = BAR_GATE + 8,
                   BAR_FIX = BAR_RT,
                   BAR_MFULL = BAR_FIX + 64, BAR_LAND = BAR_FULL,
                   BAR_EMPTY = OFF_BAR + 28 * 8, BAR_OEMPTY = BAR_EMPTY + 64, BAR_RTD = BAR_OEMPTY + 40, BAR_DONE = BAR_RTD + 8,
                   BAR_OWN = BAR_DONE + 8, BAR_PA = BAR_OWN + 8, BAR_PUB = BAR_PA + 8, BAR_MEMPTY = BAR_PUB + 16,
                   BAR_IDX = BAR_MEMPTY + 8,
                   BAR_OFULL = OFF_BAR + 52 * 8, BAR_SP = OFF_BAR + 60 * 8;
static_assert(BAR_MFULL + MOD_BUFS0 * 8 <= BAR_EMPTY && BAR_MEMPTY + MOD_BUFS0 * 8 == BAR_OFULL, "barrier groups");
static_assert(SMEM_BYTES <= 232448, "smem");
static_assert(TL == 3 && PRE == 2, "schedule");

constexpr int NB_WG0 = 1, NB_ORDER_12 = 3, NB_ORDER_3O = 4, NB_STG = 5, NB_MODW = 6, NB_KEY = 7, NB_HOLD = 8;

struct Scratch {
  uint4 kv[2][8][3][128];
  float4 y[2][3][128];
  unsigned cnt[32][32];
  unsigned gslot[S_];
  unsigned rslot[8][NCTA];
  unsigned spare[128];
  unsigned block[NCTA];
  uint4 o[16][16][1024];
};
static_assert(offsetof(Scratch, gslot) == NCTA * 56 * 16, "clear size");
__device__ __align__(1024) Scratch g_scratch;

#define PROF(cond, i) do {} while (0)
#define PROF_C(cond, i) do {} while (0)

__device__ __forceinline__ void mbar_init(uint32_t bar, int cnt) { asm volatile("mbarrier.init.shared::cta.b64 [%0], %1;" ::"r"(bar), "r"(cnt)); }
__device__ __forceinline__ void mbar_expect_tx(uint32_t bar, uint32_t bytes) { asm volatile("mbarrier.arrive.expect_tx.shared::cta.b64 _, [%0], %1;" ::"r"(bar), "r"(bytes) : "memory"); }
__device__ __forceinline__ void mbar_arrive(uint32_t bar) { asm volatile("mbarrier.arrive.shared::cta.b64 _, [%0];" ::"r"(bar) : "memory"); }
__device__ __forceinline__ uint32_t peer_addr(uint32_t a) {
  uint32_t r;
  asm volatile("{\n.reg .u32 c;\nmov.u32 c, %%cluster_ctarank;\nxor.b32 c, c, 1;\nmapa.shared::cluster.u32 %0, %1, c;\n}" : "=r"(r) : "r"(a));
  return r;
}
__device__ __forceinline__ void mbar_arrive_peer(uint32_t bar) { asm volatile("mbarrier.arrive.shared::cluster.b64 _, [%0];" ::"r"(bar) : "memory"); }
__device__ __forceinline__ uint32_t mism(uint32_t a, uint32_t b, uint32_t p) {
  uint32_t r; asm("lop3.b32 %0, %1, %2, %3, 0x7E;" : "=r"(r) : "r"(a), "r"(b), "r"(p)); return r;
}
__device__ __forceinline__ bool elect() {
  uint32_t r;
  asm volatile("{\n.reg .pred p;\nelect.sync _|p, 0xffffffff;\nselp.u32 %0, 1, 0, p;\n}" : "=r"(r));
  return r;
}
__device__ __forceinline__ uint32_t fresh_tid() { uint32_t r; asm volatile("mov.u32 %0, %%tid.x;" : "=r"(r)); return r; }
__device__ __forceinline__ void mbar_arrive_warp(uint32_t bar) {
  asm volatile("{\n.reg .pred p;\nelect.sync _|p, 0xffffffff;\n@p mbarrier.arrive.shared::cta.b64 _, [%0];\n}" ::"r"(bar) : "memory");
}
__device__ __forceinline__ void mbar_wait(uint32_t bar, uint32_t parity) {
  asm volatile("{\n.reg .pred p;\nWAIT_L:\nmbarrier.try_wait.parity.shared::cta.b64 p, [%0], %1;\n@p bra DONE_L;\nbra WAIT_L;\nDONE_L:\n}"
               ::"r"(bar), "r"(parity) : "memory");
}
__device__ __forceinline__ uint32_t mbar_try(uint32_t bar, uint32_t parity) {
  uint32_t ok;
  asm volatile("{\n.reg .pred p;\nmbarrier.try_wait.parity.shared::cta.b64 p, [%1], %2;\nselp.u32 %0, 1, 0, p;\n}" : "=r"(ok) : "r"(bar), "r"(parity) : "memory");
  return ok;
}
__device__ __forceinline__ uint32_t mbar_test(uint32_t bar, uint32_t parity) {
  uint32_t ok;
  asm volatile("{\n.reg .pred p;\nmbarrier.test_wait.parity.shared::cta.b64 p, [%1], %2;\nselp.u32 %0, 1, 0, p;\n}" : "=r"(ok) : "r"(bar), "r"(parity) : "memory");
  return ok;
}
constexpr unsigned long long WATCHDOG_NS = 2000000000ull;
__device__ __forceinline__ unsigned long long gtime() { unsigned long long t; asm volatile("mov.u64 %0, %%globaltimer;" : "=l"(t)); return t; }
__device__ __forceinline__ uint32_t clock32() { uint32_t t; asm volatile("mov.u32 %0, %%clock;" : "=r"(t)); return t; }
__device__ __forceinline__ void mbar_wait_bounded(uint32_t bar, uint32_t parity) {
  unsigned long long t0 = 0;
  for (;;) {
    uint32_t ok;
    asm volatile("{\n.reg .pred p;\nmbarrier.try_wait.parity.shared::cta.b64 p, [%1], %2;\nselp.u32 %0, 1, 0, p;\n}" : "=r"(ok) : "r"(bar), "r"(parity) : "memory");
    if (ok) break;
    const unsigned long long t1 = gtime();
    if (t0 == 0) t0 = t1;
    if (t1 - t0 > WATCHDOG_NS) __trap();
  }
}
__device__ __forceinline__ void tma2d(uint32_t dst, const CUtensorMap* m, int c0, int c1, uint32_t bar) {
  asm volatile("cp.async.bulk.tensor.2d.shared::cluster.global.mbarrier::complete_tx::bytes [%0], [%1, {%3, %4}], [%2];"
               ::"r"(dst), "l"(m), "r"(bar), "r"(c0), "r"(c1) : "memory");
}
__device__ __forceinline__ void tma3d(uint32_t dst, const CUtensorMap* m, int c0, int c1, int c2, uint32_t bar) {
  asm volatile("cp.async.bulk.tensor.3d.shared::cluster.global.mbarrier::complete_tx::bytes [%0], [%1, {%3, %4, %5}], [%2];"
               ::"r"(dst), "l"(m), "r"(bar), "r"(c0), "r"(c1), "r"(c2) : "memory");
}
__device__ __forceinline__ void bulk_load(uint32_t dst, const void* src, uint32_t bytes, uint32_t bar) {
  asm volatile("cp.async.bulk.shared::cluster.global.mbarrier::complete_tx::bytes [%0], [%1], %2, [%3];" ::"r"(dst), "l"(src), "r"(bytes), "r"(bar) : "memory");
}
__device__ __forceinline__ void bulk_store(void* dst, uint32_t src, uint32_t bytes) {
  asm volatile("cp.async.bulk.global.shared::cta.bulk_group [%0], [%1], %2;" ::"l"(dst), "r"(src), "r"(bytes) : "memory");
}
__device__ __forceinline__ void st_async4(uint32_t dst, const uint32_t (&v)[4], uint32_t bar) {
  asm volatile("st.async.shared::cluster.mbarrier::complete_tx::bytes.v4.b32 [%0], {%1, %2, %3, %4}, [%5];" ::"r"(dst), "r"(v[0]), "r"(v[1]), "r"(v[2]), "r"(v[3]), "r"(bar) : "memory");
}
__device__ __forceinline__ void bulk_commit() { asm volatile("cp.async.bulk.commit_group;" ::: "memory"); }
__device__ __forceinline__ void bulk_prefetch(const void* p, uint32_t bytes) {
  asm volatile("cp.async.bulk.prefetch.L2.global [%0], %1;" ::"l"(p), "r"(bytes) : "memory");
}
__device__ __forceinline__ void tma2d_store(const CUtensorMap* m, uint32_t src, int c0, int c1) {
  asm volatile("cp.async.bulk.tensor.2d.global.shared::cta.bulk_group [%0, {%2, %3}], [%1];" ::"l"(m), "r"(src), "r"(c0), "r"(c1) : "memory");
}
__device__ __forceinline__ void wg_fence() { asm volatile("wgmma.fence.sync.aligned;" ::: "memory"); }
__device__ __forceinline__ void wg_commit() { asm volatile("wgmma.commit_group.sync.aligned;" ::: "memory"); }
template <int N> __device__ __forceinline__ void wg_wait() { asm volatile("wgmma.wait_group.sync.aligned %0;" ::"n"(N) : "memory"); }
__device__ __forceinline__ void fence_async_smem() { asm volatile("fence.proxy.async.shared::cta;" ::: "memory"); }
__device__ __forceinline__ void fence_async_global() { asm volatile("fence.proxy.async.global;" ::: "memory"); }
__device__ __forceinline__ void fence_release() { asm volatile("fence.release.gpu;" ::: "memory"); }
__device__ __forceinline__ void fence_acquire() { asm volatile("fence.acquire.gpu;" ::: "memory"); }
__device__ __forceinline__ void nb_sync(int id, int n) { asm volatile("bar.sync %0, %1;" ::"r"(id), "r"(n) : "memory"); }
__device__ __forceinline__ void nb_arrive(int id, int n) { asm volatile("bar.arrive %0, %1;" ::"r"(id), "r"(n) : "memory"); }
__device__ __forceinline__ void stsm4(uint32_t addr, uint32_t r0, uint32_t r1, uint32_t r2, uint32_t r3) {
  asm volatile("stmatrix.sync.aligned.m8n8.x4.shared.b16 [%0], {%1, %2, %3, %4};" ::"r"(addr), "r"(r0), "r"(r1), "r"(r2), "r"(r3) : "memory");
}
__device__ __forceinline__ void stsm4t(uint32_t addr, uint32_t r0, uint32_t r1, uint32_t r2, uint32_t r3) {
  asm volatile("stmatrix.sync.aligned.m8n8.x4.trans.shared.b16 [%0], {%1, %2, %3, %4};" ::"r"(addr), "r"(r0), "r"(r1), "r"(r2), "r"(r3) : "memory");
}
__device__ __forceinline__ void st_relaxed4(void* p, const uint32_t (&v)[4]) {
  asm volatile("st.relaxed.gpu.global.v4.u32 [%0], {%1, %2, %3, %4};" ::"l"(p), "r"(v[0]), "r"(v[1]), "r"(v[2]), "r"(v[3]) : "memory");
}
__device__ __forceinline__ void sts128(uint32_t addr, uint32_t a, uint32_t b, uint32_t c, uint32_t d) {
  asm volatile("st.shared.v4.b32 [%0], {%1, %2, %3, %4};" ::"r"(addr), "r"(a), "r"(b), "r"(c), "r"(d) : "memory");
}
__device__ __forceinline__ uint32_t pack2(float lo, float hi) {
  uint32_t r; asm("cvt.rn.bf16x2.f32 %0, %1, %2;" : "=r"(r) : "f"(hi), "f"(lo)); return r;
}
__device__ __forceinline__ float bf_lo(uint32_t v) { return __uint_as_float(v << 16); }
__device__ __forceinline__ float bf_hi(uint32_t v) { return __uint_as_float(v & 0xffff0000u); }
__device__ __forceinline__ float bf_round(float v) { return __bfloat162float(__float2bfloat16_rn(v)); }
__device__ __forceinline__ void ldsm4(uint32_t addr, uint32_t (&r)[4]) {
  asm volatile("ldmatrix.sync.aligned.m8n8.x4.shared.b16 {%0, %1, %2, %3}, [%4];" : "=r"(r[0]), "=r"(r[1]), "=r"(r[2]), "=r"(r[3]) : "r"(addr) : "memory");
}
__device__ __forceinline__ uint4 lds128(uint32_t addr) {
  uint4 v; asm volatile("ld.volatile.shared.v4.u32 {%0, %1, %2, %3}, [%4];" : "=r"(v.x), "=r"(v.y), "=r"(v.z), "=r"(v.w) : "r"(addr) : "memory"); return v;
}
__device__ __forceinline__ uint2 lds64(uint32_t addr) { uint2 v; asm volatile("ld.volatile.shared.v2.u32 {%0, %1}, [%2];" : "=r"(v.x), "=r"(v.y) : "r"(addr) : "memory"); return v; }
__device__ __forceinline__ uint32_t lds32(uint32_t addr) { uint32_t v; asm volatile("ld.volatile.shared.u32 %0, [%1];" : "=r"(v) : "r"(addr) : "memory"); return v; }
__device__ __forceinline__ uint32_t ld_generic(const void* p) { uint32_t v; asm volatile("ld.volatile.u32 %0, [%1];" : "=r"(v) : "l"(p) : "memory"); return v; }
__device__ __forceinline__ void sts32(uint32_t addr, uint32_t v) { asm volatile("st.shared.u32 [%0], %1;" ::"r"(addr), "r"(v) : "memory"); }
__device__ __forceinline__ uint32_t fma_bf2(uint32_t a, uint32_t b, uint32_t c) { uint32_t r; asm("fma.rn.bf16x2 %0, %1, %2, %3;" : "=r"(r) : "r"(a), "r"(b), "r"(c)); return r; }
__device__ __forceinline__ uint32_t mul_bf2(uint32_t a, uint32_t b) { uint32_t r; asm("mul.rn.bf16x2 %0, %1, %2;" : "=r"(r) : "r"(a), "r"(b)); return r; }
__device__ __forceinline__ unsigned ld_relaxed(const unsigned* p) { unsigned v; asm volatile("ld.relaxed.gpu.global.u32 %0, [%1];" : "=r"(v) : "l"(p) : "memory"); return v; }
__device__ __forceinline__ void st_relaxed(unsigned* p, unsigned v) { asm volatile("st.relaxed.gpu.global.u32 [%0], %1;" ::"l"(p), "r"(v) : "memory"); }
__device__ __forceinline__ uint4 ld_relaxed4(const void* p) {
  uint4 v; asm volatile("ld.relaxed.gpu.global.v4.u32 {%0, %1, %2, %3}, [%4];" : "=r"(v.x), "=r"(v.y), "=r"(v.z), "=r"(v.w) : "l"(p) : "memory"); return v;
}
__device__ __forceinline__ float4 ld_relaxed_f4(const void* p) {
  float4 v; asm volatile("ld.relaxed.gpu.global.v4.f32 {%0, %1, %2, %3}, [%4];" : "=f"(v.x), "=f"(v.y), "=f"(v.z), "=f"(v.w) : "l"(p) : "memory"); return v;
}
__device__ __forceinline__ void red_add4(void* p, float a, float b, float c, float d) {
  asm volatile("red.relaxed.gpu.global.add.v4.f32 [%0], {%1, %2, %3, %4};" ::"l"(p), "f"(a), "f"(b), "f"(c), "f"(d) : "memory");
}
__device__ __forceinline__ void red_add_bf(void* p, uint32_t a, uint32_t b, uint32_t c) {
  asm volatile("red.relaxed.gpu.global.add.noftz.v4.bf16x2 [%0], {%1, %2, %3, %4};" ::"l"(p), "r"(a), "r"(b), "r"(c), "r"(0x3F803F80u) : "memory");
}
__device__ __forceinline__ void red_add(unsigned* p, unsigned v) { asm volatile("red.relaxed.gpu.global.add.u32 [%0], %1;" ::"l"(p), "r"(v) : "memory"); }
__device__ __forceinline__ float rcp(float v) { float r; asm("rcp.approx.ftz.f32 %0, %1;" : "=f"(r) : "f"(v)); return r; }
__device__ __forceinline__ float sigmoidf_(float v) { return rcp(1.f + __expf(-v)); }
__device__ __forceinline__ uint32_t phi2(float a, float b, float l2e = 1.4426950408889634f) {
  float ea, eb;
  asm("ex2.approx.ftz.f32 %0, %1;" : "=f"(ea) : "f"(a * l2e));
  asm("ex2.approx.ftz.f32 %0, %1;" : "=f"(eb) : "f"(b * l2e));
  uint32_t t = pack2(a, b), e = pack2(ea, eb), r;
  asm("max.NaN.bf16x2 %0, %0, %1;" : "+r"(t) : "r"(0x35863586u));
  asm("min.bf16x2 %0, %0, %1;" : "+r"(e) : "r"(0x3F803F80u));
  asm("add.rn.bf16x2 %0, %1, %2;" : "=r"(r) : "r"(t), "r"(e));
  return r;
}
__device__ __forceinline__ uint64_t mkdesc(uint32_t addr, uint32_t lbo, uint32_t sbo, uint32_t sw) {
  return (uint64_t)(((addr & 0x3FFFF) >> 4) | ((lbo >> 4) << 16)) | ((uint64_t)((sbo >> 4) | (sw << 30)) << 32);
}

template <int TA, int TB>
__device__ __forceinline__ void mma128(float (&d)[64], uint64_t da, uint64_t db, int sc) {
  asm volatile("{\n.reg .pred p;\nsetp.ne.b32 p, %66, 0;\n"
    "wgmma.mma_async.sync.aligned.m64n128k16.f32.bf16.bf16 "
    "{%0,%1,%2,%3,%4,%5,%6,%7,%8,%9,%10,%11,%12,%13,%14,%15,%16,%17,%18,%19,%20,%21,%22,%23,"
    "%24,%25,%26,%27,%28,%29,%30,%31,%32,%33,%34,%35,%36,%37,%38,%39,%40,%41,%42,%43,%44,%45,%46,%47,"
    "%48,%49,%50,%51,%52,%53,%54,%55,%56,%57,%58,%59,%60,%61,%62,%63}, "
    "%64, %65, p, 1, 1, %67, %68;\n}\n"
    : "+f"(d[0]), "+f"(d[1]), "+f"(d[2]), "+f"(d[3]), "+f"(d[4]), "+f"(d[5]), "+f"(d[6]), "+f"(d[7]),
      "+f"(d[8]), "+f"(d[9]), "+f"(d[10]), "+f"(d[11]), "+f"(d[12]), "+f"(d[13]), "+f"(d[14]), "+f"(d[15]),
      "+f"(d[16]), "+f"(d[17]), "+f"(d[18]), "+f"(d[19]), "+f"(d[20]), "+f"(d[21]), "+f"(d[22]), "+f"(d[23]),
      "+f"(d[24]), "+f"(d[25]), "+f"(d[26]), "+f"(d[27]), "+f"(d[28]), "+f"(d[29]), "+f"(d[30]), "+f"(d[31]),
      "+f"(d[32]), "+f"(d[33]), "+f"(d[34]), "+f"(d[35]), "+f"(d[36]), "+f"(d[37]), "+f"(d[38]), "+f"(d[39]),
      "+f"(d[40]), "+f"(d[41]), "+f"(d[42]), "+f"(d[43]), "+f"(d[44]), "+f"(d[45]), "+f"(d[46]), "+f"(d[47]),
      "+f"(d[48]), "+f"(d[49]), "+f"(d[50]), "+f"(d[51]), "+f"(d[52]), "+f"(d[53]), "+f"(d[54]), "+f"(d[55]),
      "+f"(d[56]), "+f"(d[57]), "+f"(d[58]), "+f"(d[59]), "+f"(d[60]), "+f"(d[61]), "+f"(d[62]), "+f"(d[63])
    : "l"(da), "l"(db), "r"(sc), "n"(TA), "n"(TB));
}

__device__ __forceinline__ void mma_ktv(float (&d)[36], const uint32_t (&a)[4], uint64_t db, int sc) {
  asm volatile("{\n.reg .pred p;\nsetp.ne.b32 p, %41, 0;\n"
    "wgmma.mma_async.sync.aligned.m64n72k16.f32.bf16.bf16 "
    "{%0,%1,%2,%3,%4,%5,%6,%7,%8,%9,%10,%11,%12,%13,%14,%15,%16,%17,%18,%19,%20,%21,%22,%23,"
    "%24,%25,%26,%27,%28,%29,%30,%31,%32,%33,%34,%35}, "
    "{%36,%37,%38,%39}, %40, p, 1, 1, 0;\n}\n"
    : "+f"(d[0]), "+f"(d[1]), "+f"(d[2]), "+f"(d[3]), "+f"(d[4]), "+f"(d[5]), "+f"(d[6]), "+f"(d[7]),
      "+f"(d[8]), "+f"(d[9]), "+f"(d[10]), "+f"(d[11]), "+f"(d[12]), "+f"(d[13]), "+f"(d[14]), "+f"(d[15]),
      "+f"(d[16]), "+f"(d[17]), "+f"(d[18]), "+f"(d[19]), "+f"(d[20]), "+f"(d[21]), "+f"(d[22]), "+f"(d[23]),
      "+f"(d[24]), "+f"(d[25]), "+f"(d[26]), "+f"(d[27]), "+f"(d[28]), "+f"(d[29]), "+f"(d[30]), "+f"(d[31]),
      "+f"(d[32]), "+f"(d[33]), "+f"(d[34]), "+f"(d[35])
    : "r"(a[0]), "r"(a[1]), "r"(a[2]), "r"(a[3]), "l"(db), "r"(sc));
}

__device__ __forceinline__ void mma_qkvz(float (&d)[20], uint64_t da, uint64_t db, int sc) {
  asm volatile("{\n.reg .pred p;\nsetp.ne.b32 p, %22, 0;\n"
    "wgmma.mma_async.sync.aligned.m64n40k16.f32.bf16.bf16 "
    "{%0,%1,%2,%3,%4,%5,%6,%7,%8,%9,%10,%11,%12,%13,%14,%15,%16,%17,%18,%19}, "
    "%20, %21, p, 1, 1, 0, 1;\n}\n"
    : "+f"(d[0]), "+f"(d[1]), "+f"(d[2]), "+f"(d[3]), "+f"(d[4]), "+f"(d[5]), "+f"(d[6]), "+f"(d[7]),
      "+f"(d[8]), "+f"(d[9]), "+f"(d[10]), "+f"(d[11]), "+f"(d[12]), "+f"(d[13]), "+f"(d[14]), "+f"(d[15]),
      "+f"(d[16]), "+f"(d[17]), "+f"(d[18]), "+f"(d[19])
    : "l"(da), "l"(db), "r"(sc));
}

template <int N> __device__ __forceinline__ void pin(float (&d)[N]) {
#pragma unroll
  for (int i = 0; i < N; i++) asm volatile("" : "+f"(d[i])::"memory");
}

struct Params {
  CUtensorMap x, w, w1, xr, gate, up, wo, out, down;
};

__device__ __forceinline__ uint32_t dup_lo(uint32_t v) { uint32_t r; asm("{\n.reg .b16 l, h;\nmov.b32 {l, h}, %1;\nmov.b32 %0, {l, l};\n}" : "=r"(r) : "r"(v)); return r; }
__device__ __forceinline__ uint32_t dup_hi(uint32_t v) { uint32_t r; asm("{\n.reg .b16 l, h;\nmov.b32 {l, h}, %1;\nmov.b32 %0, {h, h};\n}" : "=r"(r) : "r"(v)); return r; }
__device__ __forceinline__ float butterfly8(float (&s)[8], int lane, int o) {
#pragma unroll
  for (int k = 1; k < 8; k <<= 1) {
    const bool up = lane & (o * k);
#pragma unroll
    for (int j = 0; j < 4 / k; j++) s[j] = (up ? s[2 * j + 1] : s[2 * j]) + __shfl_xor_sync(~0u, up ? s[2 * j] : s[2 * j + 1], o * k);
  }
  return s[0];
}
constexpr int OWN = 8, PEER = 9;
static_assert((OA_SLOTS >> OWN * 4 & 15) * SLOT == OFF_V && (OA_SLOTS >> PEER * 4 & 15) * SLOT == OFF_PK, "");
template <int B> __device__ __forceinline__ void verify_tiles(uint32_t sb, Scratch* gs, int tm, int tn, int w, int lane) {
  const uint32_t par = lds32(sb + OFF_MISC + 24), fix = sb + BAR_FIX + (B * 4 + w) * 8;
  uint32_t slots = (uint32_t)(OA_SLOTS >> B * 40);
#pragma unroll 1
  for (int i = 0; i < 8 - 2 * B; i++, slots >>= 4) {
    const uint32_t a = sb + OFF_RING + (slots & 15) * SLOT + w * 1024, cw = a + lane * 32 + (lane >> 2) * 4;
    if (!B && i == 4) mbar_wait(sb + BAR_EMPTY + 7 * 8, 1);
    mbar_wait(sb + BAR_LAND + i * 8, B);
    for (;;) {
      const uint32_t u0 = lds32(cw), u1 = lds32(cw + 4096), u2 = lds32(cw + 8192), u3 = lds32(cw + 12288);
      if (__all_sync(~0u, !(mism(mism(u0, u1, par), mism(u2, u3, par), 0) & 1))) break;
      const uint4* src = gs->o[tm][!B ? i : DYN ? lds32(sb + OFF_MISC + (i & 4)) >> (i & 3) * 8 & 15 : i < (tn & 6) ? i + 8 : i + 10] + w * 64;
      const uint32_t ph = !mbar_test(fix, 1);
      fence_async_smem();
      __syncwarp();
      if (elect()) {
        mbar_expect_tx(fix, 4096);
#pragma unroll 1
        for (int j = 0; j < 4; j++) bulk_load(a + j * 4096, src + j * 256, 1024, fix);
      }
      mbar_wait(fix, ph);
    }
    mbar_arrive_warp(sb + BAR_OFULL + (i < 5 ? i : i - 5) * 8);
  }
}
template <bool BY_SM> struct Tile {
  int sm, tm, tn, mu;
  bool spare;
  __device__ __forceinline__ Tile() {
    if (BY_SM) asm volatile("mov.u32 %0, %%smid;" : "=r"(sm));
    else sm = blockIdx.x + (blockIdx.x >= 120) * 4;
    const int tp = sm >> 1, pr = sm & 1;
    const int v = tp < 32 ? tp : tp < 60 ? (tp * 293 - 928) >> 8 : tp * 8 - 464, g = v & 7, i = v >> 3;
    tm = (v & 6) * 2 + (i & 3); tn = (v & 1) * 4 + (v >> 4 & 2) + pr;
    mu = i == 5 ? 112 : g * 14 + (i - (i > 5)) * 2 + pr;
    spare = (tp | 1) == 61;
  }
};

template <bool BY_SM> __global__ void __cluster_dims__(2, 1, 1) __launch_bounds__(NTHREADS, 1) fused_kernel(const __nv_bfloat16* __restrict__ px, Scratch* gs, const __nv_bfloat16* __restrict__ w_gate,
             const __nv_bfloat16* __restrict__ w_up, const __nv_bfloat16* __restrict__ w_r, const __nv_bfloat16* __restrict__ gate_w, const __nv_bfloat16* __restrict__ w_down, __nv_bfloat16* __restrict__ pout,
             const __grid_constant__ Params p) {
  extern __shared__ __align__(1024) uint8_t smem[];
  const uint32_t sb = __shfl_sync(~0u, (uint32_t)__cvta_generic_to_shared(smem), 0);
  const int tid = threadIdx.x, lane = tid & 31;
  const int warp = __shfl_sync(~0u, tid >> 5, 0), wg = warp >> 2;
  const uint32_t t_start = clock32();
  const Tile<BY_SM> tile;
  const int tm = tile.tm, tn = tile.tn, mu = tile.mu, cta = tm * 8 + tn;
  const uint32_t zero = tile.sm >> 12;
  if (warp == 0) {
#pragma unroll
    for (int s = 0; s < (D1 ? 1 : PRE); s++)
      if (elect()) mbar_init(sb + BAR_FULL + s * 8, 1);
    if (SP && elect()) mbar_init(sb + BAR_SP, 1);
    asm volatile("fence.mbarrier_init.release.cluster;" ::: "memory");
    if (!tile.spare) {
      if (SP) {
        if (elect()) tma3d(sb + OFF_W1 + 8192, &p.w1, tn * 64, 0, 1, sb + BAR_FULL);
        if (elect()) tma2d(sb + OFF_RING, &p.x, 0, tm * 128, sb + BAR_FULL);
        if (elect()) tma3d(sb + OFF_W1 + 16384, &p.w1, tn * 64, 0, 2, sb + BAR_SP);
        if (elect()) tma3d(sb + OFF_W1, &p.w1, tn * 64, 0, 0, sb + BAR_SP);
        PROF(lane == 0, 64);
      }
#pragma unroll
      for (int s = SP; s < (D1 ? 1 : PRE); s++) {
        if (elect()) tma3d(sb + OFF_W1 + s * WQKV_BYTES, &p.w, tn * 64, s * 64, 0, sb + BAR_FULL + s * 8);
        if (elect()) tma2d(sb + OFF_RING + s * SLOT, &p.x, s * 64, tm * 128, sb + BAR_FULL + s * 8);
        PROF(lane == 0, 64 + s);
      }
      if (elect()) {
#pragma unroll
        for (int s = 0; s < (D1 ? 1 : PRE); s++) mbar_expect_tx(sb + BAR_FULL + s * 8, s || !SP ? SLOT + WQKV_BYTES : SLOT + 8192);
        if (SP) mbar_expect_tx(sb + BAR_SP, 16384);
      }
    }
  }
  if (warp) {
    const int wi = warp == 15 ? 0 : warp;
    const int cnt = wi < 7 ? 1 : wi < 13 ? 4 : 5;
#pragma unroll
    for (int i = 0; i < 4; i++)
      if ((i >= (D1 ? 1 : PRE) || wi) && elect()) mbar_init(sb + OFF_BAR + wi * 32 + i * 8, cnt);
    asm volatile("fence.mbarrier_init.release.cluster;" ::: "memory");
    if (D1 && warp == 15 && !tile.spare) {
      while ((int)(clock32() - t_start) < D1) {}
      if (elect()) tma2d(sb + OFF_RING + SLOT, &p.x, 64, tm * 128, sb + BAR_FULL + 8);
      if (elect()) tma3d(sb + OFF_W1 + WQKV_BYTES, &p.w, tn * 64, 64, 0, sb + BAR_FULL + 8);
      if (elect()) mbar_expect_tx(sb + BAR_FULL + 8, SLOT + WQKV_BYTES);
      PROF(lane == 0, 65);
    }
  }
  __syncthreads();
  if (tile.spare) {
    if (warp == 0) {
      const unsigned tag = (ld_relaxed(&gs->spare[tile.sm & 3]) + 1) & 0xFFF;
      const unsigned long long t0 = gtime();
      uint4 r4;
      do {
        __nanosleep(2048);
        if (gtime() - t0 > WATCHDOG_NS) __trap();
        r4 = ld_relaxed4(&gs->rslot[tile.sm & 3][lane * 4]);
      } while (!__all_sync(~0u, (((r4.x ^ tag) | (r4.y ^ tag) | (r4.z ^ tag) | (r4.w ^ tag)) & 0xFFF) == 0));
      if (tid == 0) st_relaxed(&gs->spare[tile.sm & 3], tag);
    }
    return;
  }

  if (wg == 3) {
    asm volatile("setmaxnreg.dec.sync.aligned.u32 24;");
    if (warp == 12) {
      mbar_wait(sb + BAR_PUB, 0);
      while (!__all_sync(~0u, ld_relaxed(gs->cnt[tm]) == 0x44444444u)) __nanosleep(A_SLEEP);
      if (FN) { fence_acquire(); fence_async_global(); }
      PROF(lane == 0, 7);
      mbar_wait(sb + BAR_GATE, 0);
      uint32_t slots = (uint32_t)OA_SLOTS, deps = 0xA9877654u;
#pragma unroll 1
      for (int i = 0; i < 8; i++, deps >>= 4, slots >>= 4) {
        mbar_wait(sb + BAR_EMPTY + (deps & 15) * 8, i < 5);
        if (elect()) bulk_load(sb + OFF_RING + (slots & 15) * SLOT, gs->o[tm][i], SLOT, sb + BAR_LAND + i * 8);
        if (elect()) mbar_expect_tx(sb + BAR_LAND + i * 8, SLOT);
        PROF(lane == 0, 44 + i);
      }
      slots = (uint32_t)(OA_SLOTS >> 40);
      uint32_t ws = (uint32_t)(OW_SLOTS >> 40), todo = 0x44444444u ^ 0x44u << (tn & 6) * 4, seen = 0, st = 0;
      mbar_wait(sb + BAR_PUB + 8, 0);
#pragma unroll 1
      for (int i = 0; i < 6; i++, slots >>= 4, ws >>= 4) {
        const uint32_t need = DYN ? todo : todo & -todo;
        if (!(seen & need)) {
          while (!((seen = __shfl_sync(~0u, ld_relaxed(gs->cnt[16 + tm]), 0)) & need)) __nanosleep(B_SLEEP);
          if (FN) { fence_acquire(); fence_async_global(); }
        }
        const uint32_t bit = seen & need & -(seen & need), slab = 8 + ((31 - __clz(bit)) >> 2);
        todo ^= bit;
        if (DYN && elect()) asm volatile("st.shared.u8 [%0], %1;" ::"r"(sb + OFF_MISC + i), "r"(slab) : "memory");
        mbar_wait(sb + BAR_OEMPTY + st * 8, i < 5);
        if (elect()) bulk_load(sb + OFF_RING + (slots & 15) * SLOT, gs->o[tm][slab], SLOT, sb + BAR_LAND + i * 8);
        if (DYN && elect()) tma3d(sb + OFF_RING + (ws & 15) * SLOT, &p.wo, 0, slab * 64, tn * 2, sb + BAR_OFULL + st * 8);
        if (elect()) mbar_expect_tx(sb + BAR_LAND + i * 8, SLOT);
        if (DYN && elect()) mbar_expect_tx(sb + BAR_OFULL + st * 8, SLOT);
        PROF(lane == 0, 54 + i);
        st = st == 4 ? 0 : st + 1;
      }
    } else if (warp == 13) {
#pragma unroll 1
      for (int g = E7 ? 4 : PRE; g < 32; g++) {
        const bool reuse = (g >> 2) == 4;
        const uint32_t s = g & 3, full = sb + BAR_FULL + (g & 7) * 8, c0 = tn * 64 + (g & 16) * 32, c1 = (g < 16 ? g : g - 4 & 15) * 64;
        if (!E7 && g < 4) while ((int)(clock32() - t_start) < g * ST1) {}
        mbar_wait(sb + BAR_EMPTY + (g + 4 & 7) * 8, (g + 4 >> 3 & 1) ^ 1);
        if (!reuse && elect()) tma2d(sb + OFF_RING + s * SLOT, &p.x, c1, tm * 128, full);
        if (elect()) tma3d(sb + OFF_W1 + s * WQKV_BYTES, &p.w, c0, c1, 0, full);
        if (elect()) mbar_expect_tx(full, reuse ? WQKV_BYTES : SLOT + WQKV_BYTES);
        PROF(lane == 0, 64 + g);
        const uint32_t i = g - RT_G0;
        if (i < 4 && elect()) {
          mbar_expect_tx(sb + BAR_RT + i * 8, i ? 8192 : 8192 + 4096);
          tma2d(sb + OFF_PK + i * 8192 + (i == 3) * 1024, &p.xr, ((i + RT_ROT) & 3) * 256, cta * 16, sb + BAR_RT + i * 8);
          if (i == 0) { bulk_load(sb + OFF_KVB, w_r, 2048, sb + BAR_RT); bulk_load(sb + OFF_KVB + 2048, gate_w, 2048, sb + BAR_RT); }
        }
        const uint32_t c = g - MOD_START;
        if (c == MOD_BUFS) mbar_wait(sb + BAR_RTD, 0);
        if (c < MOD_BUFS0 && mu < MOD_CTAS && elect()) {
          PROF(true, 192 + c);
          const uint32_t mb = c < MOD_BUFS ? c + 2 : c - MOD_BUFS, mfull = sb + BAR_MFULL + mb * 8, mdst = sb + OFF_V + mb * MOD_STEP;
          mbar_expect_tx(mfull, c ? 8192 : 8192 + 2048);
          tma3d(mdst, &p.gate, mu * 32, c * 16, 0, mfull); tma3d(mdst + 4096, &p.up, mu * 32, c * 16, 0, mfull);
        }
        const uint32_t pc = g - PF_MOD;
        if (pc < 16 && elect()) bulk_prefetch((cta & 64 ? w_up : w_gate) + (size_t)(pc * 64 + (cta & 63)) * F_, F_ * 2);
      }
      mbar_arrive_warp(sb + BAR_GATE);
      const uint32_t lowb = (1u << (tn & 6) * 4) - 1;
      uint64_t slabs = (uint64_t)((0xFEDCBA98u & lowb) | (0xFEDCBAu & ~lowb)) << 40 | (uint64_t)(8 + (tn ^ 1)) << 36 | (uint64_t)(8 + tn) << 32 | 0x76543210u;
      uint64_t deps = 0x8CBA98CBA9876554ull, ws = OW_SLOTS;
      uint32_t full = sb + BAR_OFULL, ph = 1;
#pragma unroll 1
      for (int g = 0; g < (DYN ? 10 : 16); g++, slabs >>= 4, deps >>= 4, ws >>= 4) {
        mbar_wait(sb + BAR_EMPTY + ((uint32_t)deps & 15) * 8, ph);
        if (elect()) tma3d(sb + OFF_RING + ((uint32_t)ws & 15) * SLOT, &p.wo, 0, ((uint32_t)slabs & 15) * 64, tn * 2, full);
        if (elect()) mbar_expect_tx(full, SLOT);
        PROF(lane == 0, 96 + g);
        if (g >> 1 == OWN / 2 && lane < 4) mbar_arrive(full);
        if (DYN && g == PW && tm < 8 && elect())
          asm volatile("cp.async.bulk.prefetch.tensor.3d.L2.global [%0, {%1, %2, %3}];" ::"l"(&p.wo), "r"(0), "r"((8 + tm) * 64), "r"(tn * 2) : "memory");
        full += 8;
        if (full == sb + BAR_OFULL + 40) { full -= 40; ph ^= 1; }
      }
    } else if (warp == 14) {
      if (mu < MOD_CTAS) {
        uint32_t full = sb + BAR_MFULL + 16, dst = sb + OFF_MOD, ph = 0;
#pragma unroll 1
        for (int c = MOD_BUFS0; c < 24; c++) {
          mbar_wait(full + (BAR_MEMPTY - BAR_MFULL), ph);
          PROF(lane == 0, 192 + c);
          if (c < 16) {
            if (elect()) { tma3d(dst, &p.gate, mu * 32, c * 16, 0, full); tma3d(dst + 4096, &p.up, mu * 32, c * 16, 0, full); }
          } else if (elect()) tma3d(dst, &p.down, 0, mu * 32 + (c - 16) * 4, 0, full);
          if (elect()) mbar_expect_tx(full, 8192);
          if (PD && (uint32_t)(c + PD - 16) < 8 && elect()) bulk_prefetch(w_down + (size_t)(mu * 32 + (c + PD - 16) * 4) * D_, 8192);
          full += 8; dst += MOD_STEP;
          if (full == sb + BAR_MFULL + MOD_BUFS0 * 8) { full -= MOD_BUFS * 8; dst = sb + OFF_MOD; ph ^= 1; }
        }
      }
      if (elect()) {
      mbar_wait(sb + BAR_IDX, 0);
      const bool paired = PAIRED && ld_relaxed(&gs->block[cta ^ 1]) == (blockIdx.x ^ 1);
      if (paired) mbar_expect_tx(sb + BAR_PEER, SLOT);
      mbar_expect_tx(sb + BAR_X, 32768);
      mbar_wait(sb + BAR_OEMPTY + 3 * 8, 0);
      tma2d(sb + OFF_RES, &p.x, tn * 128, tm * 128, sb + BAR_X);
      mbar_wait(sb + BAR_OEMPTY + 4 * 8, 0);
      tma2d(sb + OFF_RES + RES_H, &p.x, tn * 128 + 64, tm * 128, sb + BAR_X);
      if (!paired) {
        mbar_wait(sb + BAR_OWN, 0);
        while (!(ld_relaxed(gs->cnt[16 + tm]) & 4u << (tn ^ 1) * 4)) __nanosleep(32);
        fence_acquire();
        fence_async_global();
        const uint32_t par = lds32(sb + OFF_MISC + 24);
        for (uint32_t ph = !mbar_test(sb + BAR_MFULL, 1), bad = 1; bad & 1; ph ^= 1) {
          fence_async_smem();
          mbar_expect_tx(sb + BAR_MFULL, SLOT);
          bulk_load(sb + OFF_PK, gs->o[tm][8 + (tn ^ 1)], SLOT, sb + BAR_MFULL);
          mbar_wait(sb + BAR_MFULL, ph);
          bad = 0;
#pragma unroll 1
          for (int i = 0; i < 512; i++) bad |= lds32(sb + OFF_PK + i * 32 + (i & 28)) ^ par;
        }
        mbar_arrive(sb + BAR_PEER);
      }
      }
    } else {
#pragma unroll 1
      for (int i = 3; i < 9; i++)
        if (elect()) asm volatile("prefetch.tensormap [%0];" ::"l"(&p.x + i) : "memory");
      mbar_wait_bounded(sb + BAR_DONE, 0);
    }
  } else if (wg == 2) {
    asm volatile("setmaxnreg.dec.sync.aligned.u32 40;");
    const int mw = warp & 3;
    if (mw == 0) {
      const unsigned tag = (ld_relaxed(&gs->rslot[tn][cta]) + 1) & 0xFFF;
#pragma unroll
      for (int i = 0; i < 2; i++)
        if (lane < 28) ((float4*)gs)[cta * 56 + i * 28 + lane] = make_float4(0.f, 0.f, 0.f, 0.f);
      if (lane == 29) gs->block[cta] = blockIdx.x;
      fence_release();
      nb_sync(NB_KEY, 160);
      const uint4 k4 = lds128(sb + OFF_MISC);
      if (lane < 8) st_relaxed(&gs->rslot[lane][cta], max(max(k4.x, k4.y), max(k4.z, k4.w)) | tag);
      if (lane < 16) st_relaxed(&gs->gslot[cta * 16 + lane], lds32(sb + OFF_G + lane * 4) | tag);
      PROF(lane == 0, 20);
      uint4 r4;
      do {
        __nanosleep(RT_SLEEP);
        r4 = ld_relaxed4(&gs->rslot[tn][lane * 4]);
      } while (!__all_sync(~0u, (((r4.x ^ tag) | (r4.y ^ tag) | (r4.z ^ tag) | (r4.w ^ tag)) & 0xFFF) == 0));
      const int c0 = 0xFFF0 - lane * 64;
      unsigned key = max(max((r4.x & 0xFFFF0000u) | (c0 + ((r4.x >> 12) & 15)), (r4.y & 0xFFFF0000u) | (c0 - 16 + ((r4.y >> 12) & 15))),
                         max((r4.z & 0xFFFF0000u) | (c0 - 32 + ((r4.z >> 12) & 15)), (r4.w & 0xFFFF0000u) | (c0 - 48 + ((r4.w >> 12) & 15))));
      key = __reduce_max_sync(~0u, key);
      if (elect()) {
        sts32(sb + OFF_MISC + 16, key);
        sts32(sb + OFF_MISC + 24, tag & 1);
        if (mu < MOD_CTAS) {
          const __nv_bfloat16* row = px + (size_t)(0xFFFF - (key & 0xFFFF)) * D_;
          bulk_load(sb + OFF_XSEL, row, 1024, sb + BAR_MFULL + 16);
          bulk_load(sb + OFF_XSEL + MOD_STEP, row + 512, 1024, sb + BAR_MFULL + 16);
        }
      }
      PROF(lane == 0, 21);
      do {
        r4 = ld_relaxed4(&gs->gslot[tm * 128 + lane * 4]);
      } while (!__all_sync(~0u, (((r4.x ^ tag) | (r4.y ^ tag) | (r4.z ^ tag) | (r4.w ^ tag)) & 0xFFF) == 0));
      sts128(sb + OFF_G + lane * 16, r4.x & 0xFFFF0000u, r4.y & 0xFFFF0000u, r4.z & 0xFFFF0000u, r4.w & 0xFFFF0000u);
      fence_acquire();
      __syncwarp();
    }
    PROF(tid == 256, 22);
    if (mu >= MOD_CTAS) {
      mbar_arrive_warp(sb + BAR_IDX);
    } else {
      const uint32_t wp = sb + OFF_V + (mw >> 1) * 4096 + (mw & 1) * 512 + lane * 16;
      uint32_t mp = sb + OFF_XSEL + (mw & 1) * 64 + (lane >> 2) * 8, mc = 128;
      float acc[8] = {0.f, 0.f, 0.f, 0.f, 0.f, 0.f, 0.f, 0.f};
      uint32_t b = 2, ph = 0;
#pragma unroll 1
      for (int c = 0; c < 24; c++) {
        if (MOD_SLEEP && c >= MOD_S0) __nanosleep(MOD_SLEEP);
        mbar_wait(sb + BAR_MFULL + b * 8, ph);
        PROF_C(tid == 256, 216 + c);
        const uint32_t a = wp + b * MOD_STEP;
        const uint2 m = lds64(mp);
        const uint4 w0 = lds128(a), w1 = lds128(a + 1024), w2 = lds128(a + 2048), w3 = lds128(a + 3072);
        mp += c == 7 ? MOD_STEP - 1024 + 128 : mc;
        const uint32_t m0 = dup_lo(m.x), m1 = dup_hi(m.x), m2 = dup_lo(m.y), m3 = dup_hi(m.y);
        uint4 q = make_uint4(mul_bf2(w0.x, m0), mul_bf2(w0.y, m0), mul_bf2(w0.z, m0), mul_bf2(w0.w, m0));
        q = make_uint4(fma_bf2(w1.x, m1, q.x), fma_bf2(w1.y, m1, q.y), fma_bf2(w1.z, m1, q.z), fma_bf2(w1.w, m1, q.w));
        q = make_uint4(fma_bf2(w2.x, m2, q.x), fma_bf2(w2.y, m2, q.y), fma_bf2(w2.z, m2, q.z), fma_bf2(w2.w, m2, q.w));
        mbar_arrive_warp(sb + BAR_MEMPTY + b * 8 + (w3.x & zero));
        q = make_uint4(fma_bf2(w3.x, m3, q.x), fma_bf2(w3.y, m3, q.y), fma_bf2(w3.z, m3, q.z), fma_bf2(w3.w, m3, q.w));
        if (++b == 5) b = c < 3 ? 0 : 2;
        if (b == 2) ph ^= 1;
        acc[0] += bf_lo(q.x); acc[1] += bf_hi(q.x); acc[2] += bf_lo(q.y); acc[3] += bf_hi(q.y);
        acc[4] += bf_lo(q.z); acc[5] += bf_hi(q.z); acc[6] += bf_lo(q.w); acc[7] += bf_hi(q.w);
        if (c == 15) {
          const uint32_t ft = fresh_tid(), fl = ft & 31;
          sts32(sb + OFF_PART + (ft & 96) * 4 + ((ft & 3) * 8 + (fl >> 2)) * 4, __float_as_uint(butterfly8(acc, fl, 4)));
          nb_sync(NB_MODW, 128);
          const float* part = (const float*)(smem + OFF_PART) + fl;
          const float gp = bf_round(part[0] + part[32]), up = bf_round(part[64] + part[96]);
          *(__nv_bfloat16*)(smem + OFF_PART + 512 + fl * 2) = __float2bfloat16_rn(bf_round(gp * sigmoidf_(gp)) * up);
          __syncwarp();
          mp = sb + OFF_PART + 512; mc = 8;
#pragma unroll
          for (int i = 0; i < 8; i++) acc[i] = 0.f;
          PROF(lane == 0 && mw == 0, 23);
        }
      }
      float4* yacc = gs->y[tn & 1][0] + (fresh_tid() & 127);
      red_add4(yacc, acc[0], acc[1], acc[2], 1.f);
      red_add4(yacc + 128, acc[3], acc[4], acc[5], 1.f);
      red_add4(yacc + 256, acc[6], acc[7], 0.f, 1.f);
      PROF(lane == 0 && mw == 0, 25);
    }
    mbar_wait(sb + BAR_GATE, 0);
    mbar_wait(sb + BAR_IDX, 0);
    verify_tiles<0>(sb, gs, tm, tn, mw, lane);
    const unsigned key = lds32(sb + OFF_MISC + 16);
    const int sel = 0xFFFF - (int)(key & 0xFFFF) - tm * 128;
    if (mw == 0 && sel >= 0 && sel < 128) {
      const unsigned k16 = key >> 16;
      const float rs = bf_round(sigmoidf_(__uint_as_float(((k16 & 0x8000u) ? (k16 & 0x7FFFu) : (~k16 & 0xFFFFu)) << 16)));
      float v[12];
      const float4* yp = gs->y[lane >> 4][0] + tn * 16 + (lane & 15);
      for (;;) {
#pragma unroll
        for (int i = 0; i < 3; i++) {
          const float4 u = ld_relaxed_f4(yp + i * 128);
          v[4 * i] = u.x; v[4 * i + 1] = u.y; v[4 * i + 2] = u.z; v[4 * i + 3] = u.w;
        }
        const float n = v[3] + v[7] + v[11];
        if (__all_sync(~0u, n + __shfl_xor_sync(~0u, n, 16) == 3.f * MOD_CTAS)) break;
        __nanosleep(Y_SLEEP);
      }
#pragma unroll
      for (int i = 0; i < 10; i++) v[i] = bf_round(bf_round(v[i] + __shfl_xor_sync(~0u, v[i], 16)) * rs);
      PROF(lane == 0, 24);
      mbar_wait(sb + BAR_X, 0);
      if (lane < 16) {
        uint4* xp = (uint4*)(smem + OFF_RES + (lane >> 3) * RES_H + sel * 128 + (((lane ^ sel) & 7) << 4));
        const uint4 xv = *xp;
        *xp = make_uint4(pack2(bf_lo(xv.x) + v[0], bf_hi(xv.x) + v[1]), pack2(bf_lo(xv.y) + v[2], bf_hi(xv.y) + v[4]),
                         pack2(bf_lo(xv.z) + v[5], bf_hi(xv.z) + v[6]), pack2(bf_lo(xv.w) + v[8], bf_hi(xv.w) + v[9]));
      }
      __syncwarp();
      mbar_arrive_warp(sb + BAR_Y);
    }
  } else {
    if (E7 && warp == 7) {
#pragma unroll
      for (int g = PRE; g < 4; g++) {
        while ((int)(clock32() - t_start) < ST0 + (g - PRE) * ST1) {}
        if (elect()) tma2d(sb + OFF_RING + g * SLOT, &p.x, g * 64, tm * 128, sb + BAR_FULL + g * 8);
        if (elect()) tma3d(sb + OFF_W1 + g * WQKV_BYTES, &p.w, tn * 64, g * 64, 0, sb + BAR_FULL + g * 8);
        if (elect()) mbar_expect_tx(sb + BAR_FULL + g * 8, SLOT + WQKV_BYTES);
        PROF(lane == 0, 64 + g);
        const int i = g - RT_G0;
        if (i >= 0 && elect()) {
          mbar_expect_tx(sb + BAR_RT + i * 8, i ? 8192 : 8192 + 4096);
          tma2d(sb + OFF_PK + i * 8192, &p.xr, ((i + RT_ROT) & 3) * 256, cta * 16, sb + BAR_RT + i * 8);
          if (i == 0) { bulk_load(sb + OFF_KVB, w_r, 2048, sb + BAR_RT); bulk_load(sb + OFF_KVB + 2048, gate_w, 2048, sb + BAR_RT); }
        }
      }
    }
    asm volatile("setmaxnreg.inc.sync.aligned.u32 224;");
    const int w = warp & 3, wt = tid & 127;
    const int nb_self = NB_WG0 + wg;
    const uint64_t da0 = mkdesc(sb + OFF_RING, 16, 1024, 1), db0 = mkdesc(sb + OFF_RING, 8192, 1024, 1);

    if (wg == 1) {
      sts128(sb + OFF_ONES - (w >> 1) * 9216 + (w & 1) * 512 + lane * 16, 0x3F803F80u, 0x3F803F80u, 0x3F803F80u, 0x3F803F80u);
      sts32(sb + OFF_MISC + 20, 0x3FB8AA3Bu);
      fence_async_smem();
      float s[8] = {0.f, 0.f, 0.f, 0.f, 0.f, 0.f, 0.f, 0.f};
      uint32_t mask = 0xffff0000u;
#pragma unroll 1
      for (int i = 0; i < 4; i++) {
        const uint32_t u = (i + RT_ROT) & 3;
        mbar_wait(sb + BAR_RT + i * 8, 0);
        const uint4 wr = lds128(sb + OFF_KVB + u * 512 + lane * 16), gw = lds128(sb + OFF_KVB + 2048 + u * 512 + lane * 16);
        uint4 xv[4];
#pragma unroll
        for (int r = 0; r < 4; r++) xv[r] = lds128(sb + OFF_PK + i * 8192 + (i == 3) * 1024 + (w * 4 + r) * 512 + lane * 16);
        const float wf[16] = {bf_lo(wr.x), bf_hi(wr.x), bf_lo(wr.y), bf_hi(wr.y), bf_lo(wr.z), bf_hi(wr.z), bf_lo(wr.w), bf_hi(wr.w),
                              bf_lo(gw.x), bf_hi(gw.x), bf_lo(gw.y), bf_hi(gw.y), bf_lo(gw.z), bf_hi(gw.z), bf_lo(gw.w), bf_hi(gw.w)};
#pragma unroll
        for (int r = 0; r < 4; r++) {
          const uint4 xq = xv[r];
          const float xf[8] = {bf_lo(xq.x), __uint_as_float(xq.x & mask), bf_lo(xq.y), bf_hi(xq.y), bf_lo(xq.z), bf_hi(xq.z), bf_lo(xq.w), bf_hi(xq.w)};
#pragma unroll
          for (int j = 0; j < 8; j++) { s[2 * r] = fmaf(xf[j ^ 1], wf[j ^ 1], s[2 * r]); s[2 * r + 1] = fmaf(xf[j ^ 1], wf[8 + (j ^ 1)], s[2 * r + 1]); }
          mask = ((__float_as_uint(s[2 * r]) | __float_as_uint(s[2 * r + 1])) & zero) | 0xffff0000u;
        }
      }
      mbar_arrive_warp(sb + BAR_RTD + (__float_as_uint(s[6]) & zero));
      float v = butterfly8(s, lane, 1);
      PROF_C(wt == 0 && v != 12345.f, 19);
      v += __shfl_xor_sync(~0u, v, 8);
      v = bf_round(v + __shfl_xor_sync(~0u, v, 16));
      const unsigned rb = __float_as_uint(v) >> 16, row = w * 4 + ((lane & 7) >> 1);
      unsigned key = (lane & 1) ? 0u : ((((rb & 0x8000u) ? (~rb & 0xFFFFu) : (rb | 0x8000u)) << 16) | ((15 - row) << 12));
      key = __reduce_max_sync(~0u, key);
      if (lane == 0) sts32(sb + OFF_MISC + w * 4, key);
      if (lane < 8 && (lane & 1)) sts32(sb + OFF_G + row * 4, __float_as_uint(bf_round(sigmoidf_(v))));
      nb_arrive(NB_KEY, 160);
      nb_sync(NB_ORDER_12, 256);
    }
    uint4* const kvacc = &gs->kv[wg][tn][0][wt];
    float aq[64];
    uint32_t su[9];
    float pq[64], ak[64], av[64];
    auto proj = [&](float (&d)[64], int j, uint32_t s, int sc) {
#pragma unroll
      for (int kk = 0; kk < 4; kk++)
        mma128<1, 0>(d, da0 + ((OFF_W1 >> 4) + s * (WQKV_BYTES >> 4) + j * 512 + kk * 128), da0 + (s * (SLOT >> 4) + kk * 2), kk ? 1 : sc);
    };
    PROF_C(wt == 0, 1 + wg * 8);
#pragma unroll 1
    for (int g = 0; g < 15; g++) {
      mbar_wait(sb + BAR_FULL + (g & 7) * 8, g >> 3);
      if (g == 0) PROF_C(wt == 0, 2 + wg * 8);
      wg_fence();
      proj(ak, 1, g & 3, g);
      wg_commit();
      wg_wait<1>();
      if (g) mbar_arrive_warp(sb + BAR_EMPTY + (g - 1 & 7) * 8);
      if (g == 14) break;
      if (SP && g == 0) mbar_wait(sb + BAR_SP, 0);
      wg_fence();
      proj(av, 2, g & 3, g);
      proj(pq, 0, g & 3, g);
      wg_commit();
    }
    auto finish = [&](auto reorder) {
      constexpr int re = decltype(reorder)::value, vk = re ? VK1 : VK, mm = re ? MM1 : MM, kl = re ? KL1 : KL, qw = re ? QW1 : 0;
      float c[36];
      uint32_t pk[8][4];
      if (!re) {
        wg_fence();
        proj(av, 2, 2, 1);
        proj(pq, 0, 2, 1);
        wg_commit();
      }
      mbar_wait(sb + BAR_FULL + 7 * 8, 1);
      wg_fence();
      proj(ak, 1, 3, 1);
      wg_commit();
      if (!re) {
        wg_wait<1>();
        mbar_arrive_warp(sb + BAR_EMPTY + 6 * 8);
      }
      wg_fence();
      if (re) proj(av, 2, 2, 1);
      proj(av, 2, 3, 1);
      wg_commit();
      if (!re) {
        proj(pq, 0, 3, 1);
        wg_commit();
        if (wg == 0) nb_arrive(NB_ORDER_12, 256);
      }
      mbar_wait(sb + BAR_IDX, 0);
      if (wg == 1) nb_sync(NB_STG, 256);
      wg_wait<2 - re>();
      pin(ak);
      PROF_C(wt == 0, 3 + wg * 8);
      const uint32_t va = sb + OFF_V + (w * 16 + (lane & 15)) * 128;
      uint32_t lk[8];
#pragma unroll
      for (int u = 0; u < kl; u++) lk[u] = 0x3FB8AA3Bu;
#pragma unroll
      for (int u = 0; u < 8; u++) {
        if (re && (u == Q0 || u == Q0 + QS)) {
          wg_fence();
          proj(pq, 0, u == Q0 ? 3 - re : 3, 1);
          wg_commit();
          if (wg == 0 && u != Q0) nb_arrive(NB_ORDER_12, 256);
          if (qw) {
            wg_wait<7>();
            const uint32_t l = lds32(sb + OFF_MISC + 20);
#pragma unroll
            for (int t = u; t < u + kl && t < 8; t++) lk[t] = l;
          }
        }
#pragma unroll
        for (int i = 0; i < 4; i++) pk[u][i] = phi2(ak[8 * u + 2 * i], ak[8 * u + 2 * i + 1], __uint_as_float(lk[u]));
        if (u == vk) { wg_wait<re ? (vk >= Q0) + (vk >= Q0 + QS) : 1>(); pin(av); }
        if (u == M0 && re) { wg_wait<(M0 >= Q0 + QS)>(); mbar_arrive_warp(sb + BAR_EMPTY + 6 * 8); }
        if (u == mm) { wg_wait<0>(); mbar_arrive_warp(sb + BAR_EMPTY + 7 * 8); }
        const uint32_t z = mism(pk[u][0], pk[u][1], 0) | mism(pk[u][2], pk[u][3], 0);
#pragma unroll
        for (int t = u < vk ? 8 : (u - vk) * 8 / (8 - vk); t < (u - vk + 1) * 8 / (8 - vk); t++) {
          const float* v = &av[8 * t];
          stsm4(va + (t >> 2) * 9216 + ((((lane >> 4) + 2 * (t & 3)) ^ (lane & 7)) << 4) + (z & zero), pack2(v[0], v[1]), pack2(v[2], v[3]), pack2(v[4], v[5]), pack2(v[6], v[7]));
        }
        if (u + kl < 8) lk[u + kl] = lds32(sb + OFF_MISC + 20 + (u < vk ? z & zero : 0));
      }
      fence_async_smem();
      nb_sync(nb_self, 128);
      PROF_C(wt == 0, 8 + wg * 8);
      const uint64_t dv = mkdesc(sb + OFF_V, 16, 1024, 1);
      wg_fence();
#pragma unroll
      for (int kk = 0; kk < 8; kk++) mma_ktv(c, pk[kk], dv + ((kk >> 2) * 576 + (kk & 3) * 2), kk ? 1 : 0);
      wg_commit();
      if (wg == 1) nb_arrive(NB_ORDER_3O, 256);
      wg_wait<0>();
      pin(c); pin(pq);
#pragma unroll
      for (int i = 0; i < 64; i++) aq[i] = pq[i];
      PROF_C(wt == 0, 4 + wg * 8);
#pragma unroll
      for (int i = 0; i < 8; i++) {
        const int j = (i & 3) * 4 + (i >> 2) * 2;
        su[i] = w >= 2 ? pack2(c[16 + j], c[17 + j]) : pack2(c[j], c[j + 1]);
      }
      su[8] = pack2(c[32], c[34]);
#pragma unroll
      for (int u = 0; u < 3; u++)
        if (u < R0 || wg) red_add_bf(kvacc + u * 128, su[3 * u], su[3 * u + 1], su[3 * u + 2]);
    };
    if (TR == 2) {
      if (wg == 0) finish(std::integral_constant<int, 0>());
      else finish(std::integral_constant<int, 1>());
    } else finish(std::integral_constant<int, TR>());
    const uint32_t par = lds32(sb + OFF_MISC + 24);
    {
      const bool paired = PAIRED && ld_relaxed(&gs->block[cta ^ 1]) == (blockIdx.x ^ 1);
      uint4 kv[3];
      int tries = wg ? 0 : TRY_A;
      const uint8_t* gl = smem + OFF_MISC + 20;
      asm volatile("" : "+l"(gl));
      const uint32_t l2e = ld_generic(gl);
    auto stage_kv = [&]() {
      const uint32_t kb = sb + OFF_KVB + w * 256, ka = kb + (lane & 3) * KVB_N + (lane >> 2) * 16;
      sts128(ka, kv[0].x, kv[0].y, kv[0].z, kv[1].x);
      sts128(ka + 128, kv[1].y, kv[1].z, kv[2].x, kv[2].y);
      sts32(kb + 4 * KVB_N + lane * 4, dup_lo(kv[2].z));
      sts32(kb + 4 * KVB_N + 128 + lane * 4, dup_hi(kv[2].z));
      return __all_sync(~0u, (kv[0].w & kv[1].w & kv[2].w) == 0x41804180u && (kv[0].w | kv[1].w | kv[2].w) == 0x41804180u);
    };
      bool have = false;
      const uint32_t qa = sb + OFF_PK + ((lane >> 4) * 8 + (lane & 7)) * 128 + (((2 * w + ((lane >> 3) & 1)) ^ (lane & 7)) << 4);
      uint32_t lq[8];
#pragma unroll
      for (int u = 0; u < QA; u++) lq[u] = l2e;
#pragma unroll
      for (int u = 0; u < 8; u++) {
        uint32_t r[4];
        if (u == KF && wg) {
#pragma unroll
          for (int i = 0; i < 3; i++) kv[i] = ld_relaxed4(kvacc + i * 128);
        }
#pragma unroll
        for (int i = 0; i < 4; i++) r[i] = phi2(aq[8 * u + 2 * i], aq[8 * u + 2 * i + 1], __uint_as_float(lq[u]));
        stsm4t(qa + u * 2048, r[0], r[1], r[2], r[3]);
        if (u % RS == RS - 1 && u / RS + R0 < 3 && !wg) red_add_bf(kvacc + (u / RS + R0) * 128, su[3 * (u / RS + R0)], su[3 * (u / RS + R0) + 1], su[3 * (u / RS + R0) + 2]);
        if (u + QA < 8) lq[u + QA] = QD ? ld_generic(gl) : lds32(sb + OFF_MISC + 20);
        if (u == KU && wg) have = stage_kv();
      }
      PROF_C(wt == 0, 34 + wg * 2);
      if (NAP_A && !wg) __nanosleep(NAP_A);
      if (KU > 7 && KF < 8 && wg) have = stage_kv();
      for (; !have; tries++) {
        if (tries > RETRY)
          while (ld_relaxed((const unsigned*)&(kvacc - lane)[256 + 31].w) != 0x41804180u) __nanosleep(wg ? KV_SLEEP : KV_SLEEP_A);
#pragma unroll
        for (int i = 0; i < 3; i++) kv[i] = ld_relaxed4(kvacc + i * 128);
        have = stage_kv();
      }
      PROF_C(wt == 0, 5 + wg * 8);
      fence_async_smem();
      nb_sync(nb_self, 128);
      float o[2][2][20];
      const uint64_t dq = mkdesc(sb + OFF_PK, 16, 1024, 1), dz = mkdesc(sb + OFF_KVB, 128, KVB_N, 0);
      wg_fence();
#pragma unroll
      for (int m = 0; m < 2; m++) {
#pragma unroll
        for (int h = 0; h < 2; h++)
#pragma unroll
          for (int kk = 0; kk < 2; kk++) mma_qkvz(o[m][h], dq + (m * 512 + h * 4 + kk * 2), dz + (h * 32 + kk * 16), kk);
        wg_commit();
      }
      if (HOLD < 8 && HP == 0 && wg) nb_arrive(NB_HOLD, 256);
      if (EF == 3 && wg && elect()) red_add(gs->cnt[16 + tm], 1u << tn * 4);
      uint32_t tag[2][4];
#pragma unroll
      for (int i = 0; i < 8; i++) tag[i >> 2][i & 3] = (lane >> 3) == (i & 3) && ((lane ^ (lane >> 3)) & 1) == (i >> 2);
      uint32_t gr[8];
      const uint8_t* ga = smem + OFF_G + (w * 16 + (lane >> 2)) * 4;
      asm volatile("" : "+l"(ga));
#pragma unroll
      for (int i = 0; i < OA; i++) gr[i] = ld_generic(ga + (i >> 2) * 256 + (i & 1) * 32);
      const uint32_t oo = w * 1024 + (lane >> 2) * 64 + (((lane ^ (lane >> 3)) & 3) << 4);
      uint8_t* const og = (uint8_t*)gs->o[tm][wg * 8 + tn] + oo;
      uint32_t ob[8][4];
#pragma unroll
      for (int m = 0; m < 2; m++) {
        if (m == 0) wg_wait<1>(); else wg_wait<0>();
        pin(o[m][0]); pin(o[m][1]);
        if (EF == 2 - m && wg && elect()) red_add(gs->cnt[16 + tm], 1u << tn * 4);
        if (PB == 2 - m && wg) mbar_arrive_warp(sb + BAR_PUB + 8);
        if (m && !wg) nb_arrive(NB_STG, 256);
        if (HOLD < 8 && HP == 1 && m && wg) nb_arrive(NB_HOLD, 256);
        if (m && wg && paired && elect()) mbar_arrive_peer(peer_addr(sb + BAR_PA));
        if (m == 0) PROF_C(wt == 0, 6 + wg * 8);
#pragma unroll
        for (int u = 0; u < 4; u++) {
          const int h = u >> 1, i = u & 1;
          const float* on = o[m][h];
          const float sc = __uint_as_float(gr[m * 4 + u]) * rcp(on[16 + 2 * i] + 1e-6f);
          const uint32_t sc2 = pack2(sc, sc);
#pragma unroll
          for (int j = 0; j < 4; j++) {
            const uint32_t v = HS ? mul_bf2(pack2(on[4 * j + 2 * i], on[4 * j + 2 * i + 1]), sc2) : pack2(on[4 * j + 2 * i] * sc, on[4 * j + 2 * i + 1] * sc);
            asm("lop3.b32 %0, %1, %2, %3, 0xB8;" : "=r"(ob[m * 4 + u][j]) : "r"(v), "r"(tag[i][j]), "r"(par));
          }
          st_relaxed4(og + (h * 8192 + m * 4096 + i * 512), ob[m * 4 + u]);
          if (OWN1 == 2 && wg) sts128(sb + OFF_V + oo + (h * 8192 + m * 4096 + i * 512), ob[m * 4 + u][0], ob[m * 4 + u][1], ob[m * 4 + u][2], ob[m * 4 + u][3]);
          if (HOLD < 8 && HP == 10 + m * 4 + u && wg) nb_arrive(NB_HOLD, 256);
          const int n = m * 4 + u + OA;
          if (n < 8) gr[n] = ld_generic(ga + (n >> 2) * 256 + (n & 1) * 32);
        }
      }
      if ((!EF || !wg) && elect()) red_add(gs->cnt[wg * 16 + tm], 1u << tn * 4);
      if (!PB || !wg) mbar_arrive_warp(sb + BAR_PUB + wg * 8);
      if (HOLD < 8 && HP == 2 && wg) nb_arrive(NB_HOLD, 256);
      PROF(wt == 0, 17 + wg);
      if (wg) {
        auto to_peer = [&]() {
        if (paired) {
          const uint32_t pb = peer_addr(sb);
          mbar_wait(sb + BAR_PA, 0);
#pragma unroll
          for (int u = 0; u < 8; u++) st_async4(pb + OFF_PK + oo + ((u >> 1 & 1) * 8192 + (u >> 2) * 4096 + (u & 1) * 512), ob[u], pb + BAR_PEER);
        }
        };
        if (!OWN1) to_peer();
#pragma unroll
        for (int u = 0, z = 0; u < (OWN1 == 2 ? 0 : 8); u++) {
          sts128(sb + OFF_V + oo + ((u >> 1 & 1) * 8192 + (u >> 2) * 4096 + (u & 1) * 512) + z, ob[u][0], ob[u][1], ob[u][2], ob[u][3]);
          if (PO && u % PO == PO - 1 && u < 7) z = lds32(sb + OFF_ONES) & 16;
        }
        fence_async_smem();
        __syncwarp();
        mbar_arrive_warp(sb + BAR_OWN);
        if (HOLD < 8 && HP == 3) nb_arrive(NB_HOLD, 256);
        PROF(wt == 0, 15);
        if (OWN1) to_peer();
      }
    }
    if (wg == 1) {
      verify_tiles<1>(sb, gs, tm, tn, w, lane);
    } else {
      float acc[2][64];
      nb_sync(NB_ORDER_3O, 256);
      PROF_C(wt == 0, 26);
      uint32_t xr[2][8][4], q[2][2];
      const uint32_t ta = sb + OFF_RES + (uint32_t)(w * 16 + (lane & 15)) * 128;
      const uint64_t do0 = mkdesc(sb + OFF_RING, 16, 512, 2);
      uint64_t xs = OA_SLOTS, ws = OW_SLOTS;
#pragma unroll 1
      for (int g = 0; g < 13 - TL; g++, xs >>= 4, ws >>= 4) {
        const uint32_t r = g * 52 >> 8, s = g - r * 5;
        const uint64_t da = do0 + ((uint32_t)xs & 15) * (SLOT >> 4), db = db0 + ((uint32_t)ws & 15) * (SLOT >> 4);
        if (g == OWN) mbar_wait(sb + BAR_OWN, 0);
        if (g == PEER) { mbar_wait(sb + BAR_PEER, 0); fence_async_smem(); }
        if (g == HOLD) {
          if (HR) { wg_wait<0>(); mbar_arrive_warp(sb + BAR_OEMPTY + (HOLD + 4) % 5 * 8); }
          nb_sync(NB_HOLD, 256);
        }
        mbar_wait(sb + BAR_OFULL + s * 8, r & 1);
        wg_fence();
#pragma unroll
        for (int kk = 0; kk < 4; kk++)
#pragma unroll
          for (int m = 0; m < 2; m++) mma128<0, 1>(acc[m], da + (m * 256 + (kk >> 1) * 512 + (kk & 1) * 2), db + kk * 128, kk ? 1 : g);
        wg_commit();
        wg_wait<1>();
        if (g && (g != HOLD || !HR)) mbar_arrive_warp(sb + BAR_OEMPTY + (s ? s - 1 : 4) * 8);
      }
      mbar_wait(sb + BAR_X, 0);
      const int selw = ((0xFFFF - (int)(lds32(sb + OFF_MISC + 16) & 0xFFFF)) >> 4) - tm * 8 - w;
#pragma unroll
      for (int u = 0; u < 4; u++) {
        const int m = u >> 1, g = 13 - TL + u;
        const float g1 = 1.f - __uint_as_float(lds32(sb + OFF_G + (m * 64 + w * 16 + (u & 1) * 8 + (lane >> 2)) * 4));
        q[m][u & 1] = pack2(g1, g1);
#pragma unroll
        for (int j = 0; j < 4; j++) ldsm4(ta + (u & 1) * RES_H + m * 8192 + ((((lane >> 4) + 2 * j) ^ (lane & 7)) << 4), xr[m][(u & 1) * 4 + j]);
        if (u == 3) break;
        mbar_wait(sb + BAR_OFULL + g % 5 * 8, g / 5 & 1);
        wg_fence();
#pragma unroll
        for (int kk = 0; kk < 4; kk++)
#pragma unroll
          for (int mm = 0; mm < 2; mm++)
            mma128<0, 1>(acc[mm], do0 + ((OA_SLOTS >> g * 4 & 15) * (SLOT >> 4) + mm * 256 + (kk >> 1) * 512 + (kk & 1) * 2), db0 + ((OW_SLOTS >> g * 4 & 15) * (SLOT >> 4) + kk * 128), 1);
        wg_commit();
        wg_wait<1>();
        if (g <= 11) mbar_arrive_warp(sb + BAR_OEMPTY + (g + 4) % 5 * 8);
      }
#pragma unroll
      for (int m = 0; m < 2; m++) {
#pragma unroll
        for (int g = 16 - TL; g < 16; g++) {
          if (m == 0) { mbar_wait(sb + BAR_OFULL + g % 5 * 8, g / 5 & 1); wg_fence(); }
#pragma unroll
          for (int kk = 0; kk < 4; kk++)
            mma128<0, 1>(acc[m], do0 + ((OA_SLOTS >> g * 4 & 15) * (SLOT >> 4) + m * 256 + (kk >> 1) * 512 + (kk & 1) * 2), db0 + ((OW_SLOTS >> g * 4 & 15) * (SLOT >> 4) + kk * 128), 1);
        }
        wg_commit();
      }
      mbar_arrive_warp(sb + BAR_DONE);
      const uint32_t tb = sb + OFF_RES + w * 2048 + (lane >> 3) * 128 + (((lane ^ (lane >> 3)) & 7) << 4), tx = lane & 4 ? 64 : -64;
      uint8_t* const og = (uint8_t*)pout + (size_t)(tm * 128 + w * 16 + (lane >> 3)) * 2048 + tn * 256 + (lane & 7) * 16;
#pragma unroll
      for (int m = 0; m < 2; m++) {
        if (selw == 4 * m) {
          mbar_wait(sb + BAR_Y, 0);
#pragma unroll
          for (int j = 0; j < 8; j++) ldsm4(ta + (j >> 2) * RES_H + m * 8192 + ((((lane >> 4) + 2 * (j & 3)) ^ (lane & 7)) << 4), xr[m][j]);
        }
        if (m == 0) wg_wait<1>(); else wg_wait<0>();
        if (m) PROF(wt == 0, 31);
#pragma unroll
        for (int h = 0; h < 2; h++) {
#pragma unroll
          for (int j = 4 * h; j < 4 * h + 4; j++) {
            const float* v = &acc[m][8 * j];
            stsm4(ta + h * RES_H + m * 8192 + ((((lane >> 4) + 2 * (j & 3)) ^ (lane & 7)) << 4),
                  fma_bf2(xr[m][j][0], q[m][0], pack2(v[0], v[1])), fma_bf2(xr[m][j][1], q[m][1], pack2(v[2], v[3])),
                  fma_bf2(xr[m][j][2], q[m][0], pack2(v[4], v[5])), fma_bf2(xr[m][j][3], q[m][1], pack2(v[6], v[7])));
          }
          if (FS >> m & 1) {
            __syncwarp();
            uint4 t[4];
#pragma unroll
            for (int j = 0; j < 4; j++) t[j] = lds128(tb + h * RES_H + m * 8192 + j * 512 - (j & 1) * tx);
#pragma unroll
            for (int j = 0; j < 4; j++) *(uint4*)(og + (m * 64 + j * 4) * 2048 + h * 128) = t[j];
          } else {
            fence_async_smem();
            __syncwarp();
            if (elect()) tma2d_store(&p.out, sb + OFF_RES + h * RES_H + m * 8192 + w * 2048, tn * 128 + h * 64, tm * 128 + m * 64 + w * 16);
          }
          if (FS != 3 && m && h && elect()) { bulk_commit(); asm volatile("cp.async.bulk.wait_group.read 0;" ::: "memory"); }
        }
        if (!m) PROF(wt == 0, 33);
      }
      PROF(wt == 0, 32);
    }
  }
}

typedef CUresult (*EncodeFn)(CUtensorMap*, CUtensorMapDataType, cuuint32_t, void*, const cuuint64_t*, const cuuint64_t*, const cuuint32_t*,
                             const cuuint32_t*, CUtensorMapInterleave, CUtensorMapSwizzle, CUtensorMapL2promotion, CUtensorMapFloatOOBfill);

void encode(EncodeFn fn, CUtensorMap* m, const void* ptr, int rank, const cuuint64_t* dims, const cuuint64_t* strides, const cuuint32_t* box,
            CUtensorMapSwizzle sw, CUtensorMapDataType dt = CU_TENSOR_MAP_DATA_TYPE_BFLOAT16) {
  const cuuint32_t es[3] = {1, 1, 1};
  fn(m, dt, rank, const_cast<void*>(ptr), dims, strides, box, es, CU_TENSOR_MAP_INTERLEAVE_NONE, sw,
     CU_TENSOR_MAP_L2_PROMOTION_L2_128B, CU_TENSOR_MAP_FLOAT_OOB_FILL_NONE);
}

}

extern "C" void kernel_launch(void* const* d_in, const int* in_sizes, int n_in, void* d_out, int out_size) {
  (void)in_sizes; (void)n_in; (void)out_size;
  EncodeFn fn = nullptr;
  cudaDriverEntryPointQueryResult qr;
  cudaGetDriverEntryPoint("cuTensorMapEncodeTiled", (void**)&fn, cudaEnableDefault, &qr);

  Params p;
  {
    const cuuint64_t dims[2] = {D_, S_}, str[1] = {D_ * 2};
    const cuuint32_t box[2] = {64, 128}, box_st[2] = {64, 16}, box_r[2] = {256, 16};
    encode(fn, &p.xr, d_in[0], 2, dims, str, box_r, CU_TENSOR_MAP_SWIZZLE_NONE);
    encode(fn, &p.x, d_in[0], 2, dims, str, box, CU_TENSOR_MAP_SWIZZLE_128B);
    encode(fn, &p.out, d_out, 2, dims, str, box_st, CU_TENSOR_MAP_SWIZZLE_128B);
  }
  {
    const cuuint64_t dims[3] = {D_, D_, 3}, str[2] = {3 * D_ * 2, D_ * 2};
    const cuuint32_t box[3] = {64, 64, 3};
    encode(fn, &p.w, d_in[1], 3, dims, str, box, CU_TENSOR_MAP_SWIZZLE_128B);
    const cuuint32_t box1[3] = {64, 64, 1};
    encode(fn, &p.w1, d_in[1], 3, dims, str, box1, CU_TENSOR_MAP_SWIZZLE_128B);
  }
  {
    const cuuint64_t dims[3] = {64, D_, D_ / 64}, str[2] = {D_ * 2, 128};
    const cuuint32_t box[3] = {64, 64, 2};
    encode(fn, &p.wo, d_in[2], 3, dims, str, box, CU_TENSOR_MAP_SWIZZLE_128B);
  }
  {
    const cuuint64_t dims[3] = {F_, D_ / 4, 4}, str[2] = {F_ * 8, F_ * 2};
    const cuuint32_t box[3] = {32, 16, 4};
    encode(fn, &p.gate, d_in[5], 3, dims, str, box, CU_TENSOR_MAP_SWIZZLE_NONE);
    encode(fn, &p.up, d_in[6], 3, dims, str, box, CU_TENSOR_MAP_SWIZZLE_NONE);
  }
  {
    const cuuint64_t dims[3] = {D_ / 4, F_, 2}, str[2] = {D_ * 2, D_};
    const cuuint32_t box[3] = {256, 4, 2};
    encode(fn, &p.down, d_in[7], 3, dims, str, box, CU_TENSOR_MAP_SWIZZLE_NONE, CU_TENSOR_MAP_DATA_TYPE_UINT32);
  }
  void* gs = nullptr;
  cudaGetSymbolAddress(&gs, g_scratch);
  typedef const __nv_bfloat16* bp;
  int dev = 0, sms = 0;
  cudaGetDevice(&dev);
  cudaDeviceGetAttribute(&sms, cudaDevAttrMultiProcessorCount, dev);
  const bool by_sm = BYSM && sms == NGRID;
  const auto kernel = by_sm ? fused_kernel<true> : fused_kernel<false>;
  cudaFuncSetAttribute(kernel, cudaFuncAttributeMaxDynamicSharedMemorySize, SMEM_BYTES);
  kernel<<<by_sm ? NGRID : NCTA, NTHREADS, SMEM_BYTES, cudaStreamPerThread>>>((bp)d_in[0], (Scratch*)gs, (bp)d_in[5], (bp)d_in[6], (bp)d_in[4], (bp)d_in[8], (bp)d_in[7], (__nv_bfloat16*)d_out, p);
}
```

```cpp
#include <cuda_runtime.h>
#include <cuda.h>
#include <cuda_bf16.h>
#include <stdint.h>
#include <stddef.h>
#include <type_traits>

namespace {

constexpr int S_ = 2048, D_ = 1024, F_ = 3584;
constexpr int NCTA = 128, NGRID = 132, NTHREADS = 512;
#define NOMOD 0
constexpr int MOD_CTAS = NOMOD ? 0 : F_ / 32;

#define PRE 2
#define ST1 700
#define RT_G0 2
#define RT_ROT 1
#define RT_SLEEP 500
#define PF_MOD 7
#define MOD_START 9
#define MM 3
#define PO 2
#define A_SLEEP 128
#define KU 99
#define HS 1
#define HOLD 5
#define OWN1 2
#define KF 6
#define QA 3
#define R0 1
#define OA 3
#define Y_SLEEP 200
#define TRY_A 9
#define VK 1
#define TR 2
#define Q0 0
#define QS 2
#define QW1 0
#define VK1 2
#define MM1 5
#define KL1 2
#define M0 3
#define HP 1
#define FS 0
#define SP 1
#define E7 1
#define ST0 1600
#define QE 1
#define KL 3
#define RS 2
#define RETRY 1
#define KV_SLEEP_A 64
#define KV_SLEEP 50
#define TL 3
#define EF 3
#define PB 1
#define B_SLEEP 32
#define HR 0
#define PAIRED 1
#define BYSM 1

constexpr uint32_t SLOT = 16384, WQKV_BYTES = 24576;
constexpr int MOD_BUFS = 3, MOD_BUFS0 = MOD_BUFS + 2;
static_assert(MOD_START + MOD_BUFS0 <= 16, "first FFN round is requested during W1");
constexpr uint32_t OFF_RING = 0, OFF_W1 = 4 * SLOT;
constexpr uint64_t OA_SLOTS = 0x0AB210AB21098210ull, OW_SLOTS = 0x4376543765437654ull;
constexpr uint32_t OFF_RES = OFF_RING + 8 * SLOT, RES_H = SLOT;
constexpr uint32_t OFF_PK = 10 * SLOT;
constexpr uint32_t OFF_V = 11 * SLOT;
constexpr uint32_t OFF_ONES = OFF_V + 9216 + 8192;
constexpr uint32_t MOD_STEP = 9216, OFF_MOD = OFF_V + 2 * MOD_STEP;
constexpr uint32_t OFF_XSEL = OFF_MOD + 8192;
constexpr uint32_t OFF_KVB = OFF_MOD + 2 * MOD_STEP + 8192;
constexpr uint32_t KVB_N = 1056;
constexpr uint32_t OFF_G = OFF_KVB + 4 * KVB_N + 1024;
constexpr uint32_t OFF_PART = OFF_G + 512;
constexpr uint32_t OFF_MISC = OFF_PART + 576;
constexpr uint32_t OFF_BAR = OFF_MISC + 32;
constexpr uint32_t SMEM_BYTES = OFF_BAR + 488;
constexpr uint32_t BAR_FULL = OFF_BAR, BAR_Y = BAR_FULL + 64, BAR_X = BAR_Y + 8, BAR_PEER = BAR_X + 8, BAR_GATE = BAR_PEER + 8, BAR_RT = BAR_GATE + 8,
                   BAR_FIX = BAR_RT,
                   BAR_MFULL = BAR_FIX + 64, BAR_LAND = BAR_FULL,
                   BAR_EMPTY = OFF_BAR + 28 * 8, BAR_OEMPTY = BAR_EMPTY + 64, BAR_RTD = BAR_OEMPTY + 40, BAR_DONE = BAR_RTD + 8,
                   BAR_OWN = BAR_DONE + 8, BAR_PA = BAR_OWN + 8, BAR_PUB = BAR_PA + 8, BAR_MEMPTY = BAR_PUB + 16,
                   BAR_IDX = BAR_MEMPTY + 8,
                   BAR_OFULL = OFF_BAR + 52 * 8, BAR_SP = OFF_BAR + 60 * 8;
static_assert(BAR_MFULL + MOD_BUFS0 * 8 <= BAR_EMPTY && BAR_MEMPTY + MOD_BUFS0 * 8 == BAR_OFULL, "barrier groups");
static_assert(SMEM_BYTES <= 232448, "smem");
static_assert(TL == 3 && PRE == 2, "schedule");

constexpr int NB_WG0 = 1, NB_ORDER_12 = 3, NB_ORDER_3O = 4, NB_STG = 5, NB_MODW = 6, NB_KEY = 7, NB_HOLD = 8;

struct Scratch {
  uint4 kv[2][8][3][128];
  float4 y[2][3][128];
  unsigned cnt[32][32];
  unsigned gslot[S_];
  unsigned rslot[8][NCTA];
  unsigned spare[128];
  unsigned block[NCTA];
  uint4 o[16][16][1024];
};
static_assert(offsetof(Scratch, gslot) == NCTA * 56 * 16, "clear size");
__device__ __align__(1024) Scratch g_scratch;

#define PROF(cond, i) do {} while (0)
#define PROF_C(cond, i) do {} while (0)

__device__ __forceinline__ void mbar_init(uint32_t bar, int cnt) { asm volatile("mbarrier.init.shared::cta.b64 [%0], %1;" ::"r"(bar), "r"(cnt)); }
__device__ __forceinline__ void mbar_expect_tx(uint32_t bar, uint32_t bytes) { asm volatile("mbarrier.arrive.expect_tx.shared::cta.b64 _, [%0], %1;" ::"r"(bar), "r"(bytes) : "memory"); }
__device__ __forceinline__ void mbar_arrive(uint32_t bar) { asm volatile("mbarrier.arrive.shared::cta.b64 _, [%0];" ::"r"(bar) : "memory"); }
__device__ __forceinline__ uint32_t peer_addr(uint32_t a) {
  uint32_t r;
  asm volatile("{\n.reg .u32 c;\nmov.u32 c, %%cluster_ctarank;\nxor.b32 c, c, 1;\nmapa.shared::cluster.u32 %0, %1, c;\n}" : "=r"(r) : "r"(a));
  return r;
}
__device__ __forceinline__ void mbar_arrive_peer(uint32_t bar) { asm volatile("mbarrier.arrive.shared::cluster.b64 _, [%0];" ::"r"(bar) : "memory"); }
__device__ __forceinline__ uint32_t mism(uint32_t a, uint32_t b, uint32_t p) {
  uint32_t r; asm("lop3.b32 %0, %1, %2, %3, 0x7E;" : "=r"(r) : "r"(a), "r"(b), "r"(p)); return r;
}
__device__ __forceinline__ bool elect() {
  uint32_t r;
  asm volatile("{\n.reg .pred p;\nelect.sync _|p, 0xffffffff;\nselp.u32 %0, 1, 0, p;\n}" : "=r"(r));
  return r;
}
__device__ __forceinline__ uint32_t fresh_tid() { uint32_t r; asm volatile("mov.u32 %0, %%tid.x;" : "=r"(r)); return r; }
__device__ __forceinline__ void mbar_arrive_warp(uint32_t bar) {
  asm volatile("{\n.reg .pred p;\nelect.sync _|p, 0xffffffff;\n@p mbarrier.arrive.shared::cta.b64 _, [%0];\n}" ::"r"(bar) : "memory");
}
__device__ __forceinline__ void mbar_wait(uint32_t bar, uint32_t parity) {
  asm volatile("{\n.reg .pred p;\nWAIT_L:\nmbarrier.try_wait.parity.shared::cta.b64 p, [%0], %1;\n@p bra DONE_L;\nbra WAIT_L;\nDONE_L:\n}"
               ::"r"(bar), "r"(parity) : "memory");
}
__device__ __forceinline__ uint32_t mbar_try(uint32_t bar, uint32_t parity) {
  uint32_t ok;
  asm volatile("{\n.reg .pred p;\nmbarrier.try_wait.parity.shared::cta.b64 p, [%1], %2;\nselp.u32 %0, 1, 0, p;\n}" : "=r"(ok) : "r"(bar), "r"(parity) : "memory");
  return ok;
}
__device__ __forceinline__ uint32_t mbar_test(uint32_t bar, uint32_t parity) {
  uint32_t ok;
  asm volatile("{\n.reg .pred p;\nmbarrier.test_wait.parity.shared::cta.b64 p, [%1], %2;\nselp.u32 %0, 1, 0, p;\n}" : "=r"(ok) : "r"(bar), "r"(parity) : "memory");
  return ok;
}
constexpr unsigned long long WATCHDOG_NS = 2000000000ull;
__device__ __forceinline__ unsigned long long gtime() { unsigned long long t; asm volatile("mov.u64 %0, %%globaltimer;" : "=l"(t)); return t; }
__device__ __forceinline__ uint32_t clock32() { uint32_t t; asm volatile("mov.u32 %0, %%clock;" : "=r"(t)); return t; }
__device__ __forceinline__ void mbar_wait_bounded(uint32_t bar, uint32_t parity) {
  unsigned long long t0 = 0;
  for (;;) {
    uint32_t ok;
    asm volatile("{\n.reg .pred p;\nmbarrier.try_wait.parity.shared::cta.b64 p, [%1], %2;\nselp.u32 %0, 1, 0, p;\n}" : "=r"(ok) : "r"(bar), "r"(parity) : "memory");
    if (ok) break;
    const unsigned long long t1 = gtime();
    if (t0 == 0) t0 = t1;
    if (t1 - t0 > WATCHDOG_NS) __trap();
  }
}
__device__ __forceinline__ void tma2d(uint32_t dst, const CUtensorMap* m, int c0, int c1, uint32_t bar) {
  asm volatile("cp.async.bulk.tensor.2d.shared::cluster.global.mbarrier::complete_tx::bytes [%0], [%1, {%3, %4}], [%2];"
               ::"r"(dst), "l"(m), "r"(bar), "r"(c0), "r"(c1) : "memory");
}
__device__ __forceinline__ void tma3d(uint32_t dst, const CUtensorMap* m, int c0, int c1, int c2, uint32_t bar) {
  asm volatile("cp.async.bulk.tensor.3d.shared::cluster.global.mbarrier::complete_tx::bytes [%0], [%1, {%3, %4, %5}], [%2];"
               ::"r"(dst), "l"(m), "r"(bar), "r"(c0), "r"(c1), "r"(c2) : "memory");
}
__device__ __forceinline__ void bulk_load(uint32_t dst, const void* src, uint32_t bytes, uint32_t bar) {
  asm volatile("cp.async.bulk.shared::cluster.global.mbarrier::complete_tx::bytes [%0], [%1], %2, [%3];" ::"r"(dst), "l"(src), "r"(bytes), "r"(bar) : "memory");
}
__device__ __forceinline__ void bulk_store(void* dst, uint32_t src, uint32_t bytes) {
  asm volatile("cp.async.bulk.global.shared::cta.bulk_group [%0], [%1], %2;" ::"l"(dst), "r"(src), "r"(bytes) : "memory");
}
__device__ __forceinline__ void st_async4(uint32_t dst, const uint32_t (&v)[4], uint32_t bar) {
  asm volatile("st.async.shared::cluster.mbarrier::complete_tx::bytes.v4.b32 [%0], {%1, %2, %3, %4}, [%5];" ::"r"(dst), "r"(v[0]), "r"(v[1]), "r"(v[2]), "r"(v[3]), "r"(bar) : "memory");
}
__device__ __forceinline__ void bulk_commit() { asm volatile("cp.async.bulk.commit_group;" ::: "memory"); }
__device__ __forceinline__ void bulk_prefetch(const void* p, uint32_t bytes) {
  asm volatile("cp.async.bulk.prefetch.L2.global [%0], %1;" ::"l"(p), "r"(bytes) : "memory");
}
__device__ __forceinline__ void tma2d_store(const CUtensorMap* m, uint32_t src, int c0, int c1) {
  asm volatile("cp.async.bulk.tensor.2d.global.shared::cta.bulk_group [%0, {%2, %3}], [%1];" ::"l"(m), "r"(src), "r"(c0), "r"(c1) : "memory");
}
__device__ __forceinline__ void wg_fence() { asm volatile("wgmma.fence.sync.aligned;" ::: "memory"); }
__device__ __forceinline__ void wg_commit() { asm volatile("wgmma.commit_group.sync.aligned;" ::: "memory"); }
template <int N> __device__ __forceinline__ void wg_wait() { asm volatile("wgmma.wait_group.sync.aligned %0;" ::"n"(N) : "memory"); }
__device__ __forceinline__ void fence_async_smem() { asm volatile("fence.proxy.async.shared::cta;" ::: "memory"); }
__device__ __forceinline__ void fence_async_global() { asm volatile("fence.proxy.async.global;" ::: "memory"); }
__device__ __forceinline__ void fence_release() { asm volatile("fence.release.gpu;" ::: "memory"); }
__device__ __forceinline__ void fence_acquire() { asm volatile("fence.acquire.gpu;" ::: "memory"); }
__device__ __forceinline__ void nb_sync(int id, int n) { asm volatile("bar.sync %0, %1;" ::"r"(id), "r"(n) : "memory"); }
__device__ __forceinline__ void nb_arrive(int id, int n) { asm volatile("bar.arrive %0, %1;" ::"r"(id), "r"(n) : "memory"); }
__device__ __forceinline__ void stsm4(uint32_t addr, uint32_t r0, uint32_t r1, uint32_t r2, uint32_t r3) {
  asm volatile("stmatrix.sync.aligned.m8n8.x4.shared.b16 [%0], {%1, %2, %3, %4};" ::"r"(addr), "r"(r0), "r"(r1), "r"(r2), "r"(r3) : "memory");
}
__device__ __forceinline__ void stsm4t(uint32_t addr, uint32_t r0, uint32_t r1, uint32_t r2, uint32_t r3) {
  asm volatile("stmatrix.sync.aligned.m8n8.x4.trans.shared.b16 [%0], {%1, %2, %3, %4};" ::"r"(addr), "r"(r0), "r"(r1), "r"(r2), "r"(r3) : "memory");
}
__device__ __forceinline__ void st_relaxed4(void* p, const uint32_t (&v)[4]) {
  asm volatile("st.relaxed.gpu.global.v4.u32 [%0], {%1, %2, %3, %4};" ::"l"(p), "r"(v[0]), "r"(v[1]), "r"(v[2]), "r"(v[3]) : "memory");
}
__device__ __forceinline__ void sts128(uint32_t addr, uint32_t a, uint32_t b, uint32_t c, uint32_t d) {
  asm volatile("st.shared.v4.b32 [%0], {%1, %2, %3, %4};" ::"r"(addr), "r"(a), "r"(b), "r"(c), "r"(d) : "memory");
}
__device__ __forceinline__ uint32_t pack2(float lo, float hi) {
  uint32_t r; asm("cvt.rn.bf16x2.f32 %0, %1, %2;" : "=r"(r) : "f"(hi), "f"(lo)); return r;
}
__device__ __forceinline__ float bf_lo(uint32_t v) { return __uint_as_float(v << 16); }
__device__ __forceinline__ float bf_hi(uint32_t v) { return __uint_as_float(v & 0xffff0000u); }
__device__ __forceinline__ float bf_round(float v) { return __bfloat162float(__float2bfloat16_rn(v)); }
__device__ __forceinline__ void ldsm4(uint32_t addr, uint32_t (&r)[4]) {
  asm volatile("ldmatrix.sync.aligned.m8n8.x4.shared.b16 {%0, %1, %2, %3}, [%4];" : "=r"(r[0]), "=r"(r[1]), "=r"(r[2]), "=r"(r[3]) : "r"(addr) : "memory");
}
__device__ __forceinline__ uint4 lds128(uint32_t addr) {
  uint4 v; asm volatile("ld.volatile.shared.v4.u32 {%0, %1, %2, %3}, [%4];" : "=r"(v.x), "=r"(v.y), "=r"(v.z), "=r"(v.w) : "r"(addr) : "memory"); return v;
}
__device__ __forceinline__ uint2 lds64(uint32_t addr) { uint2 v; asm volatile("ld.volatile.shared.v2.u32 {%0, %1}, [%2];" : "=r"(v.x), "=r"(v.y) : "r"(addr) : "memory"); return v; }
__device__ __forceinline__ uint32_t lds32(uint32_t addr) { uint32_t v; asm volatile("ld.volatile.shared.u32 %0, [%1];" : "=r"(v) : "r"(addr) : "memory"); return v; }
__device__ __forceinline__ uint32_t ld_generic(const void* p) { uint32_t v; asm volatile("ld.volatile.u32 %0, [%1];" : "=r"(v) : "l"(p) : "memory"); return v; }
__device__ __forceinline__ void sts32(uint32_t addr, uint32_t v) { asm volatile("st.shared.u32 [%0], %1;" ::"r"(addr), "r"(v) : "memory"); }
__device__ __forceinline__ uint32_t fma_bf2(uint32_t a, uint32_t b, uint32_t c) { uint32_t r; asm("fma.rn.bf16x2 %0, %1, %2, %3;" : "=r"(r) : "r"(a), "r"(b), "r"(c)); return r; }
__device__ __forceinline__ uint32_t mul_bf2(uint32_t a, uint32_t b) { uint32_t r; asm("mul.rn.bf16x2 %0, %1, %2;" : "=r"(r) : "r"(a), "r"(b)); return r; }
__device__ __forceinline__ unsigned ld_relaxed(const unsigned* p) { unsigned v; asm volatile("ld.relaxed.gpu.global.u32 %0, [%1];" : "=r"(v) : "l"(p) : "memory"); return v; }
__device__ __forceinline__ void st_relaxed(unsigned* p, unsigned v) { asm volatile("st.relaxed.gpu.global.u32 [%0], %1;" ::"l"(p), "r"(v) : "memory"); }
__device__ __forceinline__ uint4 ld_relaxed4(const void* p) {
  uint4 v; asm volatile("ld.relaxed.gpu.global.v4.u32 {%0, %1, %2, %3}, [%4];" : "=r"(v.x), "=r"(v.y), "=r"(v.z), "=r"(v.w) : "l"(p) : "memory"); return v;
}
__device__ __forceinline__ float4 ld_relaxed_f4(const void* p) {
  float4 v; asm volatile("ld.relaxed.gpu.global.v4.f32 {%0, %1, %2, %3}, [%4];" : "=f"(v.x), "=f"(v.y), "=f"(v.z), "=f"(v.w) : "l"(p) : "memory"); return v;
}
__device__ __forceinline__ void red_add4(void* p, float a, float b, float c, float d) {
  asm volatile("red.relaxed.gpu.global.add.v4.f32 [%0], {%1, %2, %3, %4};" ::"l"(p), "f"(a), "f"(b), "f"(c), "f"(d) : "memory");
}
__device__ __forceinline__ void red_add_bf(void* p, uint32_t a, uint32_t b, uint32_t c) {
  asm volatile("red.relaxed.gpu.global.add.noftz.v4.bf16x2 [%0], {%1, %2, %3, %4};" ::"l"(p), "r"(a), "r"(b), "r"(c), "r"(0x3F803F80u) : "memory");
}
__device__ __forceinline__ void red_add(unsigned* p, unsigned v) { asm volatile("red.relaxed.gpu.global.add.u32 [%0], %1;" ::"l"(p), "r"(v) : "memory"); }
__device__ __forceinline__ float rcp(float v) { float r; asm("rcp.approx.ftz.f32 %0, %1;" : "=f"(r) : "f"(v)); return r; }
__device__ __forceinline__ float sigmoidf_(float v) { return rcp(1.f + __expf(-v)); }
__device__ __forceinline__ uint32_t phi2(float a, float b, float l2e = 1.4426950408889634f) {
  float ea, eb;
  asm("ex2.approx.ftz.f32 %0, %1;" : "=f"(ea) : "f"(a * l2e));
  asm("ex2.approx.ftz.f32 %0, %1;" : "=f"(eb) : "f"(b * l2e));
  uint32_t t = pack2(a, b), e = pack2(ea, eb), r;
  asm("max.NaN.bf16x2 %0, %0, %1;" : "+r"(t) : "r"(0x35863586u));
  asm("min.bf16x2 %0, %0, %1;" : "+r"(e) : "r"(0x3F803F80u));
  asm("add.rn.bf16x2 %0, %1, %2;" : "=r"(r) : "r"(t), "r"(e));
  return r;
}
__device__ __forceinline__ uint64_t mkdesc(uint32_t addr, uint32_t lbo, uint32_t sbo, uint32_t sw) {
  return (uint64_t)(((addr & 0x3FFFF) >> 4) | ((lbo >> 4) << 16)) | ((uint64_t)((sbo >> 4) | (sw << 30)) << 32);
}

template <int TA, int TB>
__device__ __forceinline__ void mma128(float (&d)[64], uint64_t da, uint64_t db, int sc) {
  asm volatile("{\n.reg .pred p;\nsetp.ne.b32 p, %66, 0;\n"
    "wgmma.mma_async.sync.aligned.m64n128k16.f32.bf16.bf16 "
    "{%0,%1,%2,%3,%4,%5,%6,%7,%8,%9,%10,%11,%12,%13,%14,%15,%16,%17,%18,%19,%20,%21,%22,%23,"
    "%24,%25,%26,%27,%28,%29,%30,%31,%32,%33,%34,%35,%36,%37,%38,%39,%40,%41,%42,%43,%44,%45,%46,%47,"
    "%48,%49,%50,%51,%52,%53,%54,%55,%56,%57,%58,%59,%60,%61,%62,%63}, "
    "%64, %65, p, 1, 1, %67, %68;\n}\n"
    : "+f"(d[0]), "+f"(d[1]), "+f"(d[2]), "+f"(d[3]), "+f"(d[4]), "+f"(d[5]), "+f"(d[6]), "+f"(d[7]),
      "+f"(d[8]), "+f"(d[9]), "+f"(d[10]), "+f"(d[11]), "+f"(d[12]), "+f"(d[13]), "+f"(d[14]), "+f"(d[15]),
      "+f"(d[16]), "+f"(d[17]), "+f"(d[18]), "+f"(d[19]), "+f"(d[20]), "+f"(d[21]), "+f"(d[22]), "+f"(d[23]),
      "+f"(d[24]), "+f"(d[25]), "+f"(d[26]), "+f"(d[27]), "+f"(d[28]), "+f"(d[29]), "+f"(d[30]), "+f"(d[31]),
      "+f"(d[32]), "+f"(d[33]), "+f"(d[34]), "+f"(d[35]), "+f"(d[36]), "+f"(d[37]), "+f"(d[38]), "+f"(d[39]),
      "+f"(d[40]), "+f"(d[41]), "+f"(d[42]), "+f"(d[43]), "+f"(d[44]), "+f"(d[45]), "+f"(d[46]), "+f"(d[47]),
      "+f"(d[48]), "+f"(d[49]), "+f"(d[50]), "+f"(d[51]), "+f"(d[52]), "+f"(d[53]), "+f"(d[54]), "+f"(d[55]),
      "+f"(d[56]), "+f"(d[57]), "+f"(d[58]), "+f"(d[59]), "+f"(d[60]), "+f"(d[61]), "+f"(d[62]), "+f"(d[63])
    : "l"(da), "l"(db), "r"(sc), "n"(TA), "n"(TB));
}

__device__ __forceinline__ void mma_ktv(float (&d)[36], const uint32_t (&a)[4], uint64_t db, int sc) {
  asm volatile("{\n.reg .pred p;\nsetp.ne.b32 p, %41, 0;\n"
    "wgmma.mma_async.sync.aligned.m64n72k16.f32.bf16.bf16 "
    "{%0,%1,%2,%3,%4,%5,%6,%7,%8,%9,%10,%11,%12,%13,%14,%15,%16,%17,%18,%19,%20,%21,%22,%23,"
    "%24,%25,%26,%27,%28,%29,%30,%31,%32,%33,%34,%35}, "
    "{%36,%37,%38,%39}, %40, p, 1, 1, 0;\n}\n"
    : "+f"(d[0]), "+f"(d[1]), "+f"(d[2]), "+f"(d[3]), "+f"(d[4]), "+f"(d[5]), "+f"(d[6]), "+f"(d[7]),
      "+f"(d[8]), "+f"(d[9]), "+f"(d[10]), "+f"(d[11]), "+f"(d[12]), "+f"(d[13]), "+f"(d[14]), "+f"(d[15]),
      "+f"(d[16]), "+f"(d[17]), "+f"(d[18]), "+f"(d[19]), "+f"(d[20]), "+f"(d[21]), "+f"(d[22]), "+f"(d[23]),
      "+f"(d[24]), "+f"(d[25]), "+f"(d[26]), "+f"(d[27]), "+f"(d[28]), "+f"(d[29]), "+f"(d[30]), "+f"(d[31]),
      "+f"(d[32]), "+f"(d[33]), "+f"(d[34]), "+f"(d[35])
    : "r"(a[0]), "r"(a[1]), "r"(a[2]), "r"(a[3]), "l"(db), "r"(sc));
}

__device__ __forceinline__ void mma_qkvz(float (&d)[20], uint64_t da, uint64_t db, int sc) {
  asm volatile("{\n.reg .pred p;\nsetp.ne.b32 p, %22, 0;\n"
    "wgmma.mma_async.sync.aligned.m64n40k16.f32.bf16.bf16 "
    "{%0,%1,%2,%3,%4,%5,%6,%7,%8,%9,%10,%11,%12,%13,%14,%15,%16,%17,%18,%19}, "
    "%20, %21, p, 1, 1, 0, 1;\n}\n"
    : "+f"(d[0]), "+f"(d[1]), "+f"(d[2]), "+f"(d[3]), "+f"(d[4]), "+f"(d[5]), "+f"(d[6]), "+f"(d[7]),
      "+f"(d[8]), "+f"(d[9]), "+f"(d[10]), "+f"(d[11]), "+f"(d[12]), "+f"(d[13]), "+f"(d[14]), "+f"(d[15]),
      "+f"(d[16]), "+f"(d[17]), "+f"(d[18]), "+f"(d[19])
    : "l"(da), "l"(db), "r"(sc));
}

template <int N> __device__ __forceinline__ void pin(float (&d)[N]) {
#pragma unroll
  for (int i = 0; i < N; i++) asm volatile("" : "+f"(d[i])::"memory");
}

struct Params {
  CUtensorMap x, w, w1, xr, gate, up, wo, out, down;
};

__device__ __forceinline__ uint32_t dup_lo(uint32_t v) { uint32_t r; asm("{\n.reg .b16 l, h;\nmov.b32 {l, h}, %1;\nmov.b32 %0, {l, l};\n}" : "=r"(r) : "r"(v)); return r; }
__device__ __forceinline__ uint32_t dup_hi(uint32_t v) { uint32_t r; asm("{\n.reg .b16 l, h;\nmov.b32 {l, h}, %1;\nmov.b32 %0, {h, h};\n}" : "=r"(r) : "r"(v)); return r; }
__device__ __forceinline__ float butterfly8(float (&s)[8], int lane, int o) {
#pragma unroll
  for (int k = 1; k < 8; k <<= 1) {
    const bool up = lane & (o * k);
#pragma unroll
    for (int j = 0; j < 4 / k; j++) s[j] = (up ? s[2 * j + 1] : s[2 * j]) + __shfl_xor_sync(~0u, up ? s[2 * j] : s[2 * j + 1], o * k);
  }
  return s[0];
}
constexpr int OWN = 8, PEER = 9;
static_assert((OA_SLOTS >> OWN * 4 & 15) * SLOT == OFF_V && (OA_SLOTS >> PEER * 4 & 15) * SLOT == OFF_PK, "");
template <int B> __device__ __forceinline__ void verify_tiles(uint32_t sb, Scratch* gs, int tm, int tn, int w, int lane) {
  const uint32_t par = lds32(sb + OFF_MISC + 24), fix = sb + BAR_FIX + (B * 4 + w) * 8;
  uint32_t slots = (uint32_t)(OA_SLOTS >> B * 40);
#pragma unroll 1
  for (int i = 0; i < 8 - 2 * B; i++, slots >>= 4) {
    const uint32_t a = sb + OFF_RING + (slots & 15) * SLOT + w * 1024, cw = a + lane * 32 + (lane >> 2) * 4;
    if (!B && i == 4) mbar_wait(sb + BAR_EMPTY + 7 * 8, 1);
    mbar_wait(sb + BAR_LAND + i * 8, B);
    for (;;) {
      const uint32_t u0 = lds32(cw), u1 = lds32(cw + 4096), u2 = lds32(cw + 8192), u3 = lds32(cw + 12288);
      if (__all_sync(~0u, !(mism(mism(u0, u1, par), mism(u2, u3, par), 0) & 1))) break;
      const uint4* src = gs->o[tm][!B ? i : i < (tn & 6) ? i + 8 : i + 10] + w * 64;
      const uint32_t ph = !mbar_test(fix, 1);
      fence_async_smem();
      __syncwarp();
      if (elect()) {
        mbar_expect_tx(fix, 4096);
#pragma unroll 1
        for (int j = 0; j < 4; j++) bulk_load(a + j * 4096, src + j * 256, 1024, fix);
      }
      mbar_wait(fix, ph);
    }
    mbar_arrive_warp(sb + BAR_OFULL + (i < 5 ? i : i - 5) * 8);
  }
}
template <bool BY_SM> struct Tile {
  int sm, tm, tn, mu;
  bool spare;
  __device__ __forceinline__ Tile() {
    if (BY_SM) asm volatile("mov.u32 %0, %%smid;" : "=r"(sm));
    else sm = blockIdx.x + (blockIdx.x >= 120) * 4;
    const int tp = sm >> 1, pr = sm & 1;
    const int v = tp < 32 ? tp : tp < 60 ? (tp * 293 - 928) >> 8 : tp * 8 - 464, g = v & 7, i = v >> 3;
    tm = (v & 6) * 2 + (i & 3); tn = (v & 1) * 4 + (v >> 4 & 2) + pr;
    mu = i == 5 ? 112 : g * 14 + (i - (i > 5)) * 2 + pr;
    spare = (tp | 1) == 61;
  }
};

template <bool BY_SM> __global__ void __cluster_dims__(2, 1, 1) __launch_bounds__(NTHREADS, 1) fused_kernel(const __nv_bfloat16* __restrict__ px, Scratch* gs, const __nv_bfloat16* __restrict__ w_gate,
             const __nv_bfloat16* __restrict__ w_up, const __nv_bfloat16* __restrict__ w_r, const __nv_bfloat16* __restrict__ gate_w, __nv_bfloat16* __restrict__ pout,
             const __grid_constant__ Params p) {
  extern __shared__ __align__(1024) uint8_t smem[];
  const uint32_t sb = __shfl_sync(~0u, (uint32_t)__cvta_generic_to_shared(smem), 0);
  const int tid = threadIdx.x, lane = tid & 31;
  const int warp = __shfl_sync(~0u, tid >> 5, 0), wg = warp >> 2;
  const uint32_t t_start = clock32();
  const Tile<BY_SM> tile;
  const int tm = tile.tm, tn = tile.tn, mu = tile.mu, cta = tm * 8 + tn;
  const uint32_t zero = tile.sm >> 12;
  if (warp == 0) {
#pragma unroll
    for (int s = 0; s < PRE; s++)
      if (elect()) mbar_init(sb + BAR_FULL + s * 8, 1);
    if (SP && elect()) mbar_init(sb + BAR_SP, 1);
    asm volatile("fence.mbarrier_init.release.cluster;" ::: "memory");
    if (!tile.spare) {
      if (SP) {
        if (elect()) tma3d(sb + OFF_W1 + 8192, &p.w1, tn * 64, 0, 1, sb + BAR_FULL);
        if (elect()) tma2d(sb + OFF_RING, &p.x, 0, tm * 128, sb + BAR_FULL);
        if (elect()) tma3d(sb + OFF_W1 + 16384, &p.w1, tn * 64, 0, 2, sb + BAR_SP);
        if (elect()) tma3d(sb + OFF_W1, &p.w1, tn * 64, 0, 0, sb + BAR_SP);
        PROF(lane == 0, 64);
      }
#pragma unroll
      for (int s = SP; s < PRE; s++) {
        if (elect()) tma3d(sb + OFF_W1 + s * WQKV_BYTES, &p.w, tn * 64, s * 64, 0, sb + BAR_FULL + s * 8);
        if (elect()) tma2d(sb + OFF_RING + s * SLOT, &p.x, s * 64, tm * 128, sb + BAR_FULL + s * 8);
        PROF(lane == 0, 64 + s);
      }
      if (elect()) {
#pragma unroll
        for (int s = 0; s < PRE; s++) mbar_expect_tx(sb + BAR_FULL + s * 8, s || !SP ? SLOT + WQKV_BYTES : SLOT + 8192);
        if (SP) mbar_expect_tx(sb + BAR_SP, 16384);
      }
    }
  }
  if (warp) {
    const int wi = warp == 15 ? 0 : warp;
    const int cnt = wi < 7 ? 1 : wi < 13 ? 4 : 5;
#pragma unroll
    for (int i = 0; i < 4; i++)
      if ((i >= PRE || wi) && elect()) mbar_init(sb + OFF_BAR + wi * 32 + i * 8, cnt);
    asm volatile("fence.mbarrier_init.release.cluster;" ::: "memory");
  }
  __syncthreads();
  if (tile.spare) {
    if (warp == 0) {
      const unsigned tag = (ld_relaxed(&gs->spare[tile.sm & 3]) + 1) & 0xFFF;
      const unsigned long long t0 = gtime();
      uint4 r4;
      do {
        __nanosleep(2048);
        if (gtime() - t0 > WATCHDOG_NS) __trap();
        r4 = ld_relaxed4(&gs->rslot[tile.sm & 3][lane * 4]);
      } while (!__all_sync(~0u, (((r4.x ^ tag) | (r4.y ^ tag) | (r4.z ^ tag) | (r4.w ^ tag)) & 0xFFF) == 0));
      if (tid == 0) st_relaxed(&gs->spare[tile.sm & 3], tag);
    }
    return;
  }

  if (wg == 3) {
    asm volatile("setmaxnreg.dec.sync.aligned.u32 24;");
    if (warp == 12) {
      mbar_wait(sb + BAR_PUB, 0);
      while (!__all_sync(~0u, ld_relaxed(gs->cnt[tm]) == 0x44444444u)) __nanosleep(A_SLEEP);
      PROF(lane == 0, 7);
      mbar_wait(sb + BAR_GATE, 0);
      uint32_t slots = (uint32_t)OA_SLOTS, deps = 0xA9877654u;
#pragma unroll 1
      for (int i = 0; i < 8; i++, deps >>= 4, slots >>= 4) {
        mbar_wait(sb + BAR_EMPTY + (deps & 15) * 8, i < 5);
        if (elect()) bulk_load(sb + OFF_RING + (slots & 15) * SLOT, gs->o[tm][i], SLOT, sb + BAR_LAND + i * 8);
        if (elect()) mbar_expect_tx(sb + BAR_LAND + i * 8, SLOT);
        PROF(lane == 0, 44 + i);
      }
      slots = (uint32_t)(OA_SLOTS >> 40);
      uint32_t seen = 0;
      mbar_wait(sb + BAR_PUB + 8, 0);
#pragma unroll 1
      for (int i = 0; i < 6; i++, slots >>= 4) {
        const uint32_t slab = i < (tn & 6) ? i : i + 2;
        if (!(seen >> slab * 4 & 4))
          while (!((seen = __shfl_sync(~0u, ld_relaxed(gs->cnt[16 + tm]), 0)) >> slab * 4 & 4)) __nanosleep(B_SLEEP);
        mbar_wait(sb + BAR_OEMPTY + (i < 5 ? i : 0) * 8, i < 5);
        if (elect()) bulk_load(sb + OFF_RING + (slots & 15) * SLOT, gs->o[tm][8 + slab], SLOT, sb + BAR_LAND + i * 8);
        if (elect()) mbar_expect_tx(sb + BAR_LAND + i * 8, SLOT);
        PROF(lane == 0, 54 + i);
      }
    } else if (warp == 13) {
#pragma unroll 1
      for (int g = E7 ? 4 : PRE; g < 32; g++) {
        const bool reuse = (g >> 2) == 4;
        const uint32_t s = g & 3, full = sb + BAR_FULL + (g & 7) * 8, c0 = tn * 64 + (g & 16) * 32, c1 = (g < 16 ? g : g - 4 & 15) * 64;
        if (!E7 && g < 4) while ((int)(clock32() - t_start) < g * ST1) {}
        mbar_wait(sb + BAR_EMPTY + (g + 4 & 7) * 8, (g + 4 >> 3 & 1) ^ 1);
        if (!reuse && elect()) tma2d(sb + OFF_RING + s * SLOT, &p.x, c1, tm * 128, full);
        if (elect()) tma3d(sb + OFF_W1 + s * WQKV_BYTES, &p.w, c0, c1, 0, full);
        if (elect()) mbar_expect_tx(full, reuse ? WQKV_BYTES : SLOT + WQKV_BYTES);
        PROF(lane == 0, 64 + g);
        const uint32_t i = g - RT_G0;
        if (i < 4 && elect()) {
          mbar_expect_tx(sb + BAR_RT + i * 8, i ? 8192 : 8192 + 4096);
          tma2d(sb + OFF_PK + i * 8192 + (i == 3) * 1024, &p.xr, ((i + RT_ROT) & 3) * 256, cta * 16, sb + BAR_RT + i * 8);
          if (i == 0) { bulk_load(sb + OFF_KVB, w_r, 2048, sb + BAR_RT); bulk_load(sb + OFF_KVB + 2048, gate_w, 2048, sb + BAR_RT); }
        }
        const uint32_t c = g - MOD_START;
        if (c == MOD_BUFS) mbar_wait(sb + BAR_RTD, 0);
        if (c < MOD_BUFS0 && mu < MOD_CTAS && elect()) {
          PROF(true, 192 + c);
          const uint32_t mb = c < MOD_BUFS ? c + 2 : c - MOD_BUFS, mfull = sb + BAR_MFULL + mb * 8, mdst = sb + OFF_V + mb * MOD_STEP;
          mbar_expect_tx(mfull, c ? 8192 : 8192 + 2048);
          tma3d(mdst, &p.gate, mu * 32, c * 16, 0, mfull); tma3d(mdst + 4096, &p.up, mu * 32, c * 16, 0, mfull);
        }
        const uint32_t pc = g - PF_MOD;
        if (pc < 16 && elect()) bulk_prefetch((cta & 64 ? w_up : w_gate) + (size_t)(pc * 64 + (cta & 63)) * F_, F_ * 2);
      }
      mbar_arrive_warp(sb + BAR_GATE);
      const uint32_t lowb = (1u << (tn & 6) * 4) - 1;
      uint64_t slabs = (uint64_t)((0xFEDCBA98u & lowb) | (0xFEDCBAu & ~lowb)) << 40 | (uint64_t)(8 + (tn ^ 1)) << 36 | (uint64_t)(8 + tn) << 32 | 0x76543210u;
      uint64_t deps = 0x8CBA98CBA9876554ull, ws = OW_SLOTS;
      uint32_t full = sb + BAR_OFULL, ph = 1;
#pragma unroll 1
      for (int g = 0; g < 16; g++, slabs >>= 4, deps >>= 4, ws >>= 4) {
        mbar_wait(sb + BAR_EMPTY + ((uint32_t)deps & 15) * 8, ph);
        if (elect()) tma3d(sb + OFF_RING + ((uint32_t)ws & 15) * SLOT, &p.wo, 0, ((uint32_t)slabs & 15) * 64, tn * 2, full);
        if (elect()) mbar_expect_tx(full, SLOT);
        PROF(lane == 0, 96 + g);
        if (g >> 1 == OWN / 2 && lane < 4) mbar_arrive(full);
        full += 8;
        if (full == sb + BAR_OFULL + 40) { full -= 40; ph ^= 1; }
      }
    } else if (warp == 14) {
      if (mu < MOD_CTAS) {
        uint32_t full = sb + BAR_MFULL + 16, dst = sb + OFF_MOD, ph = 0;
#pragma unroll 1
        for (int c = MOD_BUFS0; c < 24; c++) {
          mbar_wait(full + (BAR_MEMPTY - BAR_MFULL), ph);
          PROF(lane == 0, 192 + c);
          if (c < 16) {
            if (elect()) { tma3d(dst, &p.gate, mu * 32, c * 16, 0, full); tma3d(dst + 4096, &p.up, mu * 32, c * 16, 0, full); }
          } else if (elect()) tma3d(dst, &p.down, 0, mu * 32 + (c - 16) * 4, 0, full);
          if (elect()) mbar_expect_tx(full, 8192);
          full += 8; dst += MOD_STEP;
          if (full == sb + BAR_MFULL + MOD_BUFS0 * 8) { full -= MOD_BUFS * 8; dst = sb + OFF_MOD; ph ^= 1; }
        }
      }
      if (elect()) {
      mbar_wait(sb + BAR_IDX, 0);
      const bool paired = PAIRED && ld_relaxed(&gs->block[cta ^ 1]) == (blockIdx.x ^ 1);
      if (paired) mbar_expect_tx(sb + BAR_PEER, SLOT);
      mbar_expect_tx(sb + BAR_X, 32768);
      mbar_wait(sb + BAR_OEMPTY + 3 * 8, 0);
      tma2d(sb + OFF_RES, &p.x, tn * 128, tm * 128, sb + BAR_X);
      mbar_wait(sb + BAR_OEMPTY + 4 * 8, 0);
      tma2d(sb + OFF_RES + RES_H, &p.x, tn * 128 + 64, tm * 128, sb + BAR_X);
      if (!paired) {
        mbar_wait(sb + BAR_OWN, 0);
        while (!(ld_relaxed(gs->cnt[16 + tm]) & 4u << (tn ^ 1) * 4)) __nanosleep(32);
        fence_acquire();
        fence_async_global();
        const uint32_t par = lds32(sb + OFF_MISC + 24);
        for (uint32_t ph = !mbar_test(sb + BAR_MFULL, 1), bad = 1; bad & 1; ph ^= 1) {
          fence_async_smem();
          mbar_expect_tx(sb + BAR_MFULL, SLOT);
          bulk_load(sb + OFF_PK, gs->o[tm][8 + (tn ^ 1)], SLOT, sb + BAR_MFULL);
          mbar_wait(sb + BAR_MFULL, ph);
          bad = 0;
#pragma unroll 1
          for (int i = 0; i < 512; i++) bad |= lds32(sb + OFF_PK + i * 32 + (i & 28)) ^ par;
        }
        mbar_arrive(sb + BAR_PEER);
      }
      }
    } else {
#pragma unroll 1
      for (int i = 3; i < 9; i++)
        if (elect()) asm volatile("prefetch.tensormap [%0];" ::"l"(&p.x + i) : "memory");
      mbar_wait_bounded(sb + BAR_DONE, 0);
    }
  } else if (wg == 2) {
    asm volatile("setmaxnreg.dec.sync.aligned.u32 40;");
    const int mw = warp & 3;
    if (mw == 0) {
      const unsigned tag = (ld_relaxed(&gs->rslot[tn][cta]) + 1) & 0xFFF;
#pragma unroll
      for (int i = 0; i < 2; i++)
        if (lane < 28) ((float4*)gs)[cta * 56 + i * 28 + lane] = make_float4(0.f, 0.f, 0.f, 0.f);
      if (lane == 29) gs->block[cta] = blockIdx.x;
      fence_release();
      nb_sync(NB_KEY, 160);
      const uint4 k4 = lds128(sb + OFF_MISC);
      if (lane < 8) st_relaxed(&gs->rslot[lane][cta], max(max(k4.x, k4.y), max(k4.z, k4.w)) | tag);
      if (lane < 16) st_relaxed(&gs->gslot[cta * 16 + lane], lds32(sb + OFF_G + lane * 4) | tag);
      PROF(lane == 0, 20);
      uint4 r4;
      do {
        __nanosleep(RT_SLEEP);
        r4 = ld_relaxed4(&gs->rslot[tn][lane * 4]);
      } while (!__all_sync(~0u, (((r4.x ^ tag) | (r4.y ^ tag) | (r4.z ^ tag) | (r4.w ^ tag)) & 0xFFF) == 0));
      const int c0 = 0xFFF0 - lane * 64;
      unsigned key = max(max((r4.x & 0xFFFF0000u) | (c0 + ((r4.x >> 12) & 15)), (r4.y & 0xFFFF0000u) | (c0 - 16 + ((r4.y >> 12) & 15))),
                         max((r4.z & 0xFFFF0000u) | (c0 - 32 + ((r4.z >> 12) & 15)), (r4.w & 0xFFFF0000u) | (c0 - 48 + ((r4.w >> 12) & 15))));
      key = __reduce_max_sync(~0u, key);
      if (elect()) {
        sts32(sb + OFF_MISC + 16, key);
        sts32(sb + OFF_MISC + 24, tag & 1);
        if (mu < MOD_CTAS) {
          const __nv_bfloat16* row = px + (size_t)(0xFFFF - (key & 0xFFFF)) * D_;
          bulk_load(sb + OFF_XSEL, row, 1024, sb + BAR_MFULL + 16);
          bulk_load(sb + OFF_XSEL + MOD_STEP, row + 512, 1024, sb + BAR_MFULL + 16);
        }
      }
      PROF(lane == 0, 21);
      do {
        r4 = ld_relaxed4(&gs->gslot[tm * 128 + lane * 4]);
      } while (!__all_sync(~0u, (((r4.x ^ tag) | (r4.y ^ tag) | (r4.z ^ tag) | (r4.w ^ tag)) & 0xFFF) == 0));
      sts128(sb + OFF_G + lane * 16, r4.x & 0xFFFF0000u, r4.y & 0xFFFF0000u, r4.z & 0xFFFF0000u, r4.w & 0xFFFF0000u);
      fence_acquire();
      __syncwarp();
    }
    PROF(tid == 256, 22);
    if (mu >= MOD_CTAS) {
      mbar_arrive_warp(sb + BAR_IDX);
    } else {
      const uint32_t wp = sb + OFF_V + (mw >> 1) * 4096 + (mw & 1) * 512 + lane * 16;
      uint32_t mp = sb + OFF_XSEL + (mw & 1) * 64 + (lane >> 2) * 8, mc = 128;
      float acc[8] = {0.f, 0.f, 0.f, 0.f, 0.f, 0.f, 0.f, 0.f};
      uint32_t b = 2, ph = 0;
#pragma unroll 1
      for (int c = 0; c < 24; c++) {
        mbar_wait(sb + BAR_MFULL + b * 8, ph);
        PROF_C(tid == 256, 216 + c);
        const uint32_t a = wp + b * MOD_STEP;
        const uint2 m = lds64(mp);
        const uint4 w0 = lds128(a), w1 = lds128(a + 1024), w2 = lds128(a + 2048), w3 = lds128(a + 3072);
        mp += c == 7 ? MOD_STEP - 1024 + 128 : mc;
        const uint32_t m0 = dup_lo(m.x), m1 = dup_hi(m.x), m2 = dup_lo(m.y), m3 = dup_hi(m.y);
        uint4 q = make_uint4(mul_bf2(w0.x, m0), mul_bf2(w0.y, m0), mul_bf2(w0.z, m0), mul_bf2(w0.w, m0));
        q = make_uint4(fma_bf2(w1.x, m1, q.x), fma_bf2(w1.y, m1, q.y), fma_bf2(w1.z, m1, q.z), fma_bf2(w1.w, m1, q.w));
        q = make_uint4(fma_bf2(w2.x, m2, q.x), fma_bf2(w2.y, m2, q.y), fma_bf2(w2.z, m2, q.z), fma_bf2(w2.w, m2, q.w));
        mbar_arrive_warp(sb + BAR_MEMPTY + b * 8 + (w3.x & zero));
        q = make_uint4(fma_bf2(w3.x, m3, q.x), fma_bf2(w3.y, m3, q.y), fma_bf2(w3.z, m3, q.z), fma_bf2(w3.w, m3, q.w));
        if (++b == 5) b = c < 3 ? 0 : 2;
        if (b == 2) ph ^= 1;
        acc[0] += bf_lo(q.x); acc[1] += bf_hi(q.x); acc[2] += bf_lo(q.y); acc[3] += bf_hi(q.y);
        acc[4] += bf_lo(q.z); acc[5] += bf_hi(q.z); acc[6] += bf_lo(q.w); acc[7] += bf_hi(q.w);
        if (c == 15) {
          const uint32_t ft = fresh_tid(), fl = ft & 31;
          sts32(sb + OFF_PART + (ft & 96) * 4 + ((ft & 3) * 8 + (fl >> 2)) * 4, __float_as_uint(butterfly8(acc, fl, 4)));
          nb_sync(NB_MODW, 128);
          const float* part = (const float*)(smem + OFF_PART) + fl;
          const float gp = bf_round(part[0] + part[32]), up = bf_round(part[64] + part[96]);
          *(__nv_bfloat16*)(smem + OFF_PART + 512 + fl * 2) = __float2bfloat16_rn(bf_round(gp * sigmoidf_(gp)) * up);
          __syncwarp();
          mp = sb + OFF_PART + 512; mc = 8;
#pragma unroll
          for (int i = 0; i < 8; i++) acc[i] = 0.f;
          PROF(lane == 0 && mw == 0, 23);
        }
      }
      float4* yacc = gs->y[tn & 1][0] + (fresh_tid() & 127);
      red_add4(yacc, acc[0], acc[1], acc[2], 1.f);
      red_add4(yacc + 128, acc[3], acc[4], acc[5], 1.f);
      red_add4(yacc + 256, acc[6], acc[7], 0.f, 1.f);
      PROF(lane == 0 && mw == 0, 25);
    }
    mbar_wait(sb + BAR_GATE, 0);
    mbar_wait(sb + BAR_IDX, 0);
    verify_tiles<0>(sb, gs, tm, tn, mw, lane);
    const unsigned key = lds32(sb + OFF_MISC + 16);
    const int sel = 0xFFFF - (int)(key & 0xFFFF) - tm * 128;
    if (mw == 0 && sel >= 0 && sel < 128) {
      const unsigned k16 = key >> 16;
      const float rs = bf_round(sigmoidf_(__uint_as_float(((k16 & 0x8000u) ? (k16 & 0x7FFFu) : (~k16 & 0xFFFFu)) << 16)));
      float v[12];
      const float4* yp = gs->y[lane >> 4][0] + tn * 16 + (lane & 15);
      for (;;) {
#pragma unroll
        for (int i = 0; i < 3; i++) {
          const float4 u = ld_relaxed_f4(yp + i * 128);
          v[4 * i] = u.x; v[4 * i + 1] = u.y; v[4 * i + 2] = u.z; v[4 * i + 3] = u.w;
        }
        const float n = v[3] + v[7] + v[11];
        if (__all_sync(~0u, n + __shfl_xor_sync(~0u, n, 16) == 3.f * MOD_CTAS)) break;
        __nanosleep(Y_SLEEP);
      }
#pragma unroll
      for (int i = 0; i < 10; i++) v[i] = bf_round(bf_round(v[i] + __shfl_xor_sync(~0u, v[i], 16)) * rs);
      PROF(lane == 0, 24);
      mbar_wait(sb + BAR_X, 0);
      if (lane < 16) {
        uint4* xp = (uint4*)(smem + OFF_RES + (lane >> 3) * RES_H + sel * 128 + (((lane ^ sel) & 7) << 4));
        const uint4 xv = *xp;
        *xp = make_uint4(pack2(bf_lo(xv.x) + v[0], bf_hi(xv.x) + v[1]), pack2(bf_lo(xv.y) + v[2], bf_hi(xv.y) + v[4]),
                         pack2(bf_lo(xv.z) + v[5], bf_hi(xv.z) + v[6]), pack2(bf_lo(xv.w) + v[8], bf_hi(xv.w) + v[9]));
      }
      __syncwarp();
      mbar_arrive_warp(sb + BAR_Y);
    }
  } else {
    if (E7 && warp == 7) {
#pragma unroll
      for (int g = PRE; g < 4; g++) {
        while ((int)(clock32() - t_start) < ST0 + (g - PRE) * ST1) {}
        if (elect()) tma2d(sb + OFF_RING + g * SLOT, &p.x, g * 64, tm * 128, sb + BAR_FULL + g * 8);
        if (elect()) tma3d(sb + OFF_W1 + g * WQKV_BYTES, &p.w, tn * 64, g * 64, 0, sb + BAR_FULL + g * 8);
        if (elect()) mbar_expect_tx(sb + BAR_FULL + g * 8, SLOT + WQKV_BYTES);
        PROF(lane == 0, 64 + g);
        const int i = g - RT_G0;
        if (i >= 0 && elect()) {
          mbar_expect_tx(sb + BAR_RT + i * 8, i ? 8192 : 8192 + 4096);
          tma2d(sb + OFF_PK + i * 8192, &p.xr, ((i + RT_ROT) & 3) * 256, cta * 16, sb + BAR_RT + i * 8);
          if (i == 0) { bulk_load(sb + OFF_KVB, w_r, 2048, sb + BAR_RT); bulk_load(sb + OFF_KVB + 2048, gate_w, 2048, sb + BAR_RT); }
        }
      }
    }
    asm volatile("setmaxnreg.inc.sync.aligned.u32 224;");
    const int w = warp & 3, wt = tid & 127;
    const int nb_self = NB_WG0 + wg;
    const uint64_t da0 = mkdesc(sb + OFF_RING, 16, 1024, 1), db0 = mkdesc(sb + OFF_RING, 8192, 1024, 1);

    if (wg == 1) {
      sts128(sb + OFF_ONES - (w >> 1) * 9216 + (w & 1) * 512 + lane * 16, 0x3F803F80u, 0x3F803F80u, 0x3F803F80u, 0x3F803F80u);
      sts32(sb + OFF_MISC + 20, 0x3FB8AA3Bu);
      fence_async_smem();
      float s[8] = {0.f, 0.f, 0.f, 0.f, 0.f, 0.f, 0.f, 0.f};
      uint32_t mask = 0xffff0000u;
#pragma unroll 1
      for (int i = 0; i < 4; i++) {
        const uint32_t u = (i + RT_ROT) & 3;
        mbar_wait(sb + BAR_RT + i * 8, 0);
        const uint4 wr = lds128(sb + OFF_KVB + u * 512 + lane * 16), gw = lds128(sb + OFF_KVB + 2048 + u * 512 + lane * 16);
        uint4 xv[4];
#pragma unroll
        for (int r = 0; r < 4; r++) xv[r] = lds128(sb + OFF_PK + i * 8192 + (i == 3) * 1024 + (w * 4 + r) * 512 + lane * 16);
        const float wf[16] = {bf_lo(wr.x), bf_hi(wr.x), bf_lo(wr.y), bf_hi(wr.y), bf_lo(wr.z), bf_hi(wr.z), bf_lo(wr.w), bf_hi(wr.w),
                              bf_lo(gw.x), bf_hi(gw.x), bf_lo(gw.y), bf_hi(gw.y), bf_lo(gw.z), bf_hi(gw.z), bf_lo(gw.w), bf_hi(gw.w)};
#pragma unroll
        for (int r = 0; r < 4; r++) {
          const uint4 xq = xv[r];
          const float xf[8] = {bf_lo(xq.x), __uint_as_float(xq.x & mask), bf_lo(xq.y), bf_hi(xq.y), bf_lo(xq.z), bf_hi(xq.z), bf_lo(xq.w), bf_hi(xq.w)};
#pragma unroll
          for (int j = 0; j < 8; j++) { s[2 * r] = fmaf(xf[j ^ 1], wf[j ^ 1], s[2 * r]); s[2 * r + 1] = fmaf(xf[j ^ 1], wf[8 + (j ^ 1)], s[2 * r + 1]); }
          mask = ((__float_as_uint(s[2 * r]) | __float_as_uint(s[2 * r + 1])) & zero) | 0xffff0000u;
        }
      }
      mbar_arrive_warp(sb + BAR_RTD + (__float_as_uint(s[6]) & zero));
      float v = butterfly8(s, lane, 1);
      PROF_C(wt == 0 && v != 12345.f, 19);
      v += __shfl_xor_sync(~0u, v, 8);
      v = bf_round(v + __shfl_xor_sync(~0u, v, 16));
      const unsigned rb = __float_as_uint(v) >> 16, row = w * 4 + ((lane & 7) >> 1);
      unsigned key = (lane & 1) ? 0u : ((((rb & 0x8000u) ? (~rb & 0xFFFFu) : (rb | 0x8000u)) << 16) | ((15 - row) << 12));
      key = __reduce_max_sync(~0u, key);
      if (lane == 0) sts32(sb + OFF_MISC + w * 4, key);
      if (lane < 8 && (lane & 1)) sts32(sb + OFF_G + row * 4, __float_as_uint(bf_round(sigmoidf_(v))));
      nb_arrive(NB_KEY, 160);
      nb_sync(NB_ORDER_12, 256);
    }
    uint4* const kvacc = &gs->kv[wg][tn][0][wt];
    float aq[64];
    uint32_t su[9];
    float pq[64], ak[64], av[64];
    auto proj = [&](float (&d)[64], int j, uint32_t s, int sc) {
#pragma unroll
      for (int kk = 0; kk < 4; kk++)
        mma128<1, 0>(d, da0 + ((OFF_W1 >> 4) + s * (WQKV_BYTES >> 4) + j * 512 + kk * 128), da0 + (s * (SLOT >> 4) + kk * 2), kk ? 1 : sc);
    };
    PROF_C(wt == 0, 1 + wg * 8);
#pragma unroll 1
    for (int g = 0; g < 15; g++) {
      mbar_wait(sb + BAR_FULL + (g & 7) * 8, g >> 3);
      if (g == 0) PROF_C(wt == 0, 2 + wg * 8);
      wg_fence();
      proj(ak, 1, g & 3, g);
      wg_commit();
      wg_wait<1>();
      if (g) mbar_arrive_warp(sb + BAR_EMPTY + (g - 1 & 7) * 8);
      if (g == 14) break;
      if (SP && g == 0) mbar_wait(sb + BAR_SP, 0);
      wg_fence();
      proj(av, 2, g & 3, g);
      proj(pq, 0, g & 3, g);
      wg_commit();
    }
    const uint32_t qa = sb + OFF_PK + ((lane >> 4) * 8 + (lane & 7)) * 128 + (((2 * w + ((lane >> 3) & 1)) ^ (lane & 7)) << 4);
    auto finish = [&](auto reorder) {
      constexpr int re = decltype(reorder)::value, vk = re ? VK1 : VK, mm = re ? MM1 : MM, kl = re ? KL1 : KL, qw = re ? QW1 : 0;
      float c[36];
      uint32_t pk[8][4];
      if (!re) {
        wg_fence();
        proj(av, 2, 2, 1);
        proj(pq, 0, 2, 1);
        wg_commit();
      }
      mbar_wait(sb + BAR_FULL + 7 * 8, 1);
      wg_fence();
      proj(ak, 1, 3, 1);
      wg_commit();
      if (!re) {
        wg_wait<1>();
        mbar_arrive_warp(sb + BAR_EMPTY + 6 * 8);
      }
      wg_fence();
      if (re) proj(av, 2, 2, 1);
      proj(av, 2, 3, 1);
      wg_commit();
      if (!re) {
        proj(pq, 0, 3, 1);
        wg_commit();
        if (wg == 0) nb_arrive(NB_ORDER_12, 256);
      }
      mbar_wait(sb + BAR_IDX, 0);
      if (wg == 1) nb_sync(NB_STG, 256);
      wg_wait<2 - re>();
      pin(ak);
      PROF_C(wt == 0, 3 + wg * 8);
      const uint32_t va = sb + OFF_V + (w * 16 + (lane & 15)) * 128;
      uint32_t lk[8];
#pragma unroll
      for (int u = 0; u < kl; u++) lk[u] = 0x3FB8AA3Bu;
#pragma unroll
      for (int u = 0; u < 8; u++) {
        if (re && (u == Q0 || u == Q0 + QS)) {
          wg_fence();
          proj(pq, 0, u == Q0 ? 3 - re : 3, 1);
          wg_commit();
          if (wg == 0 && u != Q0) nb_arrive(NB_ORDER_12, 256);
          if (qw) {
            wg_wait<7>();
            const uint32_t l = lds32(sb + OFF_MISC + 20);
#pragma unroll
            for (int t = u; t < u + kl && t < 8; t++) lk[t] = l;
          }
        }
#pragma unroll
        for (int i = 0; i < 4; i++) pk[u][i] = phi2(ak[8 * u + 2 * i], ak[8 * u + 2 * i + 1], __uint_as_float(lk[u]));
        if (u == vk) { wg_wait<re ? (vk >= Q0) + (vk >= Q0 + QS) : 1>(); pin(av); }
        if (u == M0 && re) { wg_wait<(M0 >= Q0 + QS)>(); mbar_arrive_warp(sb + BAR_EMPTY + 6 * 8); }
        if (u == mm) { wg_wait<0>(); mbar_arrive_warp(sb + BAR_EMPTY + 7 * 8); }
        const uint32_t z = mism(pk[u][0], pk[u][1], 0) | mism(pk[u][2], pk[u][3], 0);
#pragma unroll
        for (int t = u < vk ? 8 : (u - vk) * 8 / (8 - vk); t < (u - vk + 1) * 8 / (8 - vk); t++) {
          const float* v = &av[8 * t];
          stsm4(va + (t >> 2) * 9216 + ((((lane >> 4) + 2 * (t & 3)) ^ (lane & 7)) << 4) + (z & zero), pack2(v[0], v[1]), pack2(v[2], v[3]), pack2(v[4], v[5]), pack2(v[6], v[7]));
        }
        if (u + kl < 8) lk[u + kl] = lds32(sb + OFF_MISC + 20 + (u < vk ? z & zero : 0));
      }
      fence_async_smem();
      nb_sync(nb_self, 128);
      PROF_C(wt == 0, 8 + wg * 8);
      const uint64_t dv = mkdesc(sb + OFF_V, 16, 1024, 1);
      wg_fence();
#pragma unroll
      for (int kk = 0; kk < 8; kk++) mma_ktv(c, pk[kk], dv + ((kk >> 2) * 576 + (kk & 3) * 2), kk ? 1 : 0);
      wg_commit();
      if (wg == 1) nb_arrive(NB_ORDER_3O, 256);
      pin(pq);
#pragma unroll
      for (int u = 0; u < QE; u++)
        stsm4t(qa + u * 2048, phi2(pq[8 * u], pq[8 * u + 1]), phi2(pq[8 * u + 2], pq[8 * u + 3]), phi2(pq[8 * u + 4], pq[8 * u + 5]), phi2(pq[8 * u + 6], pq[8 * u + 7]));
      wg_wait<0>();
      pin(c);
#pragma unroll
      for (int i = 0; i < 64; i++) aq[i] = pq[i];
      PROF_C(wt == 0, 4 + wg * 8);
#pragma unroll
      for (int i = 0; i < 8; i++) {
        const int j = (i & 3) * 4 + (i >> 2) * 2;
        su[i] = w >= 2 ? pack2(c[16 + j], c[17 + j]) : pack2(c[j], c[j + 1]);
      }
      su[8] = pack2(c[32], c[34]);
#pragma unroll
      for (int u = 0; u < 3; u++)
        if (u < R0 || wg) red_add_bf(kvacc + u * 128, su[3 * u], su[3 * u + 1], su[3 * u + 2]);
    };
    if (TR == 2) {
      if (wg == 0) finish(std::integral_constant<int, 0>());
      else finish(std::integral_constant<int, 1>());
    } else finish(std::integral_constant<int, TR>());
    const uint32_t par = lds32(sb + OFF_MISC + 24);
    {
      const bool paired = PAIRED && ld_relaxed(&gs->block[cta ^ 1]) == (blockIdx.x ^ 1);
      uint4 kv[3];
      int tries = wg ? 0 : TRY_A;
      const uint8_t* gl = smem + OFF_MISC + 20;
      asm volatile("" : "+l"(gl));
      const uint32_t l2e = ld_generic(gl);
    auto stage_kv = [&]() {
      const uint32_t kb = sb + OFF_KVB + w * 256, ka = kb + (lane & 3) * KVB_N + (lane >> 2) * 16;
      sts128(ka, kv[0].x, kv[0].y, kv[0].z, kv[1].x);
      sts128(ka + 128, kv[1].y, kv[1].z, kv[2].x, kv[2].y);
      sts32(kb + 4 * KVB_N + lane * 4, dup_lo(kv[2].z));
      sts32(kb + 4 * KVB_N + 128 + lane * 4, dup_hi(kv[2].z));
      return __all_sync(~0u, (kv[0].w & kv[1].w & kv[2].w) == 0x41804180u && (kv[0].w | kv[1].w | kv[2].w) == 0x41804180u);
    };
      bool have = false;
      uint32_t lq[8];
#pragma unroll
      for (int u = QE; u < QE + QA && u < 8; u++) lq[u] = l2e;
#pragma unroll
      for (int u = QE; u < 8; u++) {
        uint32_t r[4];
        if (u == KF && wg) {
#pragma unroll
          for (int i = 0; i < 3; i++) kv[i] = ld_relaxed4(kvacc + i * 128);
        }
#pragma unroll
        for (int i = 0; i < 4; i++) r[i] = phi2(aq[8 * u + 2 * i], aq[8 * u + 2 * i + 1], __uint_as_float(lq[u]));
        stsm4t(qa + u * 2048, r[0], r[1], r[2], r[3]);
        const int ru = (u - QE) / RS + R0;
        if ((u - QE) % RS == RS - 1 && ru < 3 && !wg) red_add_bf(kvacc + ru * 128, su[3 * ru], su[3 * ru + 1], su[3 * ru + 2]);
        if (u + QA < 8) lq[u + QA] = lds32(sb + OFF_MISC + 20);
        if (u == KU && wg) have = stage_kv();
      }
      PROF_C(wt == 0, 34 + wg * 2);
      if (KU > 7 && KF < 8 && wg) have = stage_kv();
      for (; !have; tries++) {
        if (tries > RETRY)
          while (ld_relaxed((const unsigned*)&(kvacc - lane)[256 + 31].w) != 0x41804180u) __nanosleep(wg ? KV_SLEEP : KV_SLEEP_A);
#pragma unroll
        for (int i = 0; i < 3; i++) kv[i] = ld_relaxed4(kvacc + i * 128);
        have = stage_kv();
      }
      PROF_C(wt == 0, 5 + wg * 8);
      if (EF == 4 && wg && elect()) red_add(gs->cnt[16 + tm], 1u << tn * 4);
      fence_async_smem();
      nb_sync(nb_self, 128);
      float o[2][2][20];
      const uint64_t dq = mkdesc(sb + OFF_PK, 16, 1024, 1), dz = mkdesc(sb + OFF_KVB, 128, KVB_N, 0);
      wg_fence();
#pragma unroll
      for (int m = 0; m < 2; m++) {
#pragma unroll
        for (int h = 0; h < 2; h++)
#pragma unroll
          for (int kk = 0; kk < 2; kk++) mma_qkvz(o[m][h], dq + (m * 512 + h * 4 + kk * 2), dz + (h * 32 + kk * 16), kk);
        wg_commit();
      }
      if (HOLD < 8 && HP == 0 && wg) nb_arrive(NB_HOLD, 256);
      if (EF == 3 && wg && elect()) red_add(gs->cnt[16 + tm], 1u << tn * 4);
      uint32_t tag[2][4];
#pragma unroll
      for (int i = 0; i < 8; i++) tag[i >> 2][i & 3] = (lane >> 3) == (i & 3) && ((lane ^ (lane >> 3)) & 1) == (i >> 2);
      uint32_t gr[8];
      const uint8_t* ga = smem + OFF_G + (w * 16 + (lane >> 2)) * 4;
      asm volatile("" : "+l"(ga));
#pragma unroll
      for (int i = 0; i < OA; i++) gr[i] = ld_generic(ga + (i >> 2) * 256 + (i & 1) * 32);
      const uint32_t oo = w * 1024 + (lane >> 2) * 64 + (((lane ^ (lane >> 3)) & 3) << 4);
      uint8_t* const og = (uint8_t*)gs->o[tm][wg * 8 + tn] + oo;
      uint32_t ob[8][4];
#pragma unroll
      for (int m = 0; m < 2; m++) {
        if (m == 0) wg_wait<1>(); else wg_wait<0>();
        pin(o[m][0]); pin(o[m][1]);
        if (EF == 2 - m && wg && elect()) red_add(gs->cnt[16 + tm], 1u << tn * 4);
        if (PB == 2 - m && wg) mbar_arrive_warp(sb + BAR_PUB + 8);
        if (m && !wg) nb_arrive(NB_STG, 256);
        if (HOLD < 8 && HP == 1 && m && wg) nb_arrive(NB_HOLD, 256);
        if (m && wg && paired && elect()) mbar_arrive_peer(peer_addr(sb + BAR_PA));
        if (m == 0) PROF_C(wt == 0, 6 + wg * 8);
#pragma unroll
        for (int u = 0; u < 4; u++) {
          const int h = u >> 1, i = u & 1;
          const float* on = o[m][h];
          const float sc = __uint_as_float(gr[m * 4 + u]) * rcp(on[16 + 2 * i] + 1e-6f);
          const uint32_t sc2 = pack2(sc, sc);
#pragma unroll
          for (int j = 0; j < 4; j++) {
            const uint32_t v = HS ? mul_bf2(pack2(on[4 * j + 2 * i], on[4 * j + 2 * i + 1]), sc2) : pack2(on[4 * j + 2 * i] * sc, on[4 * j + 2 * i + 1] * sc);
            asm("lop3.b32 %0, %1, %2, %3, 0xB8;" : "=r"(ob[m * 4 + u][j]) : "r"(v), "r"(tag[i][j]), "r"(par));
          }
          st_relaxed4(og + (h * 8192 + m * 4096 + i * 512), ob[m * 4 + u]);
          if (OWN1 == 2 && wg) sts128(sb + OFF_V + oo + (h * 8192 + m * 4096 + i * 512), ob[m * 4 + u][0], ob[m * 4 + u][1], ob[m * 4 + u][2], ob[m * 4 + u][3]);
          if (HOLD < 8 && HP == 10 + m * 4 + u && wg) nb_arrive(NB_HOLD, 256);
          const int n = m * 4 + u + OA;
          if (n < 8) gr[n] = ld_generic(ga + (n >> 2) * 256 + (n & 1) * 32);
        }
      }
      if ((!EF || !wg) && elect()) red_add(gs->cnt[wg * 16 + tm], 1u << tn * 4);
      if (!PB || !wg) mbar_arrive_warp(sb + BAR_PUB + wg * 8);
      if (HOLD < 8 && HP == 2 && wg) nb_arrive(NB_HOLD, 256);
      PROF(wt == 0, 17 + wg);
      if (wg) {
        auto to_peer = [&]() {
        if (paired) {
          const uint32_t pb = peer_addr(sb);
          mbar_wait(sb + BAR_PA, 0);
#pragma unroll
          for (int u = 0; u < 8; u++) st_async4(pb + OFF_PK + oo + ((u >> 1 & 1) * 8192 + (u >> 2) * 4096 + (u & 1) * 512), ob[u], pb + BAR_PEER);
        }
        };
        if (!OWN1) to_peer();
#pragma unroll
        for (int u = 0, z = 0; u < (OWN1 == 2 ? 0 : 8); u++) {
          sts128(sb + OFF_V + oo + ((u >> 1 & 1) * 8192 + (u >> 2) * 4096 + (u & 1) * 512) + z, ob[u][0], ob[u][1], ob[u][2], ob[u][3]);
          if (PO && u % PO == PO - 1 && u < 7) z = lds32(sb + OFF_ONES) & 16;
        }
        fence_async_smem();
        __syncwarp();
        mbar_arrive_warp(sb + BAR_OWN);
        if (HOLD < 8 && HP == 3) nb_arrive(NB_HOLD, 256);
        PROF(wt == 0, 15);
        if (OWN1) to_peer();
      }
    }
    if (wg == 1) {
      verify_tiles<1>(sb, gs, tm, tn, w, lane);
    } else {
      float acc[2][64];
      nb_sync(NB_ORDER_3O, 256);
      PROF_C(wt == 0, 26);
      uint32_t xr[2][8][4], q[2][2];
      const uint32_t ta = sb + OFF_RES + (uint32_t)(w * 16 + (lane & 15)) * 128;
      const uint64_t do0 = mkdesc(sb + OFF_RING, 16, 512, 2);
      uint64_t xs = OA_SLOTS, ws = OW_SLOTS;
#pragma unroll 1
      for (int g = 0; g < 13 - TL; g++, xs >>= 4, ws >>= 4) {
        const uint32_t r = g * 52 >> 8, s = g - r * 5;
        const uint64_t da = do0 + ((uint32_t)xs & 15) * (SLOT >> 4), db = db0 + ((uint32_t)ws & 15) * (SLOT >> 4);
        if (g == OWN) mbar_wait(sb + BAR_OWN, 0);
        if (g == PEER) { mbar_wait(sb + BAR_PEER, 0); fence_async_smem(); }
        if (g == HOLD) {
          if (HR) { wg_wait<0>(); mbar_arrive_warp(sb + BAR_OEMPTY + (HOLD + 4) % 5 * 8); }
          nb_sync(NB_HOLD, 256);
        }
        mbar_wait(sb + BAR_OFULL + s * 8, r & 1);
        wg_fence();
#pragma unroll
        for (int kk = 0; kk < 4; kk++)
#pragma unroll
          for (int m = 0; m < 2; m++) mma128<0, 1>(acc[m], da + (m * 256 + (kk >> 1) * 512 + (kk & 1) * 2), db + kk * 128, kk ? 1 : g);
        wg_commit();
        wg_wait<1>();
        if (g && (g != HOLD || !HR)) mbar_arrive_warp(sb + BAR_OEMPTY + (s ? s - 1 : 4) * 8);
      }
      mbar_wait(sb + BAR_X, 0);
      const int selw = ((0xFFFF - (int)(lds32(sb + OFF_MISC + 16) & 0xFFFF)) >> 4) - tm * 8 - w;
#pragma unroll
      for (int u = 0; u < 4; u++) {
        const int m = u >> 1, g = 13 - TL + u;
        const float g1 = 1.f - __uint_as_float(lds32(sb + OFF_G + (m * 64 + w * 16 + (u & 1) * 8 + (lane >> 2)) * 4));
        q[m][u & 1] = pack2(g1, g1);
#pragma unroll
        for (int j = 0; j < 4; j++) ldsm4(ta + (u & 1) * RES_H + m * 8192 + ((((lane >> 4) + 2 * j) ^ (lane & 7)) << 4), xr[m][(u & 1) * 4 + j]);
        if (u == 3) break;
        mbar_wait(sb + BAR_OFULL + g % 5 * 8, g / 5 & 1);
        wg_fence();
#pragma unroll
        for (int kk = 0; kk < 4; kk++)
#pragma unroll
          for (int mm = 0; mm < 2; mm++)
            mma128<0, 1>(acc[mm], do0 + ((OA_SLOTS >> g * 4 & 15) * (SLOT >> 4) + mm * 256 + (kk >> 1) * 512 + (kk & 1) * 2), db0 + ((OW_SLOTS >> g * 4 & 15) * (SLOT >> 4) + kk * 128), 1);
        wg_commit();
        wg_wait<1>();
        if (g <= 11) mbar_arrive_warp(sb + BAR_OEMPTY + (g + 4) % 5 * 8);
      }
#pragma unroll
      for (int m = 0; m < 2; m++) {
#pragma unroll
        for (int g = 16 - TL; g < 16; g++) {
          if (m == 0) { mbar_wait(sb + BAR_OFULL + g % 5 * 8, g / 5 & 1); wg_fence(); }
#pragma unroll
          for (int kk = 0; kk < 4; kk++)
            mma128<0, 1>(acc[m], do0 + ((OA_SLOTS >> g * 4 & 15) * (SLOT >> 4) + m * 256 + (kk >> 1) * 512 + (kk & 1) * 2), db0 + ((OW_SLOTS >> g * 4 & 15) * (SLOT >> 4) + kk * 128), 1);
        }
        wg_commit();
      }
      mbar_arrive_warp(sb + BAR_DONE);
      const uint32_t tb = sb + OFF_RES + w * 2048 + (lane >> 3) * 128 + (((lane ^ (lane >> 3)) & 7) << 4), tx = lane & 4 ? 64 : -64;
      uint8_t* const og = (uint8_t*)pout + (size_t)(tm * 128 + w * 16 + (lane >> 3)) * 2048 + tn * 256 + (lane & 7) * 16;
#pragma unroll
      for (int m = 0; m < 2; m++) {
        if (selw == 4 * m) {
          mbar_wait(sb + BAR_Y, 0);
#pragma unroll
          for (int j = 0; j < 8; j++) ldsm4(ta + (j >> 2) * RES_H + m * 8192 + ((((lane >> 4) + 2 * (j & 3)) ^ (lane & 7)) << 4), xr[m][j]);
        }
        if (m == 0) wg_wait<1>(); else wg_wait<0>();
        if (m) PROF(wt == 0, 31);
#pragma unroll
        for (int h = 0; h < 2; h++) {
#pragma unroll
          for (int j = 4 * h; j < 4 * h + 4; j++) {
            const float* v = &acc[m][8 * j];
            stsm4(ta + h * RES_H + m * 8192 + ((((lane >> 4) + 2 * (j & 3)) ^ (lane & 7)) << 4),
                  fma_bf2(xr[m][j][0], q[m][0], pack2(v[0], v[1])), fma_bf2(xr[m][j][1], q[m][1], pack2(v[2], v[3])),
                  fma_bf2(xr[m][j][2], q[m][0], pack2(v[4], v[5])), fma_bf2(xr[m][j][3], q[m][1], pack2(v[6], v[7])));
          }
          if (FS >> m & 1) {
            __syncwarp();
            uint4 t[4];
#pragma unroll
            for (int j = 0; j < 4; j++) t[j] = lds128(tb + h * RES_H + m * 8192 + j * 512 - (j & 1) * tx);
#pragma unroll
            for (int j = 0; j < 4; j++) *(uint4*)(og + (m * 64 + j * 4) * 2048 + h * 128) = t[j];
          } else {
            fence_async_smem();
            __syncwarp();
            if (elect()) tma2d_store(&p.out, sb + OFF_RES + h * RES_H + m * 8192 + w * 2048, tn * 128 + h * 64, tm * 128 + m * 64 + w * 16);
          }
          if (FS != 3 && m && h && elect()) { bulk_commit(); asm volatile("cp.async.bulk.wait_group.read 0;" ::: "memory"); }
        }
        if (!m) PROF(wt == 0, 33);
      }
      PROF(wt == 0, 32);
    }
  }
}

typedef CUresult (*EncodeFn)(CUtensorMap*, CUtensorMapDataType, cuuint32_t, void*, const cuuint64_t*, const cuuint64_t*, const cuuint32_t*,
                             const cuuint32_t*, CUtensorMapInterleave, CUtensorMapSwizzle, CUtensorMapL2promotion, CUtensorMapFloatOOBfill);

void encode(EncodeFn fn, CUtensorMap* m, const void* ptr, int rank, const cuuint64_t* dims, const cuuint64_t* strides, const cuuint32_t* box,
            CUtensorMapSwizzle sw, CUtensorMapDataType dt = CU_TENSOR_MAP_DATA_TYPE_BFLOAT16) {
  const cuuint32_t es[3] = {1, 1, 1};
  fn(m, dt, rank, const_cast<void*>(ptr), dims, strides, box, es, CU_TENSOR_MAP_INTERLEAVE_NONE, sw,
     CU_TENSOR_MAP_L2_PROMOTION_L2_128B, CU_TENSOR_MAP_FLOAT_OOB_FILL_NONE);
}

}

extern "C" void kernel_launch(void* const* d_in, const int* in_sizes, int n_in, void* d_out, int out_size) {
  (void)in_sizes; (void)n_in; (void)out_size;
  EncodeFn fn = nullptr;
  cudaDriverEntryPointQueryResult qr;
  cudaGetDriverEntryPoint("cuTensorMapEncodeTiled", (void**)&fn, cudaEnableDefault, &qr);

  Params p;
  {
    const cuuint64_t dims[2] = {D_, S_}, str[1] = {D_ * 2};
    const cuuint32_t box[2] = {64, 128}, box_st[2] = {64, 16}, box_r[2] = {256, 16};
    encode(fn, &p.xr, d_in[0], 2, dims, str, box_r, CU_TENSOR_MAP_SWIZZLE_NONE);
    encode(fn, &p.x, d_in[0], 2, dims, str, box, CU_TENSOR_MAP_SWIZZLE_128B);
    encode(fn, &p.out, d_out, 2, dims, str, box_st, CU_TENSOR_MAP_SWIZZLE_128B);
  }
  {
    const cuuint64_t dims[3] = {D_, D_, 3}, str[2] = {3 * D_ * 2, D_ * 2};
    const cuuint32_t box[3] = {64, 64, 3};
    encode(fn, &p.w, d_in[1], 3, dims, str, box, CU_TENSOR_MAP_SWIZZLE_128B);
    const cuuint32_t box1[3] = {64, 64, 1};
    encode(fn, &p.w1, d_in[1], 3, dims, str, box1, CU_TENSOR_MAP_SWIZZLE_128B);
  }
  {
    const cuuint64_t dims[3] = {64, D_, D_ / 64}, str[2] = {D_ * 2, 128};
    const cuuint32_t box[3] = {64, 64, 2};
    encode(fn, &p.wo, d_in[2], 3, dims, str, box, CU_TENSOR_MAP_SWIZZLE_128B);
  }
  {
    const cuuint64_t dims[3] = {F_, D_ / 4, 4}, str[2] = {F_ * 8, F_ * 2};
    const cuuint32_t box[3] = {32, 16, 4};
    encode(fn, &p.gate, d_in[5], 3, dims, str, box, CU_TENSOR_MAP_SWIZZLE_NONE);
    encode(fn, &p.up, d_in[6], 3, dims, str, box, CU_TENSOR_MAP_SWIZZLE_NONE);
  }
  {
    const cuuint64_t dims[3] = {D_ / 4, F_, 2}, str[2] = {D_ * 2, D_};
    const cuuint32_t box[3] = {256, 4, 2};
    encode(fn, &p.down, d_in[7], 3, dims, str, box, CU_TENSOR_MAP_SWIZZLE_NONE, CU_TENSOR_MAP_DATA_TYPE_UINT32);
  }
  void* gs = nullptr;
  cudaGetSymbolAddress(&gs, g_scratch);
  typedef const __nv_bfloat16* bp;
  int dev = 0, sms = 0;
  cudaGetDevice(&dev);
  cudaDeviceGetAttribute(&sms, cudaDevAttrMultiProcessorCount, dev);
  const bool by_sm = BYSM && sms == NGRID;
  const auto kernel = by_sm ? fused_kernel<true> : fused_kernel<false>;
  cudaFuncSetAttribute(kernel, cudaFuncAttributeMaxDynamicSharedMemorySize, SMEM_BYTES);
  kernel<<<by_sm ? NGRID : NCTA, NTHREADS, SMEM_BYTES, cudaStreamPerThread>>>((bp)d_in[0], (Scratch*)gs, (bp)d_in[5], (bp)d_in[6], (bp)d_in[4], (bp)d_in[8], (__nv_bfloat16*)d_out, p);
}
```

```cpp
#include <cuda_runtime.h>
#include <cuda.h>
#include <cuda_bf16.h>
#include <stdint.h>
#include <stddef.h>
#include <type_traits>

namespace {

constexpr int S_ = 2048, D_ = 1024, F_ = 3584;
constexpr int NCTA = 128, NGRID = 132, NTHREADS = 512;
#define NOMOD 0
constexpr int MOD_CTAS = NOMOD ? 0 : F_ / 32;

#define PRE 2
#define ST1 700
#define RT_G0 2
#define RT_ROT 1
#define RT_SLEEP 500
#define PF_MOD 7
#define MOD_START 9
#define MM 3
#define PO 2
#define A_SLEEP 128
#define KU 99
#define HS 1
#define HOLD 5
#define OWN1 2
#define KF 6
#define QA 3
#define R0 1
#define OA 3
#define Y_SLEEP 200
#define TRY_A 9
#define VK 1
#define TR 2
#define Q0 0
#define QS 2
#define QW1 0
#define VK1 2
#define MM1 5
#define KL1 2
#define M0 3
#define HP 1
#define FS 2
#define SP 1
#define E7 1
#define ST0 1600
#define QE 1
#define RM 1
#define PW 99
#define PV 0
#define PS 1
#define KL 3
#define RS 2
#define RETRY 1
#define KV_SLEEP_A 64
#define KV_SLEEP 50
#define TL 3
#define EF 3
#define PB 1
#define B_SLEEP 32
#define HR 0
#define PAIRED 1
#define BYSM 1

constexpr uint32_t SLOT = 16384, WQKV_BYTES = 24576;
constexpr int MOD_BUFS = 3, MOD_BUFS0 = MOD_BUFS + 2;
static_assert(MOD_START + MOD_BUFS0 <= 16, "first FFN round is requested during W1");
constexpr uint32_t OFF_RING = 0, OFF_W1 = 4 * SLOT;
constexpr uint64_t OA_SLOTS = 0x0AB210AB21098210ull, OW_SLOTS = 0x4376543765437654ull;
constexpr uint32_t OFF_RES = OFF_RING + 8 * SLOT, RES_H = SLOT;
constexpr uint32_t OFF_PK = 10 * SLOT;
constexpr uint32_t OFF_V = 11 * SLOT;
constexpr uint32_t OFF_ONES = OFF_V + 9216 + 8192;
constexpr uint32_t MOD_STEP = 9216, OFF_MOD = OFF_V + 2 * MOD_STEP;
constexpr __host__ __device__ uint32_t res_off(int h, int m) { return !RM ? OFF_RES + h * RES_H + m * 8192 : h & m ? OFF_RES : OFF_MOD + (h * 2 + m) * MOD_STEP; }
constexpr uint32_t OFF_XSEL = OFF_MOD + 8192;
constexpr uint32_t OFF_KVB = OFF_MOD + 2 * MOD_STEP + 8192;
constexpr uint32_t KVB_N = 1056;
constexpr uint32_t OFF_G = OFF_KVB + 4 * KVB_N + 1024;
constexpr uint32_t OFF_PART = OFF_G + 512;
constexpr uint32_t OFF_MISC = OFF_PART + 576;
constexpr uint32_t OFF_BAR = OFF_MISC + 32;
constexpr uint32_t SMEM_BYTES = OFF_BAR + 488;
constexpr uint32_t BAR_FULL = OFF_BAR, BAR_Y = BAR_FULL + 64, BAR_X = BAR_Y + 8, BAR_PEER = BAR_X + 8, BAR_GATE = BAR_PEER + 8, BAR_RT = BAR_GATE + 8,
                   BAR_FIX = BAR_RT,
                   BAR_MFULL = BAR_FIX + 32, BAR_LAND = BAR_FULL,
                   BAR_EMPTY = OFF_BAR + 28 * 8, BAR_OEMPTY = BAR_EMPTY + 64, BAR_RTD = BAR_OEMPTY + 40, BAR_DONE = BAR_RTD + 8,
                   BAR_OWN = BAR_DONE + 8, BAR_PA = BAR_OWN + 8, BAR_PUB = BAR_PA + 8, BAR_MEMPTY = BAR_PUB + 16,
                   BAR_IDX = BAR_MEMPTY + 8,
                   BAR_OFULL = OFF_BAR + 52 * 8, BAR_SP = OFF_BAR + 60 * 8;
static_assert(BAR_MFULL + MOD_BUFS0 * 8 <= BAR_EMPTY && BAR_MEMPTY + MOD_BUFS0 * 8 == BAR_OFULL, "barrier groups");
static_assert(SMEM_BYTES <= 232448, "smem");
static_assert(TL == 3 && PRE == 2, "schedule");

constexpr int NB_WG0 = 1, NB_ORDER_12 = 3, NB_ORDER_3O = 4, NB_STG = 5, NB_MODW = 6, NB_KEY = 7, NB_HOLD = 8;

struct Scratch {
  uint4 kv[2][8][3][128];
  float4 y[2][3][128];
  unsigned cnt[32][32];
  unsigned gslot[S_];
  unsigned rslot[8][NCTA];
  unsigned spare[128];
  unsigned block[NCTA];
  uint4 o[16][16][1024];
};
static_assert(offsetof(Scratch, gslot) == NCTA * 56 * 16, "clear size");
__device__ __align__(1024) Scratch g_scratch;

#define PROF(cond, i) do {} while (0)
#define PROF_C(cond, i) do {} while (0)

__device__ __forceinline__ void mbar_init(uint32_t bar, int cnt) { asm volatile("mbarrier.init.shared::cta.b64 [%0], %1;" ::"r"(bar), "r"(cnt)); }
__device__ __forceinline__ void mbar_expect_tx(uint32_t bar, uint32_t bytes) { asm volatile("mbarrier.arrive.expect_tx.shared::cta.b64 _, [%0], %1;" ::"r"(bar), "r"(bytes) : "memory"); }
__device__ __forceinline__ void mbar_arrive(uint32_t bar) { asm volatile("mbarrier.arrive.shared::cta.b64 _, [%0];" ::"r"(bar) : "memory"); }
__device__ __forceinline__ uint32_t peer_addr(uint32_t a) {
  uint32_t r;
  asm volatile("{\n.reg .u32 c;\nmov.u32 c, %%cluster_ctarank;\nxor.b32 c, c, 1;\nmapa.shared::cluster.u32 %0, %1, c;\n}" : "=r"(r) : "r"(a));
  return r;
}
__device__ __forceinline__ void mbar_arrive_peer(uint32_t bar) { asm volatile("mbarrier.arrive.shared::cluster.b64 _, [%0];" ::"r"(bar) : "memory"); }
__device__ __forceinline__ uint32_t mism(uint32_t a, uint32_t b, uint32_t p) {
  uint32_t r; asm("lop3.b32 %0, %1, %2, %3, 0x7E;" : "=r"(r) : "r"(a), "r"(b), "r"(p)); return r;
}
__device__ __forceinline__ bool elect() {
  uint32_t r;
  asm volatile("{\n.reg .pred p;\nelect.sync _|p, 0xffffffff;\nselp.u32 %0, 1, 0, p;\n}" : "=r"(r));
  return r;
}
__device__ __forceinline__ uint32_t fresh_tid() { uint32_t r; asm volatile("mov.u32 %0, %%tid.x;" : "=r"(r)); return r; }
__device__ __forceinline__ void mbar_arrive_warp(uint32_t bar) {
  asm volatile("{\n.reg .pred p;\nelect.sync _|p, 0xffffffff;\n@p mbarrier.arrive.shared::cta.b64 _, [%0];\n}" ::"r"(bar) : "memory");
}
__device__ __forceinline__ void mbar_wait(uint32_t bar, uint32_t parity) {
  asm volatile("{\n.reg .pred p;\nWAIT_L:\nmbarrier.try_wait.parity.shared::cta.b64 p, [%0], %1;\n@p bra DONE_L;\nbra WAIT_L;\nDONE_L:\n}"
               ::"r"(bar), "r"(parity) : "memory");
}
__device__ __forceinline__ uint32_t mbar_try(uint32_t bar, uint32_t parity) {
  uint32_t ok;
  asm volatile("{\n.reg .pred p;\nmbarrier.try_wait.parity.shared::cta.b64 p, [%1], %2;\nselp.u32 %0, 1, 0, p;\n}" : "=r"(ok) : "r"(bar), "r"(parity) : "memory");
  return ok;
}
__device__ __forceinline__ uint32_t mbar_test(uint32_t bar, uint32_t parity) {
  uint32_t ok;
  asm volatile("{\n.reg .pred p;\nmbarrier.test_wait.parity.shared::cta.b64 p, [%1], %2;\nselp.u32 %0, 1, 0, p;\n}" : "=r"(ok) : "r"(bar), "r"(parity) : "memory");
  return ok;
}
constexpr unsigned long long WATCHDOG_NS = 2000000000ull;
__device__ __forceinline__ unsigned long long gtime() { unsigned long long t; asm volatile("mov.u64 %0, %%globaltimer;" : "=l"(t)); return t; }
__device__ __forceinline__ uint32_t clock32() { uint32_t t; asm volatile("mov.u32 %0, %%clock;" : "=r"(t)); return t; }
__device__ __forceinline__ void mbar_wait_bounded(uint32_t bar, uint32_t parity) {
  unsigned long long t0 = 0;
  for (;;) {
    uint32_t ok;
    asm volatile("{\n.reg .pred p;\nmbarrier.try_wait.parity.shared::cta.b64 p, [%1], %2;\nselp.u32 %0, 1, 0, p;\n}" : "=r"(ok) : "r"(bar), "r"(parity) : "memory");
    if (ok) break;
    const unsigned long long t1 = gtime();
    if (t0 == 0) t0 = t1;
    if (t1 - t0 > WATCHDOG_NS) __trap();
  }
}
__device__ __forceinline__ void tma2d(uint32_t dst, const CUtensorMap* m, int c0, int c1, uint32_t bar) {
  asm volatile("cp.async.bulk.tensor.2d.shared::cluster.global.mbarrier::complete_tx::bytes [%0], [%1, {%3, %4}], [%2];"
               ::"r"(dst), "l"(m), "r"(bar), "r"(c0), "r"(c1) : "memory");
}
__device__ __forceinline__ void tma3d(uint32_t dst, const CUtensorMap* m, int c0, int c1, int c2, uint32_t bar) {
  asm volatile("cp.async.bulk.tensor.3d.shared::cluster.global.mbarrier::complete_tx::bytes [%0], [%1, {%3, %4, %5}], [%2];"
               ::"r"(dst), "l"(m), "r"(bar), "r"(c0), "r"(c1), "r"(c2) : "memory");
}
__device__ __forceinline__ void bulk_load(uint32_t dst, const void* src, uint32_t bytes, uint32_t bar) {
  asm volatile("cp.async.bulk.shared::cluster.global.mbarrier::complete_tx::bytes [%0], [%1], %2, [%3];" ::"r"(dst), "l"(src), "r"(bytes), "r"(bar) : "memory");
}
__device__ __forceinline__ void bulk_store(void* dst, uint32_t src, uint32_t bytes) {
  asm volatile("cp.async.bulk.global.shared::cta.bulk_group [%0], [%1], %2;" ::"l"(dst), "r"(src), "r"(bytes) : "memory");
}
__device__ __forceinline__ void st_async4(uint32_t dst, const uint32_t (&v)[4], uint32_t bar) {
  asm volatile("st.async.shared::cluster.mbarrier::complete_tx::bytes.v4.b32 [%0], {%1, %2, %3, %4}, [%5];" ::"r"(dst), "r"(v[0]), "r"(v[1]), "r"(v[2]), "r"(v[3]), "r"(bar) : "memory");
}
__device__ __forceinline__ void bulk_commit() { asm volatile("cp.async.bulk.commit_group;" ::: "memory"); }
__device__ __forceinline__ void bulk_prefetch(const void* p, uint32_t bytes) {
  asm volatile("cp.async.bulk.prefetch.L2.global [%0], %1;" ::"l"(p), "r"(bytes) : "memory");
}
__device__ __forceinline__ void tma2d_store(const CUtensorMap* m, uint32_t src, int c0, int c1) {
  asm volatile("cp.async.bulk.tensor.2d.global.shared::cta.bulk_group [%0, {%2, %3}], [%1];" ::"l"(m), "r"(src), "r"(c0), "r"(c1) : "memory");
}
__device__ __forceinline__ void wg_fence() { asm volatile("wgmma.fence.sync.aligned;" ::: "memory"); }
__device__ __forceinline__ void wg_commit() { asm volatile("wgmma.commit_group.sync.aligned;" ::: "memory"); }
template <int N> __device__ __forceinline__ void wg_wait() { asm volatile("wgmma.wait_group.sync.aligned %0;" ::"n"(N) : "memory"); }
__device__ __forceinline__ void fence_async_smem() { asm volatile("fence.proxy.async.shared::cta;" ::: "memory"); }
__device__ __forceinline__ void fence_async_global() { asm volatile("fence.proxy.async.global;" ::: "memory"); }
__device__ __forceinline__ void fence_release() { asm volatile("fence.release.gpu;" ::: "memory"); }
__device__ __forceinline__ void fence_acquire() { asm volatile("fence.acquire.gpu;" ::: "memory"); }
__device__ __forceinline__ void nb_sync(int id, int n) { asm volatile("bar.sync %0, %1;" ::"r"(id), "r"(n) : "memory"); }
__device__ __forceinline__ void nb_arrive(int id, int n) { asm volatile("bar.arrive %0, %1;" ::"r"(id), "r"(n) : "memory"); }
__device__ __forceinline__ void stsm4(uint32_t addr, uint32_t r0, uint32_t r1, uint32_t r2, uint32_t r3) {
  asm volatile("stmatrix.sync.aligned.m8n8.x4.shared.b16 [%0], {%1, %2, %3, %4};" ::"r"(addr), "r"(r0), "r"(r1), "r"(r2), "r"(r3) : "memory");
}
__device__ __forceinline__ void stsm4t(uint32_t addr, uint32_t r0, uint32_t r1, uint32_t r2, uint32_t r3) {
  asm volatile("stmatrix.sync.aligned.m8n8.x4.trans.shared.b16 [%0], {%1, %2, %3, %4};" ::"r"(addr), "r"(r0), "r"(r1), "r"(r2), "r"(r3) : "memory");
}
__device__ __forceinline__ void st_relaxed4(void* p, const uint32_t (&v)[4]) {
  asm volatile("st.relaxed.gpu.global.v4.u32 [%0], {%1, %2, %3, %4};" ::"l"(p), "r"(v[0]), "r"(v[1]), "r"(v[2]), "r"(v[3]) : "memory");
}
__device__ __forceinline__ void sts128(uint32_t addr, uint32_t a, uint32_t b, uint32_t c, uint32_t d) {
  asm volatile("st.shared.v4.b32 [%0], {%1, %2, %3, %4};" ::"r"(addr), "r"(a), "r"(b), "r"(c), "r"(d) : "memory");
}
__device__ __forceinline__ uint32_t pack2(float lo, float hi) {
  uint32_t r; asm("cvt.rn.bf16x2.f32 %0, %1, %2;" : "=r"(r) : "f"(hi), "f"(lo)); return r;
}
__device__ __forceinline__ float bf_lo(uint32_t v) { return __uint_as_float(v << 16); }
__device__ __forceinline__ float bf_hi(uint32_t v) { return __uint_as_float(v & 0xffff0000u); }
__device__ __forceinline__ float bf_round(float v) { return __bfloat162float(__float2bfloat16_rn(v)); }
__device__ __forceinline__ void ldsm4(uint32_t addr, uint32_t (&r)[4]) {
  asm volatile("ldmatrix.sync.aligned.m8n8.x4.shared.b16 {%0, %1, %2, %3}, [%4];" : "=r"(r[0]), "=r"(r[1]), "=r"(r[2]), "=r"(r[3]) : "r"(addr) : "memory");
}
__device__ __forceinline__ uint4 lds128(uint32_t addr) {
  uint4 v; asm volatile("ld.volatile.shared.v4.u32 {%0, %1, %2, %3}, [%4];" : "=r"(v.x), "=r"(v.y), "=r"(v.z), "=r"(v.w) : "r"(addr) : "memory"); return v;
}
__device__ __forceinline__ uint2 lds64(uint32_t addr) { uint2 v; asm volatile("ld.volatile.shared.v2.u32 {%0, %1}, [%2];" : "=r"(v.x), "=r"(v.y) : "r"(addr) : "memory"); return v; }
__device__ __forceinline__ uint32_t lds32(uint32_t addr) { uint32_t v; asm volatile("ld.volatile.shared.u32 %0, [%1];" : "=r"(v) : "r"(addr) : "memory"); return v; }
__device__ __forceinline__ uint32_t ld_generic(const void* p) { uint32_t v; asm volatile("ld.volatile.u32 %0, [%1];" : "=r"(v) : "l"(p) : "memory"); return v; }
__device__ __forceinline__ void sts32(uint32_t addr, uint32_t v) { asm volatile("st.shared.u32 [%0], %1;" ::"r"(addr), "r"(v) : "memory"); }
__device__ __forceinline__ uint32_t fma_bf2(uint32_t a, uint32_t b, uint32_t c) { uint32_t r; asm("fma.rn.bf16x2 %0, %1, %2, %3;" : "=r"(r) : "r"(a), "r"(b), "r"(c)); return r; }
__device__ __forceinline__ uint32_t mul_bf2(uint32_t a, uint32_t b) { uint32_t r; asm("mul.rn.bf16x2 %0, %1, %2;" : "=r"(r) : "r"(a), "r"(b)); return r; }
__device__ __forceinline__ unsigned ld_relaxed(const unsigned* p) { unsigned v; asm volatile("ld.relaxed.gpu.global.u32 %0, [%1];" : "=r"(v) : "l"(p) : "memory"); return v; }
__device__ __forceinline__ void st_relaxed(unsigned* p, unsigned v) { asm volatile("st.relaxed.gpu.global.u32 [%0], %1;" ::"l"(p), "r"(v) : "memory"); }
__device__ __forceinline__ uint4 ld_relaxed4(const void* p) {
  uint4 v; asm volatile("ld.relaxed.gpu.global.v4.u32 {%0, %1, %2, %3}, [%4];" : "=r"(v.x), "=r"(v.y), "=r"(v.z), "=r"(v.w) : "l"(p) : "memory"); return v;
}
__device__ __forceinline__ float4 ld_relaxed_f4(const void* p) {
  float4 v; asm volatile("ld.relaxed.gpu.global.v4.f32 {%0, %1, %2, %3}, [%4];" : "=f"(v.x), "=f"(v.y), "=f"(v.z), "=f"(v.w) : "l"(p) : "memory"); return v;
}
__device__ __forceinline__ void red_add4(void* p, float a, float b, float c, float d) {
  asm volatile("red.relaxed.gpu.global.add.v4.f32 [%0], {%1, %2, %3, %4};" ::"l"(p), "f"(a), "f"(b), "f"(c), "f"(d) : "memory");
}
__device__ __forceinline__ void red_add_bf(void* p, uint32_t a, uint32_t b, uint32_t c) {
  asm volatile("red.relaxed.gpu.global.add.noftz.v4.bf16x2 [%0], {%1, %2, %3, %4};" ::"l"(p), "r"(a), "r"(b), "r"(c), "r"(0x3F803F80u) : "memory");
}
__device__ __forceinline__ void red_add(unsigned* p, unsigned v) { asm volatile("red.relaxed.gpu.global.add.u32 [%0], %1;" ::"l"(p), "r"(v) : "memory"); }
__device__ __forceinline__ float rcp(float v) { float r; asm("rcp.approx.ftz.f32 %0, %1;" : "=f"(r) : "f"(v)); return r; }
__device__ __forceinline__ float sigmoidf_(float v) { return rcp(1.f + __expf(-v)); }
__device__ __forceinline__ uint32_t phi2(float a, float b, float l2e = 1.4426950408889634f) {
  float ea, eb;
  asm("ex2.approx.ftz.f32 %0, %1;" : "=f"(ea) : "f"(a * l2e));
  asm("ex2.approx.ftz.f32 %0, %1;" : "=f"(eb) : "f"(b * l2e));
  uint32_t t = pack2(a, b), e = pack2(ea, eb), r;
  asm("max.NaN.bf16x2 %0, %0, %1;" : "+r"(t) : "r"(0x35863586u));
  asm("min.bf16x2 %0, %0, %1;" : "+r"(e) : "r"(0x3F803F80u));
  asm("add.rn.bf16x2 %0, %1, %2;" : "=r"(r) : "r"(t), "r"(e));
  return r;
}
__device__ __forceinline__ uint64_t mkdesc(uint32_t addr, uint32_t lbo, uint32_t sbo, uint32_t sw) {
  return (uint64_t)(((addr & 0x3FFFF) >> 4) | ((lbo >> 4) << 16)) | ((uint64_t)((sbo >> 4) | (sw << 30)) << 32);
}

template <int TA, int TB>
__device__ __forceinline__ void mma128(float (&d)[64], uint64_t da, uint64_t db, int sc) {
  asm volatile("{\n.reg .pred p;\nsetp.ne.b32 p, %66, 0;\n"
    "wgmma.mma_async.sync.aligned.m64n128k16.f32.bf16.bf16 "
    "{%0,%1,%2,%3,%4,%5,%6,%7,%8,%9,%10,%11,%12,%13,%14,%15,%16,%17,%18,%19,%20,%21,%22,%23,"
    "%24,%25,%26,%27,%28,%29,%30,%31,%32,%33,%34,%35,%36,%37,%38,%39,%40,%41,%42,%43,%44,%45,%46,%47,"
    "%48,%49,%50,%51,%52,%53,%54,%55,%56,%57,%58,%59,%60,%61,%62,%63}, "
    "%64, %65, p, 1, 1, %67, %68;\n}\n"
    : "+f"(d[0]), "+f"(d[1]), "+f"(d[2]), "+f"(d[3]), "+f"(d[4]), "+f"(d[5]), "+f"(d[6]), "+f"(d[7]),
      "+f"(d[8]), "+f"(d[9]), "+f"(d[10]), "+f"(d[11]), "+f"(d[12]), "+f"(d[13]), "+f"(d[14]), "+f"(d[15]),
      "+f"(d[16]), "+f"(d[17]), "+f"(d[18]), "+f"(d[19]), "+f"(d[20]), "+f"(d[21]), "+f"(d[22]), "+f"(d[23]),
      "+f"(d[24]), "+f"(d[25]), "+f"(d[26]), "+f"(d[27]), "+f"(d[28]), "+f"(d[29]), "+f"(d[30]), "+f"(d[31]),
      "+f"(d[32]), "+f"(d[33]), "+f"(d[34]), "+f"(d[35]), "+f"(d[36]), "+f"(d[37]), "+f"(d[38]), "+f"(d[39]),
      "+f"(d[40]), "+f"(d[41]), "+f"(d[42]), "+f"(d[43]), "+f"(d[44]), "+f"(d[45]), "+f"(d[46]), "+f"(d[47]),
      "+f"(d[48]), "+f"(d[49]), "+f"(d[50]), "+f"(d[51]), "+f"(d[52]), "+f"(d[53]), "+f"(d[54]), "+f"(d[55]),
      "+f"(d[56]), "+f"(d[57]), "+f"(d[58]), "+f"(d[59]), "+f"(d[60]), "+f"(d[61]), "+f"(d[62]), "+f"(d[63])
    : "l"(da), "l"(db), "r"(sc), "n"(TA), "n"(TB));
}

__device__ __forceinline__ void mma_ktv(float (&d)[36], const uint32_t (&a)[4], uint64_t db, int sc) {
  asm volatile("{\n.reg .pred p;\nsetp.ne.b32 p, %41, 0;\n"
    "wgmma.mma_async.sync.aligned.m64n72k16.f32.bf16.bf16 "
    "{%0,%1,%2,%3,%4,%5,%6,%7,%8,%9,%10,%11,%12,%13,%14,%15,%16,%17,%18,%19,%20,%21,%22,%23,"
    "%24,%25,%26,%27,%28,%29,%30,%31,%32,%33,%34,%35}, "
    "{%36,%37,%38,%39}, %40, p, 1, 1, 0;\n}\n"
    : "+f"(d[0]), "+f"(d[1]), "+f"(d[2]), "+f"(d[3]), "+f"(d[4]), "+f"(d[5]), "+f"(d[6]), "+f"(d[7]),
      "+f"(d[8]), "+f"(d[9]), "+f"(d[10]), "+f"(d[11]), "+f"(d[12]), "+f"(d[13]), "+f"(d[14]), "+f"(d[15]),
      "+f"(d[16]), "+f"(d[17]), "+f"(d[18]), "+f"(d[19]), "+f"(d[20]), "+f"(d[21]), "+f"(d[22]), "+f"(d[23]),
      "+f"(d[24]), "+f"(d[25]), "+f"(d[26]), "+f"(d[27]), "+f"(d[28]), "+f"(d[29]), "+f"(d[30]), "+f"(d[31]),
      "+f"(d[32]), "+f"(d[33]), "+f"(d[34]), "+f"(d[35])
    : "r"(a[0]), "r"(a[1]), "r"(a[2]), "r"(a[3]), "l"(db), "r"(sc));
}

__device__ __forceinline__ void mma_qkvz(float (&d)[20], uint64_t da, uint64_t db, int sc) {
  asm volatile("{\n.reg .pred p;\nsetp.ne.b32 p, %22, 0;\n"
    "wgmma.mma_async.sync.aligned.m64n40k16.f32.bf16.bf16 "
    "{%0,%1,%2,%3,%4,%5,%6,%7,%8,%9,%10,%11,%12,%13,%14,%15,%16,%17,%18,%19}, "
    "%20, %21, p, 1, 1, 0, 1;\n}\n"
    : "+f"(d[0]), "+f"(d[1]), "+f"(d[2]), "+f"(d[3]), "+f"(d[4]), "+f"(d[5]), "+f"(d[6]), "+f"(d[7]),
      "+f"(d[8]), "+f"(d[9]), "+f"(d[10]), "+f"(d[11]), "+f"(d[12]), "+f"(d[13]), "+f"(d[14]), "+f"(d[15]),
      "+f"(d[16]), "+f"(d[17]), "+f"(d[18]), "+f"(d[19])
    : "l"(da), "l"(db), "r"(sc));
}

template <int N> __device__ __forceinline__ void pin(float (&d)[N]) {
#pragma unroll
  for (int i = 0; i < N; i++) asm volatile("" : "+f"(d[i])::"memory");
}

struct Params {
  CUtensorMap x, w, w1, xr, gate, up, wo, out, down, xh;
};

__device__ __forceinline__ uint32_t dup_lo(uint32_t v) { uint32_t r; asm("{\n.reg .b16 l, h;\nmov.b32 {l, h}, %1;\nmov.b32 %0, {l, l};\n}" : "=r"(r) : "r"(v)); return r; }
__device__ __forceinline__ uint32_t dup_hi(uint32_t v) { uint32_t r; asm("{\n.reg .b16 l, h;\nmov.b32 {l, h}, %1;\nmov.b32 %0, {h, h};\n}" : "=r"(r) : "r"(v)); return r; }
__device__ __forceinline__ float butterfly8(float (&s)[8], int lane, int o) {
#pragma unroll
  for (int k = 1; k < 8; k <<= 1) {
    const bool up = lane & (o * k);
#pragma unroll
    for (int j = 0; j < 4 / k; j++) s[j] = (up ? s[2 * j + 1] : s[2 * j]) + __shfl_xor_sync(~0u, up ? s[2 * j] : s[2 * j + 1], o * k);
  }
  return s[0];
}
constexpr int OWN = 8, PEER = 9;
static_assert((OA_SLOTS >> OWN * 4 & 15) * SLOT == OFF_V && (OA_SLOTS >> PEER * 4 & 15) * SLOT == OFF_PK, "");
constexpr uint64_t OR_SLOTS = (OA_SLOTS & 0xFFFFFFFFu) | OA_SLOTS >> 40 << 32;
__device__ __forceinline__ void verify_tiles(uint32_t sb, Scratch* gs, int tm, int tn, int w, int lane) {
  const uint32_t par = lds32(sb + OFF_MISC + 24), fix = sb + BAR_FIX + w * 8;
  uint64_t slots = OR_SLOTS, full = 0x04321021043210ull;
#pragma unroll 1
  for (int i = 0; i < 14; i++, slots >>= 4, full >>= 4) {
    const uint32_t a = sb + OFF_RING + ((uint32_t)slots & 15) * SLOT + w * 1024, cw = a + lane * 32 + (lane >> 2) * 4;
    if (i == 4) mbar_wait(sb + BAR_EMPTY + 7 * 8, 1);
    mbar_wait(sb + BAR_LAND + (i & 7) * 8, i >> 3);
    if (i >> 1 == 4) PROF(w == 0 && lane == 0, 33 + i);
    for (;;) {
      const uint32_t u0 = lds32(cw), u1 = lds32(cw + 4096), u2 = lds32(cw + 8192), u3 = lds32(cw + 12288);
      if (__all_sync(~0u, !(mism(mism(u0, u1, par), mism(u2, u3, par), 0) & 1))) break;
      const uint4* src = gs->o[tm][i < 8 + (tn & 6) ? i : i + 2] + w * 64;
      const uint32_t ph = !mbar_test(fix, 1);
      fence_async_smem();
      __syncwarp();
      if (elect()) {
        mbar_expect_tx(fix, 4096);
#pragma unroll 1
        for (int j = 0; j < 4; j++) bulk_load(a + j * 4096, src + j * 256, 1024, fix);
      }
      mbar_wait(fix, ph);
    }
    mbar_arrive_warp(sb + BAR_OFULL + ((uint32_t)full & 7) * 8);
    if (i == 8) PROF(w == 3 && lane == 0, 28);
  }
}
template <bool BY_SM> struct Tile {
  int sm, tm, tn, mu;
  bool spare;
  __device__ __forceinline__ Tile() {
    if (BY_SM) asm volatile("mov.u32 %0, %%smid;" : "=r"(sm));
    else sm = blockIdx.x + (blockIdx.x >= 120) * 4;
    const int tp = sm >> 1, pr = sm & 1;
    const int v = tp < 32 ? tp : tp < 60 ? (tp * 293 - 928) >> 8 : tp * 8 - 464, g = v & 7, i = v >> 3;
    tm = (v & 6) * 2 + (i & 3); tn = (v & 1) * 4 + (v >> 4 & 2) + pr;
    mu = i == 5 ? 112 : g * 14 + (i - (i > 5)) * 2 + pr;
    spare = (tp | 1) == 61;
  }
};

template <bool BY_SM> __global__ void __cluster_dims__(2, 1, 1) __launch_bounds__(NTHREADS, 1) fused_kernel(const __nv_bfloat16* __restrict__ px, Scratch* gs, const __nv_bfloat16* __restrict__ w_gate,
             const __nv_bfloat16* __restrict__ w_up, const __nv_bfloat16* __restrict__ w_r, const __nv_bfloat16* __restrict__ gate_w, __nv_bfloat16* __restrict__ pout,
             const __grid_constant__ Params p) {
  extern __shared__ __align__(1024) uint8_t smem[];
  const uint32_t sb = __shfl_sync(~0u, (uint32_t)__cvta_generic_to_shared(smem), 0);
  const int tid = threadIdx.x, lane = tid & 31;
  const int warp = __shfl_sync(~0u, tid >> 5, 0), wg = warp >> 2;
  const uint32_t t_start = clock32();
  const Tile<BY_SM> tile;
  const int tm = tile.tm, tn = tile.tn, mu = tile.mu, cta = tm * 8 + tn;
  const uint32_t zero = tile.sm >> 12;
  if (warp == 0) {
#pragma unroll
    for (int s = 0; s < PRE; s++)
      if (elect()) mbar_init(sb + BAR_FULL + s * 8, 1);
    if (SP && elect()) mbar_init(sb + BAR_SP, 1);
    asm volatile("fence.mbarrier_init.release.cluster;" ::: "memory");
    if (!tile.spare) {
      if (SP) {
        if (elect()) tma3d(sb + OFF_W1 + 8192, &p.w1, tn * 64, 0, 1, sb + BAR_FULL);
        if (elect()) tma2d(sb + OFF_RING, &p.x, 0, tm * 128, sb + BAR_FULL);
        if (elect()) tma3d(sb + OFF_W1 + 16384, &p.w1, tn * 64, 0, 2, sb + BAR_SP);
        if (elect()) tma3d(sb + OFF_W1, &p.w1, tn * 64, 0, 0, sb + BAR_SP);
        PROF(lane == 0, 64);
      }
#pragma unroll
      for (int s = SP; s < PRE; s++) {
        if (elect()) tma3d(sb + OFF_W1 + s * WQKV_BYTES, &p.w, tn * 64, s * 64, 0, sb + BAR_FULL + s * 8);
        if (elect()) tma2d(sb + OFF_RING + s * SLOT, &p.x, s * 64, tm * 128, sb + BAR_FULL + s * 8);
        PROF(lane == 0, 64 + s);
      }
      if (elect()) {
#pragma unroll
        for (int s = 0; s < PRE; s++) mbar_expect_tx(sb + BAR_FULL + s * 8, s || !SP ? SLOT + WQKV_BYTES : SLOT + 8192);
        if (SP) mbar_expect_tx(sb + BAR_SP, 16384);
      }
    }
  }
  if (warp) {
    const int wi = warp == 15 ? 0 : warp;
    const int cnt = wi < 7 ? 1 : wi < 13 ? 4 : 5;
#pragma unroll
    for (int i = 0; i < 4; i++)
      if ((i >= PRE || wi) && elect()) mbar_init(sb + OFF_BAR + wi * 32 + i * 8, cnt);
    asm volatile("fence.mbarrier_init.release.cluster;" ::: "memory");
  }
  __syncthreads();
  if (tile.spare) {
    if (warp == 0) {
      const unsigned tag = (ld_relaxed(&gs->spare[tile.sm & 3]) + 1) & 0xFFF;
      const unsigned long long t0 = gtime();
      uint4 r4;
      do {
        __nanosleep(2048);
        if (gtime() - t0 > WATCHDOG_NS) __trap();
        r4 = ld_relaxed4(&gs->rslot[tile.sm & 3][lane * 4]);
      } while (!__all_sync(~0u, (((r4.x ^ tag) | (r4.y ^ tag) | (r4.z ^ tag) | (r4.w ^ tag)) & 0xFFF) == 0));
      if (tid == 0) st_relaxed(&gs->spare[tile.sm & 3], tag);
    }
    return;
  }

  auto patch_row = [&](int pw) {
    const unsigned key = lds32(sb + OFF_MISC + 16);
    const int sel = 0xFFFF - (int)(key & 0xFFFF) - tm * 128;
    if (pw == 0 && sel >= 0 && sel < 128) {
      const unsigned k16 = key >> 16;
      const float rs = bf_round(sigmoidf_(__uint_as_float(((k16 & 0x8000u) ? (k16 & 0x7FFFu) : (~k16 & 0xFFFFu)) << 16)));
      float v[12];
      const float4* yp = gs->y[lane >> 4][0] + tn * 16 + (lane & 15);
      for (;;) {
#pragma unroll
        for (int i = 0; i < 3; i++) {
          const float4 u = ld_relaxed_f4(yp + i * 128);
          v[4 * i] = u.x; v[4 * i + 1] = u.y; v[4 * i + 2] = u.z; v[4 * i + 3] = u.w;
        }
        const float n = v[3] + v[7] + v[11];
        if (__all_sync(~0u, n + __shfl_xor_sync(~0u, n, 16) == 3.f * MOD_CTAS)) break;
        __nanosleep(Y_SLEEP);
      }
#pragma unroll
      for (int i = 0; i < 10; i++) v[i] = bf_round(bf_round(v[i] + __shfl_xor_sync(~0u, v[i], 16)) * rs);
      PROF(lane == 0, 24);
      mbar_wait(sb + BAR_X, 0);
      if (lane < 16) {
        uint4* xp = (uint4*)(smem + res_off(lane >> 3, sel >> 6) + (sel & 63) * 128 + (((lane ^ sel) & 7) << 4));
        const uint4 xv = *xp;
        *xp = make_uint4(pack2(bf_lo(xv.x) + v[0], bf_hi(xv.x) + v[1]), pack2(bf_lo(xv.y) + v[2], bf_hi(xv.y) + v[4]),
                         pack2(bf_lo(xv.z) + v[5], bf_hi(xv.z) + v[6]), pack2(bf_lo(xv.w) + v[8], bf_hi(xv.w) + v[9]));
      }
      __syncwarp();
      mbar_arrive_warp(sb + BAR_Y);
    }
  };
  if (wg == 3) {
    asm volatile("setmaxnreg.dec.sync.aligned.u32 24;");
    if (warp == 12) {
      mbar_wait(sb + BAR_PUB, 0);
      while (!__all_sync(~0u, ld_relaxed(gs->cnt[tm]) == 0x44444444u)) __nanosleep(A_SLEEP);
      PROF(lane == 0, 7);
      mbar_wait(sb + BAR_GATE, 0);
      uint64_t slots = OR_SLOTS, deps = 0x8CBA98A9877654ull;
      uint32_t seen = ~0u;
#pragma unroll 1
      for (int i = 0; i < 14; i++, deps >>= 4, slots >>= 4) {
        const uint32_t slab = i < 8 + (tn & 6) ? i : i + 2;
        if (i == 8) { mbar_wait(sb + BAR_PUB + 8, 0); seen = 0; }
        if (!(seen >> (slab & 7) * 4 & 4))
          while (!((seen = __shfl_sync(~0u, ld_relaxed(gs->cnt[16 + tm]), 0)) >> (slab & 7) * 4 & 4)) __nanosleep(B_SLEEP);
        mbar_wait(sb + BAR_EMPTY + ((uint32_t)deps & 15) * 8, (i & 7) < 5);
        if (elect()) bulk_load(sb + OFF_RING + ((uint32_t)slots & 15) * SLOT, gs->o[tm][slab], SLOT, sb + BAR_LAND + (i & 7) * 8);
        if (elect()) mbar_expect_tx(sb + BAR_LAND + (i & 7) * 8, SLOT);
        PROF(lane == 0, 44 + i);
        if (i == 8) PROF(lane == 0, 43);
      }
    } else if (warp == 13) {
#pragma unroll 1
      for (int g = E7 ? 4 : PRE; g < 32; g++) {
        const bool reuse = (g >> 2) == 4;
        const uint32_t s = g & 3, full = sb + BAR_FULL + (g & 7) * 8, c0 = tn * 64 + (g & 16) * 32, c1 = (g < 16 ? g : g - 4 & 15) * 64;
        if (!E7 && g < 4) while ((int)(clock32() - t_start) < g * ST1) {}
        mbar_wait(sb + BAR_EMPTY + (g + 4 & 7) * 8, (g + 4 >> 3 & 1) ^ 1);
        if (!reuse && elect()) tma2d(sb + OFF_RING + s * SLOT, &p.x, c1, tm * 128, full);
        if (elect()) tma3d(sb + OFF_W1 + s * WQKV_BYTES, &p.w, c0, c1, 0, full);
        if (elect()) mbar_expect_tx(full, reuse ? WQKV_BYTES : SLOT + WQKV_BYTES);
        PROF(lane == 0, 64 + g);
        const uint32_t i = g - RT_G0;
        if (i < 4 && elect()) {
          mbar_expect_tx(sb + BAR_RT + i * 8, i ? 8192 : 8192 + 4096);
          tma2d(sb + OFF_PK + i * 8192 + (i == 3) * 1024, &p.xr, ((i + RT_ROT) & 3) * 256, cta * 16, sb + BAR_RT + i * 8);
          if (i == 0) { bulk_load(sb + OFF_KVB, w_r, 2048, sb + BAR_RT); bulk_load(sb + OFF_KVB + 2048, gate_w, 2048, sb + BAR_RT); }
        }
        const uint32_t c = g - MOD_START;
        if (c == MOD_BUFS) mbar_wait(sb + BAR_RTD, 0);
        if (c < MOD_BUFS0 && mu < MOD_CTAS && elect()) {
          PROF(true, 192 + c);
          const uint32_t mb = c < MOD_BUFS ? c + 2 : c - MOD_BUFS, mfull = sb + BAR_MFULL + mb * 8, mdst = sb + OFF_V + mb * MOD_STEP;
          mbar_expect_tx(mfull, c ? 8192 : 8192 + 2048);
          tma3d(mdst, &p.gate, mu * 32, c * 16, 0, mfull); tma3d(mdst + 4096, &p.up, mu * 32, c * 16, 0, mfull);
        }
        const uint32_t pc = g - PF_MOD;
        if (pc < 16 && elect()) bulk_prefetch((cta & 64 ? w_up : w_gate) + (size_t)(pc * 64 + (cta & 63)) * F_, F_ * 2);
      }
      mbar_arrive_warp(sb + BAR_GATE);
      auto prefetch_wo = [&]() {
        if ((PV || tm >= 8) && elect())
          asm volatile("cp.async.bulk.prefetch.tensor.3d.L2.global [%0, {%1, %2, %3}];" ::"l"(&p.wo), "r"(0), "r"(tm * 64), "r"(tn * 2) : "memory");
      };
      if (PW < 0) prefetch_wo();
      const uint32_t lowb = (1u << (tn & 6) * 4) - 1;
      uint64_t slabs = (uint64_t)((0xFEDCBA98u & lowb) | (0xFEDCBAu & ~lowb)) << 40 | (uint64_t)(8 + (tn ^ 1)) << 36 | (uint64_t)(8 + tn) << 32 | 0x76543210u;
      uint64_t deps = 0x8CBA98CBA9876554ull, ws = OW_SLOTS;
      uint32_t full = sb + BAR_OFULL, ph = 1;
#pragma unroll 1
      for (int g = 0; g < 16; g++, slabs >>= 4, deps >>= 4, ws >>= 4) {
        mbar_wait(sb + BAR_EMPTY + ((uint32_t)deps & 15) * 8, ph);
        if (elect()) tma3d(sb + OFF_RING + ((uint32_t)ws & 15) * SLOT, &p.wo, 0, ((uint32_t)slabs & 15) * 64, tn * 2, full);
        if (elect()) mbar_expect_tx(full, SLOT);
        PROF(lane == 0, 96 + g);
        if (g == PW) prefetch_wo();
        if (g >> 1 == OWN / 2 && lane < 4) mbar_arrive(full);
        full += 8;
        if (full == sb + BAR_OFULL + 40) { full -= 40; ph ^= 1; }
      }
    } else if (warp == 14) {
      if (mu < MOD_CTAS) {
        uint32_t full = sb + BAR_MFULL + 16, dst = sb + OFF_MOD, ph = 0;
#pragma unroll 1
        for (int c = MOD_BUFS0; c < 24; c++) {
          mbar_wait(full + (BAR_MEMPTY - BAR_MFULL), ph);
          PROF(lane == 0, 192 + c);
          if (c < 16) {
            if (elect()) { tma3d(dst, &p.gate, mu * 32, c * 16, 0, full); tma3d(dst + 4096, &p.up, mu * 32, c * 16, 0, full); }
          } else if (elect()) tma3d(dst, &p.down, 0, mu * 32 + (c - 16) * 4, 0, full);
          if (elect()) mbar_expect_tx(full, 8192);
          full += 8; dst += MOD_STEP;
          if (full == sb + BAR_MFULL + MOD_BUFS0 * 8) { full -= MOD_BUFS * 8; dst = sb + OFF_MOD; ph ^= 1; }
        }
      }
      if (elect()) {
      mbar_wait(sb + BAR_IDX, 0);
      const bool paired = PAIRED && ld_relaxed(&gs->block[cta ^ 1]) == (blockIdx.x ^ 1);
      if (paired) mbar_expect_tx(sb + BAR_PEER, SLOT);
      mbar_expect_tx(sb + BAR_X, 32768);
      if (RM) {
        if (mu < MOD_CTAS) {
          mbar_wait(sb + BAR_MEMPTY + 3 * 8, 0);
          mbar_wait(sb + BAR_MEMPTY + 4 * 8, 0);
          mbar_wait(sb + BAR_MEMPTY + 2 * 8, 1);
        } else mbar_wait(sb + BAR_GATE, 0);
#pragma unroll
        for (int i = 0; i < 4; i++) {
          if (i == 3) mbar_wait(sb + BAR_OEMPTY + 3 * 8, 0);
          tma2d(sb + res_off(i >> 1, i & 1), &p.xh, tn * 128 + (i >> 1) * 64, tm * 128 + (i & 1) * 64, sb + BAR_X);
        }
      } else {
      mbar_wait(sb + BAR_OEMPTY + 3 * 8, 0);
      tma2d(sb + OFF_RES, &p.x, tn * 128, tm * 128, sb + BAR_X);
      mbar_wait(sb + BAR_OEMPTY + 4 * 8, 0);
      tma2d(sb + OFF_RES + RES_H, &p.x, tn * 128 + 64, tm * 128, sb + BAR_X);
      }
      if (!paired) {
        mbar_wait(sb + BAR_OWN, 0);
        while (!(ld_relaxed(gs->cnt[16 + tm]) & 4u << (tn ^ 1) * 4)) __nanosleep(32);
        fence_acquire();
        fence_async_global();
        const uint32_t par = lds32(sb + OFF_MISC + 24);
        for (uint32_t ph = !mbar_test(sb + BAR_MFULL, 1), bad = 1; bad & 1; ph ^= 1) {
          fence_async_smem();
          mbar_expect_tx(sb + BAR_MFULL, SLOT);
          bulk_load(sb + OFF_PK, gs->o[tm][8 + (tn ^ 1)], SLOT, sb + BAR_MFULL);
          mbar_wait(sb + BAR_MFULL, ph);
          bad = 0;
#pragma unroll 1
          for (int i = 0; i < 512; i++) bad |= lds32(sb + OFF_PK + i * 32 + (i & 28)) ^ par;
        }
        mbar_arrive(sb + BAR_PEER);
      }
      }
    } else {
#pragma unroll 1
      for (int i = 3; i < 10; i++)
        if (elect()) asm volatile("prefetch.tensormap [%0];" ::"l"(&p.x + i) : "memory");
      mbar_wait_bounded(sb + BAR_DONE, 0);
    }
  } else if (wg == 2) {
    asm volatile("setmaxnreg.dec.sync.aligned.u32 40;");
    const int mw = warp & 3;
    if (mw == 0) {
      const unsigned tag = (ld_relaxed(&gs->rslot[tn][cta]) + 1) & 0xFFF;
#pragma unroll
      for (int i = 0; i < 2; i++)
        if (lane < 28) ((float4*)gs)[cta * 56 + i * 28 + lane] = make_float4(0.f, 0.f, 0.f, 0.f);
      if (lane == 29) gs->block[cta] = blockIdx.x;
      fence_release();
      nb_sync(NB_KEY, 160);
      const uint4 k4 = lds128(sb + OFF_MISC);
      if (lane < 8) st_relaxed(&gs->rslot[lane][cta], max(max(k4.x, k4.y), max(k4.z, k4.w)) | tag);
      if (lane < 16) st_relaxed(&gs->gslot[cta * 16 + lane], lds32(sb + OFF_G + lane * 4) | tag);
      PROF(lane == 0, 20);
      uint4 r4;
      do {
        __nanosleep(RT_SLEEP);
        r4 = ld_relaxed4(&gs->rslot[tn][lane * 4]);
      } while (!__all_sync(~0u, (((r4.x ^ tag) | (r4.y ^ tag) | (r4.z ^ tag) | (r4.w ^ tag)) & 0xFFF) == 0));
      const int c0 = 0xFFF0 - lane * 64;
      unsigned key = max(max((r4.x & 0xFFFF0000u) | (c0 + ((r4.x >> 12) & 15)), (r4.y & 0xFFFF0000u) | (c0 - 16 + ((r4.y >> 12) & 15))),
                         max((r4.z & 0xFFFF0000u) | (c0 - 32 + ((r4.z >> 12) & 15)), (r4.w & 0xFFFF0000u) | (c0 - 48 + ((r4.w >> 12) & 15))));
      key = __reduce_max_sync(~0u, key);
      if (elect()) {
        sts32(sb + OFF_MISC + 16, key);
        sts32(sb + OFF_MISC + 24, tag & 1);
        if (mu < MOD_CTAS) {
          const __nv_bfloat16* row = px + (size_t)(0xFFFF - (key & 0xFFFF)) * D_;
          bulk_load(sb + OFF_XSEL, row, 1024, sb + BAR_MFULL + 16);
          bulk_load(sb + OFF_XSEL + MOD_STEP, row + 512, 1024, sb + BAR_MFULL + 16);
        }
      }
      PROF(lane == 0, 21);
      do {
        r4 = ld_relaxed4(&gs->gslot[tm * 128 + lane * 4]);
      } while (!__all_sync(~0u, (((r4.x ^ tag) | (r4.y ^ tag) | (r4.z ^ tag) | (r4.w ^ tag)) & 0xFFF) == 0));
      sts128(sb + OFF_G + lane * 16, r4.x & 0xFFFF0000u, r4.y & 0xFFFF0000u, r4.z & 0xFFFF0000u, r4.w & 0xFFFF0000u);
      fence_acquire();
      __syncwarp();
    }
    PROF(tid == 256, 22);
    if (mu >= MOD_CTAS) {
      mbar_arrive_warp(sb + BAR_IDX);
    } else {
      const uint32_t wp = sb + OFF_V + (mw >> 1) * 4096 + (mw & 1) * 512 + lane * 16;
      uint32_t mp = sb + OFF_XSEL + (mw & 1) * 64 + (lane >> 2) * 8, mc = 128;
      float acc[8] = {0.f, 0.f, 0.f, 0.f, 0.f, 0.f, 0.f, 0.f};
      uint32_t b = 2, ph = 0;
#pragma unroll 1
      for (int c = 0; c < 24; c++) {
        mbar_wait(sb + BAR_MFULL + b * 8, ph);
        PROF_C(tid == 256, 216 + c);
        const uint32_t a = wp + b * MOD_STEP;
        const uint2 m = lds64(mp);
        const uint4 w0 = lds128(a), w1 = lds128(a + 1024), w2 = lds128(a + 2048), w3 = lds128(a + 3072);
        mp += c == 7 ? MOD_STEP - 1024 + 128 : mc;
        const uint32_t m0 = dup_lo(m.x), m1 = dup_hi(m.x), m2 = dup_lo(m.y), m3 = dup_hi(m.y);
        uint4 q = make_uint4(mul_bf2(w0.x, m0), mul_bf2(w0.y, m0), mul_bf2(w0.z, m0), mul_bf2(w0.w, m0));
        q = make_uint4(fma_bf2(w1.x, m1, q.x), fma_bf2(w1.y, m1, q.y), fma_bf2(w1.z, m1, q.z), fma_bf2(w1.w, m1, q.w));
        q = make_uint4(fma_bf2(w2.x, m2, q.x), fma_bf2(w2.y, m2, q.y), fma_bf2(w2.z, m2, q.z), fma_bf2(w2.w, m2, q.w));
        mbar_arrive_warp(sb + BAR_MEMPTY + b * 8 + (w3.x & zero));
        q = make_uint4(fma_bf2(w3.x, m3, q.x), fma_bf2(w3.y, m3, q.y), fma_bf2(w3.z, m3, q.z), fma_bf2(w3.w, m3, q.w));
        if (++b == 5) b = c < 3 ? 0 : 2;
        if (b == 2) ph ^= 1;
        acc[0] += bf_lo(q.x); acc[1] += bf_hi(q.x); acc[2] += bf_lo(q.y); acc[3] += bf_hi(q.y);
        acc[4] += bf_lo(q.z); acc[5] += bf_hi(q.z); acc[6] += bf_lo(q.w); acc[7] += bf_hi(q.w);
        if (c == 15) {
          const uint32_t ft = fresh_tid(), fl = ft & 31;
          sts32(sb + OFF_PART + (ft & 96) * 4 + ((ft & 3) * 8 + (fl >> 2)) * 4, __float_as_uint(butterfly8(acc, fl, 4)));
          nb_sync(NB_MODW, 128);
          const float* part = (const float*)(smem + OFF_PART) + fl;
          const float gp = bf_round(part[0] + part[32]), up = bf_round(part[64] + part[96]);
          *(__nv_bfloat16*)(smem + OFF_PART + 512 + fl * 2) = __float2bfloat16_rn(bf_round(gp * sigmoidf_(gp)) * up);
          __syncwarp();
          mp = sb + OFF_PART + 512; mc = 8;
#pragma unroll
          for (int i = 0; i < 8; i++) acc[i] = 0.f;
          PROF(lane == 0 && mw == 0, 23);
        }
      }
      float4* yacc = gs->y[tn & 1][0] + (fresh_tid() & 127);
      red_add4(yacc, acc[0], acc[1], acc[2], 1.f);
      red_add4(yacc + 128, acc[3], acc[4], acc[5], 1.f);
      red_add4(yacc + 256, acc[6], acc[7], 0.f, 1.f);
      PROF(lane == 0 && mw == 0, 25);
    }
    mbar_wait(sb + BAR_GATE, 0);
    mbar_wait(sb + BAR_IDX, 0);
    verify_tiles(sb, gs, tm, tn, mw, lane);
  } else {
    if (E7 && warp == 7) {
#pragma unroll
      for (int g = PRE; g < 4; g++) {
        while ((int)(clock32() - t_start) < ST0 + (g - PRE) * ST1) {}
        if (elect()) tma2d(sb + OFF_RING + g * SLOT, &p.x, g * 64, tm * 128, sb + BAR_FULL + g * 8);
        if (elect()) tma3d(sb + OFF_W1 + g * WQKV_BYTES, &p.w, tn * 64, g * 64, 0, sb + BAR_FULL + g * 8);
        if (elect()) mbar_expect_tx(sb + BAR_FULL + g * 8, SLOT + WQKV_BYTES);
        PROF(lane == 0, 64 + g);
        const int i = g - RT_G0;
        if (i >= 0 && elect()) {
          mbar_expect_tx(sb + BAR_RT + i * 8, i ? 8192 : 8192 + 4096);
          tma2d(sb + OFF_PK + i * 8192, &p.xr, ((i + RT_ROT) & 3) * 256, cta * 16, sb + BAR_RT + i * 8);
          if (i == 0) { bulk_load(sb + OFF_KVB, w_r, 2048, sb + BAR_RT); bulk_load(sb + OFF_KVB + 2048, gate_w, 2048, sb + BAR_RT); }
        }
      }
    }
    asm volatile("setmaxnreg.inc.sync.aligned.u32 224;");
    const int w = warp & 3, wt = tid & 127;
    const int nb_self = NB_WG0 + wg;
    const uint64_t da0 = mkdesc(sb + OFF_RING, 16, 1024, 1), db0 = mkdesc(sb + OFF_RING, 8192, 1024, 1);

    if (wg == 1) {
      sts128(sb + OFF_ONES - (w >> 1) * 9216 + (w & 1) * 512 + lane * 16, 0x3F803F80u, 0x3F803F80u, 0x3F803F80u, 0x3F803F80u);
      sts32(sb + OFF_MISC + 20, 0x3FB8AA3Bu);
      fence_async_smem();
      float s[8] = {0.f, 0.f, 0.f, 0.f, 0.f, 0.f, 0.f, 0.f};
      uint32_t mask = 0xffff0000u;
#pragma unroll 1
      for (int i = 0; i < 4; i++) {
        const uint32_t u = (i + RT_ROT) & 3;
        mbar_wait(sb + BAR_RT + i * 8, 0);
        const uint4 wr = lds128(sb + OFF_KVB + u * 512 + lane * 16), gw = lds128(sb + OFF_KVB + 2048 + u * 512 + lane * 16);
        uint4 xv[4];
#pragma unroll
        for (int r = 0; r < 4; r++) xv[r] = lds128(sb + OFF_PK + i * 8192 + (i == 3) * 1024 + (w * 4 + r) * 512 + lane * 16);
        const float wf[16] = {bf_lo(wr.x), bf_hi(wr.x), bf_lo(wr.y), bf_hi(wr.y), bf_lo(wr.z), bf_hi(wr.z), bf_lo(wr.w), bf_hi(wr.w),
                              bf_lo(gw.x), bf_hi(gw.x), bf_lo(gw.y), bf_hi(gw.y), bf_lo(gw.z), bf_hi(gw.z), bf_lo(gw.w), bf_hi(gw.w)};
#pragma unroll
        for (int r = 0; r < 4; r++) {
          const uint4 xq = xv[r];
          const float xf[8] = {bf_lo(xq.x), __uint_as_float(xq.x & mask), bf_lo(xq.y), bf_hi(xq.y), bf_lo(xq.z), bf_hi(xq.z), bf_lo(xq.w), bf_hi(xq.w)};
#pragma unroll
          for (int j = 0; j < 8; j++) { s[2 * r] = fmaf(xf[j ^ 1], wf[j ^ 1], s[2 * r]); s[2 * r + 1] = fmaf(xf[j ^ 1], wf[8 + (j ^ 1)], s[2 * r + 1]); }
          mask = ((__float_as_uint(s[2 * r]) | __float_as_uint(s[2 * r + 1])) & zero) | 0xffff0000u;
        }
      }
      mbar_arrive_warp(sb + BAR_RTD + (__float_as_uint(s[6]) & zero));
      float v = butterfly8(s, lane, 1);
      PROF_C(wt == 0 && v != 12345.f, 19);
      v += __shfl_xor_sync(~0u, v, 8);
      v = bf_round(v + __shfl_xor_sync(~0u, v, 16));
      const unsigned rb = __float_as_uint(v) >> 16, row = w * 4 + ((lane & 7) >> 1);
      unsigned key = (lane & 1) ? 0u : ((((rb & 0x8000u) ? (~rb & 0xFFFFu) : (rb | 0x8000u)) << 16) | ((15 - row) << 12));
      key = __reduce_max_sync(~0u, key);
      if (lane == 0) sts32(sb + OFF_MISC + w * 4, key);
      if (lane < 8 && (lane & 1)) sts32(sb + OFF_G + row * 4, __float_as_uint(bf_round(sigmoidf_(v))));
      nb_arrive(NB_KEY, 160);
      nb_sync(NB_ORDER_12, 256);
    }
    uint4* const kvacc = &gs->kv[wg][tn][0][wt];
    float aq[64];
    uint32_t su[9];
    float pq[64], ak[64], av[64];
    auto proj = [&](float (&d)[64], int j, uint32_t s, int sc) {
#pragma unroll
      for (int kk = 0; kk < 4; kk++)
        mma128<1, 0>(d, da0 + ((OFF_W1 >> 4) + s * (WQKV_BYTES >> 4) + j * 512 + kk * 128), da0 + (s * (SLOT >> 4) + kk * 2), kk ? 1 : sc);
    };
    PROF_C(wt == 0, 1 + wg * 8);
#pragma unroll 1
    for (int g = 0; g < 15; g++) {
      mbar_wait(sb + BAR_FULL + (g & 7) * 8, g >> 3);
      if (g == 0) PROF_C(wt == 0, 2 + wg * 8);
      wg_fence();
      proj(ak, 1, g & 3, g);
      wg_commit();
      wg_wait<1>();
      if (g) mbar_arrive_warp(sb + BAR_EMPTY + (g - 1 & 7) * 8);
      if (g == 14) break;
      if (SP && g == 0) mbar_wait(sb + BAR_SP, 0);
      wg_fence();
      proj(av, 2, g & 3, g);
      proj(pq, 0, g & 3, g);
      wg_commit();
    }
    const uint32_t qa = sb + OFF_PK + ((lane >> 4) * 8 + (lane & 7)) * 128 + (((2 * w + ((lane >> 3) & 1)) ^ (lane & 7)) << 4);
    auto finish = [&](auto reorder) {
      constexpr int re = decltype(reorder)::value, vk = re ? VK1 : VK, mm = re ? MM1 : MM, kl = re ? KL1 : KL, qw = re ? QW1 : 0;
      float c[36];
      uint32_t pk[8][4];
      if (!re) {
        wg_fence();
        proj(av, 2, 2, 1);
        proj(pq, 0, 2, 1);
        wg_commit();
      }
      mbar_wait(sb + BAR_FULL + 7 * 8, 1);
      wg_fence();
      proj(ak, 1, 3, 1);
      wg_commit();
      if (!re) {
        wg_wait<1>();
        mbar_arrive_warp(sb + BAR_EMPTY + 6 * 8);
      }
      wg_fence();
      if (re) proj(av, 2, 2, 1);
      proj(av, 2, 3, 1);
      wg_commit();
      if (!re) {
        proj(pq, 0, 3, 1);
        wg_commit();
        if (wg == 0) nb_arrive(NB_ORDER_12, 256);
      }
      mbar_wait(sb + BAR_IDX, 0);
      if (wg == 1) nb_sync(NB_STG, 256);
      wg_wait<2 - re>();
      pin(ak);
      PROF_C(wt == 0, 3 + wg * 8);
      const uint32_t va = sb + OFF_V + (w * 16 + (lane & 15)) * 128;
      uint32_t lk[8];
#pragma unroll
      for (int u = 0; u < kl; u++) lk[u] = 0x3FB8AA3Bu;
#pragma unroll
      for (int u = 0; u < 8; u++) {
        if (re && (u == Q0 || u == Q0 + QS)) {
          wg_fence();
          proj(pq, 0, u == Q0 ? 3 - re : 3, 1);
          wg_commit();
          if (wg == 0 && u != Q0) nb_arrive(NB_ORDER_12, 256);
          if (qw) {
            wg_wait<7>();
            const uint32_t l = lds32(sb + OFF_MISC + 20);
#pragma unroll
            for (int t = u; t < u + kl && t < 8; t++) lk[t] = l;
          }
        }
#pragma unroll
        for (int i = 0; i < 4; i++) pk[u][i] = phi2(ak[8 * u + 2 * i], ak[8 * u + 2 * i + 1], __uint_as_float(lk[u]));
        if (u == vk) { wg_wait<re ? (vk >= Q0) + (vk >= Q0 + QS) : 1>(); pin(av); }
        if (u == M0 && re) { wg_wait<(M0 >= Q0 + QS)>(); mbar_arrive_warp(sb + BAR_EMPTY + 6 * 8); }
        if (u == mm) { wg_wait<0>(); mbar_arrive_warp(sb + BAR_EMPTY + 7 * 8); }
        const uint32_t z = mism(pk[u][0], pk[u][1], 0) | mism(pk[u][2], pk[u][3], 0);
#pragma unroll
        for (int t = u < vk ? 8 : (u - vk) * 8 / (8 - vk); t < (u - vk + 1) * 8 / (8 - vk); t++) {
          const float* v = &av[8 * t];
          stsm4(va + (t >> 2) * 9216 + ((((lane >> 4) + 2 * (t & 3)) ^ (lane & 7)) << 4) + (z & zero), pack2(v[0], v[1]), pack2(v[2], v[3]), pack2(v[4], v[5]), pack2(v[6], v[7]));
        }
        if (u + kl < 8) lk[u + kl] = lds32(sb + OFF_MISC + 20 + (u < vk ? z & zero : 0));
      }
      fence_async_smem();
      nb_sync(nb_self, 128);
      PROF_C(wt == 0, 8 + wg * 8);
      const uint64_t dv = mkdesc(sb + OFF_V, 16, 1024, 1);
      wg_fence();
#pragma unroll
      for (int kk = 0; kk < 8; kk++) mma_ktv(c, pk[kk], dv + ((kk >> 2) * 576 + (kk & 3) * 2), kk ? 1 : 0);
      wg_commit();
      if (wg == 1) nb_arrive(NB_ORDER_3O, 256);
      pin(pq);
#pragma unroll
      for (int u = 0; u < QE; u++)
        stsm4t(qa + u * 2048, phi2(pq[8 * u], pq[8 * u + 1]), phi2(pq[8 * u + 2], pq[8 * u + 3]), phi2(pq[8 * u + 4], pq[8 * u + 5]), phi2(pq[8 * u + 6], pq[8 * u + 7]));
      wg_wait<0>();
      pin(c);
#pragma unroll
      for (int i = 0; i < 64; i++) aq[i] = pq[i];
      PROF_C(wt == 0, 4 + wg * 8);
#pragma unroll
      for (int i = 0; i < 8; i++) {
        const int j = (i & 3) * 4 + (i >> 2) * 2;
        su[i] = w >= 2 ? pack2(c[16 + j], c[17 + j]) : pack2(c[j], c[j + 1]);
      }
      su[8] = pack2(c[32], c[34]);
#pragma unroll
      for (int u = 0; u < 3; u++)
        if (u < R0 || wg) red_add_bf(kvacc + u * 128, su[3 * u], su[3 * u + 1], su[3 * u + 2]);
    };
    if (TR == 2) {
      if (wg == 0) finish(std::integral_constant<int, 0>());
      else finish(std::integral_constant<int, 1>());
    } else finish(std::integral_constant<int, TR>());
    const uint32_t par = lds32(sb + OFF_MISC + 24);
    {
      const bool paired = PAIRED && ld_relaxed(&gs->block[cta ^ 1]) == (blockIdx.x ^ 1);
      uint4 kv[3];
      int tries = wg ? 0 : TRY_A;
      const uint8_t* gl = smem + OFF_MISC + 20;
      asm volatile("" : "+l"(gl));
      const uint32_t l2e = ld_generic(gl);
    auto stage_kv = [&]() {
      const uint32_t kb = sb + OFF_KVB + w * 256, ka = kb + (lane & 3) * KVB_N + (lane >> 2) * 16;
      sts128(ka, kv[0].x, kv[0].y, kv[0].z, kv[1].x);
      sts128(ka + 128, kv[1].y, kv[1].z, kv[2].x, kv[2].y);
      sts32(kb + 4 * KVB_N + lane * 4, dup_lo(kv[2].z));
      sts32(kb + 4 * KVB_N + 128 + lane * 4, dup_hi(kv[2].z));
      return __all_sync(~0u, (kv[0].w & kv[1].w & kv[2].w) == 0x41804180u && (kv[0].w | kv[1].w | kv[2].w) == 0x41804180u);
    };
      bool have = false;
      uint32_t lq[8];
#pragma unroll
      for (int u = QE; u < QE + QA && u < 8; u++) lq[u] = l2e;
#pragma unroll
      for (int u = QE; u < 8; u++) {
        uint32_t r[4];
        if (u == KF && wg) {
#pragma unroll
          for (int i = 0; i < 3; i++) kv[i] = ld_relaxed4(kvacc + i * 128);
        }
#pragma unroll
        for (int i = 0; i < 4; i++) r[i] = phi2(aq[8 * u + 2 * i], aq[8 * u + 2 * i + 1], __uint_as_float(lq[u]));
        stsm4t(qa + u * 2048, r[0], r[1], r[2], r[3]);
        const int ru = (u - QE) / RS + R0;
        if ((u - QE) % RS == RS - 1 && ru < 3 && !wg) red_add_bf(kvacc + ru * 128, su[3 * ru], su[3 * ru + 1], su[3 * ru + 2]);
        if (u + QA < 8) lq[u + QA] = lds32(sb + OFF_MISC + 20);
        if (u == KU && wg) have = stage_kv();
      }
      PROF_C(wt == 0, 34 + wg * 2);
      if (KU > 7 && KF < 8 && wg) have = stage_kv();
      for (; !have; tries++) {
        if (tries > RETRY)
          while (ld_relaxed((const unsigned*)&(kvacc - lane)[256 + 31].w) != 0x41804180u) __nanosleep(wg ? KV_SLEEP : KV_SLEEP_A);
#pragma unroll
        for (int i = 0; i < 3; i++) kv[i] = ld_relaxed4(kvacc + i * 128);
        have = stage_kv();
      }
      PROF_C(wt == 0, 5 + wg * 8);
      if (EF == 4 && wg && elect()) red_add(gs->cnt[16 + tm], 1u << tn * 4);
      fence_async_smem();
      nb_sync(nb_self, 128);
      float o[2][2][20];
      const uint64_t dq = mkdesc(sb + OFF_PK, 16, 1024, 1), dz = mkdesc(sb + OFF_KVB, 128, KVB_N, 0);
      wg_fence();
#pragma unroll
      for (int m = 0; m < 2; m++) {
#pragma unroll
        for (int h = 0; h < 2; h++)
#pragma unroll
          for (int kk = 0; kk < 2; kk++) mma_qkvz(o[m][h], dq + (m * 512 + h * 4 + kk * 2), dz + (h * 32 + kk * 16), kk);
        wg_commit();
      }
      if (HOLD < 8 && HP == 0 && wg) nb_arrive(NB_HOLD, 256);
      if (EF == 3 && wg && elect()) red_add(gs->cnt[16 + tm], 1u << tn * 4);
      uint32_t tag[2][4];
#pragma unroll
      for (int i = 0; i < 8; i++) tag[i >> 2][i & 3] = (lane >> 3) == (i & 3) && ((lane ^ (lane >> 3)) & 1) == (i >> 2);
      uint32_t gr[8];
      const uint8_t* ga = smem + OFF_G + (w * 16 + (lane >> 2)) * 4;
      asm volatile("" : "+l"(ga));
#pragma unroll
      for (int i = 0; i < OA; i++) gr[i] = ld_generic(ga + (i >> 2) * 256 + (i & 1) * 32);
      const uint32_t oo = w * 1024 + (lane >> 2) * 64 + (((lane ^ (lane >> 3)) & 3) << 4);
      uint8_t* const og = (uint8_t*)gs->o[tm][wg * 8 + tn] + oo;
      uint32_t ob[8][4];
#pragma unroll
      for (int m = 0; m < 2; m++) {
        if (m == 0) wg_wait<1>(); else wg_wait<0>();
        pin(o[m][0]); pin(o[m][1]);
        if (EF == 2 - m && wg && elect()) red_add(gs->cnt[16 + tm], 1u << tn * 4);
        if (PB == 2 - m && wg) mbar_arrive_warp(sb + BAR_PUB + 8);
        if (m && !wg) nb_arrive(NB_STG, 256);
        if (HOLD < 8 && HP == 1 && m && wg) nb_arrive(NB_HOLD, 256);
        if (m && wg && paired && elect()) mbar_arrive_peer(peer_addr(sb + BAR_PA));
        if (m == 0) PROF_C(wt == 0, 6 + wg * 8);
#pragma unroll
        for (int u = 0; u < 4; u++) {
          const int h = u >> 1, i = u & 1;
          const float* on = o[m][h];
          const float sc = __uint_as_float(gr[m * 4 + u]) * rcp(on[16 + 2 * i] + 1e-6f);
          const uint32_t sc2 = pack2(sc, sc);
#pragma unroll
          for (int j = 0; j < 4; j++) {
            const uint32_t v = HS ? mul_bf2(pack2(on[4 * j + 2 * i], on[4 * j + 2 * i + 1]), sc2) : pack2(on[4 * j + 2 * i] * sc, on[4 * j + 2 * i + 1] * sc);
            asm("lop3.b32 %0, %1, %2, %3, 0xB8;" : "=r"(ob[m * 4 + u][j]) : "r"(v), "r"(tag[i][j]), "r"(par));
          }
          st_relaxed4(og + (h * 8192 + m * 4096 + i * 512), ob[m * 4 + u]);
          if (OWN1 == 2 && wg) sts128(sb + OFF_V + oo + (h * 8192 + m * 4096 + i * 512), ob[m * 4 + u][0], ob[m * 4 + u][1], ob[m * 4 + u][2], ob[m * 4 + u][3]);
          if (HOLD < 8 && HP == 10 + m * 4 + u && wg) nb_arrive(NB_HOLD, 256);
          const int n = m * 4 + u + OA;
          if (n < 8) gr[n] = ld_generic(ga + (n >> 2) * 256 + (n & 1) * 32);
        }
      }
      if ((!EF || !wg) && elect()) red_add(gs->cnt[wg * 16 + tm], 1u << tn * 4);
      if (!PB || !wg) mbar_arrive_warp(sb + BAR_PUB + wg * 8);
      if (HOLD < 8 && HP == 2 && wg) nb_arrive(NB_HOLD, 256);
      PROF(wt == 0, 17 + wg);
      if (wg) {
        auto to_peer = [&]() {
        if (paired) {
          const uint32_t pb = peer_addr(sb);
          mbar_wait(sb + BAR_PA, 0);
#pragma unroll
          for (int u = 0, z = 0; u < 8; u++) {
            if (PS && u && u % PS == 0) z = lds32(sb + OFF_ONES) & zero;
            st_async4(pb + OFF_PK + oo + ((u >> 1 & 1) * 8192 + (u >> 2) * 4096 + (u & 1) * 512) + z, ob[u], pb + BAR_PEER);
          }
        }
        };
        if (!OWN1) to_peer();
#pragma unroll
        for (int u = 0, z = 0; u < (OWN1 == 2 ? 0 : 8); u++) {
          sts128(sb + OFF_V + oo + ((u >> 1 & 1) * 8192 + (u >> 2) * 4096 + (u & 1) * 512) + z, ob[u][0], ob[u][1], ob[u][2], ob[u][3]);
          if (PO && u % PO == PO - 1 && u < 7) z = lds32(sb + OFF_ONES) & 16;
        }
        fence_async_smem();
        __syncwarp();
        mbar_arrive_warp(sb + BAR_OWN);
        if (HOLD < 8 && HP == 3) nb_arrive(NB_HOLD, 256);
        PROF(wt == 0, 15);
        if (OWN1) to_peer();
      }
    }
    if (wg == 1) {
      patch_row(w);
    } else {
      float acc[2][64];
      nb_sync(NB_ORDER_3O, 256);
      PROF_C(wt == 0, 26);
      uint32_t xr[2][8][4], q[2][2];
      const uint32_t ta = sb + (uint32_t)(w * 16 + (lane & 15)) * 128;
      const uint64_t do0 = mkdesc(sb + OFF_RING, 16, 512, 2);
      uint64_t xs = OA_SLOTS, ws = OW_SLOTS;
#pragma unroll 1
      for (int g = 0; g < 13 - TL; g++, xs >>= 4, ws >>= 4) {
        const uint32_t r = g * 52 >> 8, s = g - r * 5;
        const uint64_t da = do0 + ((uint32_t)xs & 15) * (SLOT >> 4), db = db0 + ((uint32_t)ws & 15) * (SLOT >> 4);
        if (g == OWN) mbar_wait(sb + BAR_OWN, 0);
        if (g == PEER) { PROF(wt == 0, 39); mbar_wait(sb + BAR_PEER, 0); PROF(wt == 0, 40); fence_async_smem(); }
        if (g == HOLD) {
          if (HR) { wg_wait<0>(); mbar_arrive_warp(sb + BAR_OEMPTY + (HOLD + 4) % 5 * 8); }
          nb_sync(NB_HOLD, 256);
        }
        mbar_wait(sb + BAR_OFULL + s * 8, r & 1);
        wg_fence();
#pragma unroll
        for (int kk = 0; kk < 4; kk++)
#pragma unroll
          for (int m = 0; m < 2; m++) mma128<0, 1>(acc[m], da + (m * 256 + (kk >> 1) * 512 + (kk & 1) * 2), db + kk * 128, kk ? 1 : g);
        wg_commit();
        wg_wait<1>();
        if (g && (g != HOLD || !HR)) mbar_arrive_warp(sb + BAR_OEMPTY + (s ? s - 1 : 4) * 8);
      }
      PROF(wt == 0, 29);
      mbar_wait(sb + BAR_X, 0);
      PROF(wt == 0, 30);
      const int selw = ((0xFFFF - (int)(lds32(sb + OFF_MISC + 16) & 0xFFFF)) >> 4) - tm * 8 - w;
#pragma unroll
      for (int u = 0; u < 4; u++) {
        const int m = u >> 1, g = 13 - TL + u;
        const float g1 = 1.f - __uint_as_float(lds32(sb + OFF_G + (m * 64 + w * 16 + (u & 1) * 8 + (lane >> 2)) * 4));
        q[m][u & 1] = pack2(g1, g1);
#pragma unroll
        for (int j = 0; j < 4; j++) ldsm4(ta + res_off(u & 1, m) + ((((lane >> 4) + 2 * j) ^ (lane & 7)) << 4), xr[m][(u & 1) * 4 + j]);
        if (u == 3) break;
        mbar_wait(sb + BAR_OFULL + g % 5 * 8, g / 5 & 1);
        wg_fence();
#pragma unroll
        for (int kk = 0; kk < 4; kk++)
#pragma unroll
          for (int mm = 0; mm < 2; mm++)
            mma128<0, 1>(acc[mm], do0 + ((OA_SLOTS >> g * 4 & 15) * (SLOT >> 4) + mm * 256 + (kk >> 1) * 512 + (kk & 1) * 2), db0 + ((OW_SLOTS >> g * 4 & 15) * (SLOT >> 4) + kk * 128), 1);
        wg_commit();
        wg_wait<1>();
        if (g <= 11) mbar_arrive_warp(sb + BAR_OEMPTY + (g + 4) % 5 * 8);
      }
#pragma unroll
      for (int m = 0; m < 2; m++) {
#pragma unroll
        for (int g = 16 - TL; g < 16; g++) {
          if (m == 0) { mbar_wait(sb + BAR_OFULL + g % 5 * 8, g / 5 & 1); wg_fence(); }
#pragma unroll
          for (int kk = 0; kk < 4; kk++)
            mma128<0, 1>(acc[m], do0 + ((OA_SLOTS >> g * 4 & 15) * (SLOT >> 4) + m * 256 + (kk >> 1) * 512 + (kk & 1) * 2), db0 + ((OW_SLOTS >> g * 4 & 15) * (SLOT >> 4) + kk * 128), 1);
        }
        wg_commit();
      }
      mbar_arrive_warp(sb + BAR_DONE);
      const uint32_t tb = sb + w * 2048 + (lane >> 3) * 128 + (((lane ^ (lane >> 3)) & 7) << 4), tx = lane & 4 ? 64 : -64;
      uint8_t* const og = (uint8_t*)pout + (size_t)(tm * 128 + w * 16 + (lane >> 3)) * 2048 + tn * 256 + (lane & 7) * 16;
#pragma unroll
      for (int m = 0; m < 2; m++) {
        if (selw == 4 * m) {
          mbar_wait(sb + BAR_Y, 0);
#pragma unroll
          for (int j = 0; j < 8; j++) ldsm4(ta + res_off(j >> 2, m) + ((((lane >> 4) + 2 * (j & 3)) ^ (lane & 7)) << 4), xr[m][j]);
        }
        if (m == 0) wg_wait<1>(); else wg_wait<0>();
        if (m) PROF(wt == 0, 31);
#pragma unroll
        for (int h = 0; h < 2; h++) {
#pragma unroll
          for (int j = 4 * h; j < 4 * h + 4; j++) {
            const float* v = &acc[m][8 * j];
            stsm4(ta + res_off(h, m) + ((((lane >> 4) + 2 * (j & 3)) ^ (lane & 7)) << 4),
                  fma_bf2(xr[m][j][0], q[m][0], pack2(v[0], v[1])), fma_bf2(xr[m][j][1], q[m][1], pack2(v[2], v[3])),
                  fma_bf2(xr[m][j][2], q[m][0], pack2(v[4], v[5])), fma_bf2(xr[m][j][3], q[m][1], pack2(v[6], v[7])));
          }
          if (FS >> m & 1) {
            __syncwarp();
            uint4 t[4];
#pragma unroll
            for (int j = 0; j < 4; j++) t[j] = lds128(tb + res_off(h, m) + j * 512 - (j & 1) * tx);
#pragma unroll
            for (int j = 0; j < 4; j++) *(uint4*)(og + (m * 64 + j * 4) * 2048 + h * 128) = t[j];
          } else {
            fence_async_smem();
            __syncwarp();
            if (elect()) tma2d_store(&p.out, sb + res_off(h, m) + w * 2048, tn * 128 + h * 64, tm * 128 + m * 64 + w * 16);
          }
          if (FS != 3 && m && h && elect()) { bulk_commit(); asm volatile("cp.async.bulk.wait_group.read 0;" ::: "memory"); }
        }
        if (!m) PROF(wt == 0, 33);
      }
      PROF(wt == 0, 32);
    }
  }
}

typedef CUresult (*EncodeFn)(CUtensorMap*, CUtensorMapDataType, cuuint32_t, void*, const cuuint64_t*, const cuuint64_t*, const cuuint32_t*,
                             const cuuint32_t*, CUtensorMapInterleave, CUtensorMapSwizzle, CUtensorMapL2promotion, CUtensorMapFloatOOBfill);

void encode(EncodeFn fn, CUtensorMap* m, const void* ptr, int rank, const cuuint64_t* dims, const cuuint64_t* strides, const cuuint32_t* box,
            CUtensorMapSwizzle sw, CUtensorMapDataType dt = CU_TENSOR_MAP_DATA_TYPE_BFLOAT16) {
  const cuuint32_t es[3] = {1, 1, 1};
  fn(m, dt, rank, const_cast<void*>(ptr), dims, strides, box, es, CU_TENSOR_MAP_INTERLEAVE_NONE, sw,
     CU_TENSOR_MAP_L2_PROMOTION_L2_128B, CU_TENSOR_MAP_FLOAT_OOB_FILL_NONE);
}

}

extern "C" void kernel_launch(void* const* d_in, const int* in_sizes, int n_in, void* d_out, int out_size) {
  (void)in_sizes; (void)n_in; (void)out_size;
  EncodeFn fn = nullptr;
  cudaDriverEntryPointQueryResult qr;
  cudaGetDriverEntryPoint("cuTensorMapEncodeTiled", (void**)&fn, cudaEnableDefault, &qr);

  Params p;
  {
    const cuuint64_t dims[2] = {D_, S_}, str[1] = {D_ * 2};
    const cuuint32_t box[2] = {64, 128}, box_st[2] = {64, 16}, box_r[2] = {256, 16}, box_h[2] = {64, 64};
    encode(fn, &p.xh, d_in[0], 2, dims, str, box_h, CU_TENSOR_MAP_SWIZZLE_128B);
    encode(fn, &p.xr, d_in[0], 2, dims, str, box_r, CU_TENSOR_MAP_SWIZZLE_NONE);
    encode(fn, &p.x, d_in[0], 2, dims, str, box, CU_TENSOR_MAP_SWIZZLE_128B);
    encode(fn, &p.out, d_out, 2, dims, str, box_st, CU_TENSOR_MAP_SWIZZLE_128B);
  }
  {
    const cuuint64_t dims[3] = {D_, D_, 3}, str[2] = {3 * D_ * 2, D_ * 2};
    const cuuint32_t box[3] = {64, 64, 3};
    encode(fn, &p.w, d_in[1], 3, dims, str, box, CU_TENSOR_MAP_SWIZZLE_128B);
    const cuuint32_t box1[3] = {64, 64, 1};
    encode(fn, &p.w1, d_in[1], 3, dims, str, box1, CU_TENSOR_MAP_SWIZZLE_128B);
  }
  {
    const cuuint64_t dims[3] = {64, D_, D_ / 64}, str[2] = {D_ * 2, 128};
    const cuuint32_t box[3] = {64, 64, 2};
    encode(fn, &p.wo, d_in[2], 3, dims, str, box, CU_TENSOR_MAP_SWIZZLE_128B);
  }
  {
    const cuuint64_t dims[3] = {F_, D_ / 4, 4}, str[2] = {F_ * 8, F_ * 2};
    const cuuint32_t box[3] = {32, 16, 4};
    encode(fn, &p.gate, d_in[5], 3, dims, str, box, CU_TENSOR_MAP_SWIZZLE_NONE);
    encode(fn, &p.up, d_in[6], 3, dims, str, box, CU_TENSOR_MAP_SWIZZLE_NONE);
  }
  {
    const cuuint64_t dims[3] = {D_ / 4, F_, 2}, str[2] = {D_ * 2, D_};
    const cuuint32_t box[3] = {256, 4, 2};
    encode(fn, &p.down, d_in[7], 3, dims, str, box, CU_TENSOR_MAP_SWIZZLE_NONE, CU_TENSOR_MAP_DATA_TYPE_UINT32);
  }
  void* gs = nullptr;
  cudaGetSymbolAddress(&gs, g_scratch);
  typedef const __nv_bfloat16* bp;
  int dev = 0, sms = 0;
  cudaGetDevice(&dev);
  cudaDeviceGetAttribute(&sms, cudaDevAttrMultiProcessorCount, dev);
  const bool by_sm = BYSM && sms == NGRID;
  const auto kernel = by_sm ? fused_kernel<true> : fused_kernel<false>;
  cudaFuncSetAttribute(kernel, cudaFuncAttributeMaxDynamicSharedMemorySize, SMEM_BYTES);
  kernel<<<by_sm ? NGRID : NCTA, NTHREADS, SMEM_BYTES, cudaStreamPerThread>>>((bp)d_in[0], (Scratch*)gs, (bp)d_in[5], (bp)d_in[6], (bp)d_in[4], (bp)d_in[8], (__nv_bfloat16*)d_out, p);
}
```

```cpp
#include <cuda_runtime.h>
#include <cuda.h>
#include <cuda_bf16.h>
#include <stdint.h>
#include <stddef.h>

namespace {

constexpr int S_ = 2048, D_ = 1024, F_ = 3584;
constexpr int NCTA = 128, NGRID = 132, NTHREADS = 512;
#define NOMOD 0
constexpr int MOD_CTAS = NOMOD ? 0 : F_ / 32;

#define PRE 2
#define ST1 700
#define RT_G0 2
#define RT_ROT 1
#define RT_SLEEP 500
#define PF_MOD 7
#define MOD_START 9
#define MM 3
#define HOLD 5
#define KF 6
#define QA 3
#define R0 1
#define OA 3
#define Y_SLEEP 200
#define VK 1
#define KL 3
#define RS 2
#define RETRY 1
#define KV_SLEEP_A 64
#define KV_SLEEP 50
#define TL 3
#define B_SLEEP 32
#define PAIRED 1
#define BYSM 1

constexpr uint32_t SLOT = 16384, WQKV_BYTES = 24576;
constexpr int MOD_BUFS = 3, MOD_BUFS0 = MOD_BUFS + 2;
static_assert(MOD_START + MOD_BUFS0 <= 16, "first FFN round is requested during W1");
constexpr uint32_t OFF_RING = 0, OFF_W1 = 4 * SLOT;
constexpr uint64_t OA_SLOTS = 0x0AB210AB21098210ull, OW_SLOTS = 0x4376543765437654ull;
constexpr uint32_t OFF_RES = OFF_RING + 8 * SLOT;
constexpr uint32_t OFF_PK = 10 * SLOT;
constexpr uint32_t OFF_V = 11 * SLOT;
constexpr uint32_t OFF_ONES = OFF_V + 9216 + 8192;
constexpr uint32_t MOD_STEP = 9216, OFF_MOD = OFF_V + 2 * MOD_STEP;
constexpr __host__ __device__ uint32_t res_off(int h, int m) { return h & m ? OFF_RES : OFF_MOD + (h * 2 + m) * MOD_STEP; }
constexpr uint32_t OFF_XSEL = OFF_MOD + 8192;
constexpr uint32_t OFF_KVB = OFF_MOD + 2 * MOD_STEP + 8192;
constexpr uint32_t KVB_N = 1056;
constexpr uint32_t OFF_G = OFF_KVB + 4 * KVB_N + 1024;
constexpr uint32_t OFF_PART = OFF_G + 512;
constexpr uint32_t OFF_MISC = OFF_PART + 576;
constexpr uint32_t OFF_BAR = OFF_MISC + 32;
constexpr uint32_t SMEM_BYTES = OFF_BAR + 488;
constexpr uint32_t BAR_FULL = OFF_BAR, BAR_Y = BAR_FULL + 64, BAR_X = BAR_Y + 8, BAR_PEER = BAR_X + 8, BAR_GATE = BAR_PEER + 8, BAR_RT = BAR_GATE + 8,
                   BAR_FIX = BAR_RT,
                   BAR_MFULL = BAR_FIX + 32, BAR_LAND = BAR_FULL,
                   BAR_EMPTY = OFF_BAR + 28 * 8, BAR_OEMPTY = BAR_EMPTY + 64, BAR_RTD = BAR_OEMPTY + 40, BAR_DONE = BAR_RTD + 8,
                   BAR_OWN = BAR_DONE + 8, BAR_PA = BAR_OWN + 8, BAR_PUB = BAR_PA + 8, BAR_MEMPTY = BAR_PUB + 16,
                   BAR_IDX = BAR_MEMPTY + 8,
                   BAR_OFULL = OFF_BAR + 52 * 8;
static_assert(BAR_MFULL + MOD_BUFS0 * 8 <= BAR_EMPTY && BAR_MEMPTY + MOD_BUFS0 * 8 == BAR_OFULL, "barrier groups");
static_assert(SMEM_BYTES <= 232448, "smem");
static_assert(TL == 3 && PRE == 2, "schedule");

constexpr int NB_WG0 = 1, NB_ORDER_AB = 3, NB_ORDER_BO = 4, NB_STG = 5, NB_MODW = 6, NB_KEY = 7, NB_HOLD = 8;

struct Scratch {
  uint4 kv[2][8][3][128];
  float4 y[2][3][128];
  unsigned cnt[32][32];
  unsigned gslot[S_];
  unsigned rslot[8][NCTA];
  unsigned spare[128];
  unsigned block[NCTA];
  uint4 o[16][16][1024];
};
static_assert(offsetof(Scratch, gslot) == NCTA * 56 * 16, "clear size");
__device__ __align__(1024) Scratch g_scratch;

#define PROF(cond, i) do {} while (0)
#define PROF_C(cond, i) do {} while (0)

__device__ __forceinline__ void mbar_init(uint32_t bar, int cnt) { asm volatile("mbarrier.init.shared::cta.b64 [%0], %1;" ::"r"(bar), "r"(cnt)); }
__device__ __forceinline__ void mbar_expect_tx(uint32_t bar, uint32_t bytes) { asm volatile("mbarrier.arrive.expect_tx.shared::cta.b64 _, [%0], %1;" ::"r"(bar), "r"(bytes) : "memory"); }
__device__ __forceinline__ void mbar_arrive(uint32_t bar) { asm volatile("mbarrier.arrive.shared::cta.b64 _, [%0];" ::"r"(bar) : "memory"); }
__device__ __forceinline__ uint32_t peer_addr(uint32_t a) {
  uint32_t r;
  asm volatile("{\n.reg .u32 c;\nmov.u32 c, %%cluster_ctarank;\nxor.b32 c, c, 1;\nmapa.shared::cluster.u32 %0, %1, c;\n}" : "=r"(r) : "r"(a));
  return r;
}
__device__ __forceinline__ void mbar_arrive_peer(uint32_t bar) { asm volatile("mbarrier.arrive.shared::cluster.b64 _, [%0];" ::"r"(bar) : "memory"); }
__device__ __forceinline__ uint32_t mism(uint32_t a, uint32_t b, uint32_t p) {
  uint32_t r; asm("lop3.b32 %0, %1, %2, %3, 0x7E;" : "=r"(r) : "r"(a), "r"(b), "r"(p)); return r;
}
__device__ __forceinline__ bool elect() {
  uint32_t r;
  asm volatile("{\n.reg .pred p;\nelect.sync _|p, 0xffffffff;\nselp.u32 %0, 1, 0, p;\n}" : "=r"(r));
  return r;
}
__device__ __forceinline__ uint32_t fresh_tid() { uint32_t r; asm volatile("mov.u32 %0, %%tid.x;" : "=r"(r)); return r; }
__device__ __forceinline__ void mbar_arrive_warp(uint32_t bar) {
  asm volatile("{\n.reg .pred p;\nelect.sync _|p, 0xffffffff;\n@p mbarrier.arrive.shared::cta.b64 _, [%0];\n}" ::"r"(bar) : "memory");
}
__device__ __forceinline__ void mbar_wait(uint32_t bar, uint32_t parity) {
  asm volatile("{\n.reg .pred p;\nWAIT_L:\nmbarrier.try_wait.parity.shared::cta.b64 p, [%0], %1;\n@p bra DONE_L;\nbra WAIT_L;\nDONE_L:\n}"
               ::"r"(bar), "r"(parity) : "memory");
}
__device__ __forceinline__ uint32_t mbar_try(uint32_t bar, uint32_t parity) {
  uint32_t ok;
  asm volatile("{\n.reg .pred p;\nmbarrier.try_wait.parity.shared::cta.b64 p, [%1], %2;\nselp.u32 %0, 1, 0, p;\n}" : "=r"(ok) : "r"(bar), "r"(parity) : "memory");
  return ok;
}
__device__ __forceinline__ uint32_t mbar_test(uint32_t bar, uint32_t parity) {
  uint32_t ok;
  asm volatile("{\n.reg .pred p;\nmbarrier.test_wait.parity.shared::cta.b64 p, [%1], %2;\nselp.u32 %0, 1, 0, p;\n}" : "=r"(ok) : "r"(bar), "r"(parity) : "memory");
  return ok;
}
constexpr unsigned long long WATCHDOG_NS = 2000000000ull;
__device__ __forceinline__ unsigned long long gtime() { unsigned long long t; asm volatile("mov.u64 %0, %%globaltimer;" : "=l"(t)); return t; }
__device__ __forceinline__ uint32_t clock32() { uint32_t t; asm volatile("mov.u32 %0, %%clock;" : "=r"(t)); return t; }
__device__ __forceinline__ void mbar_wait_bounded(uint32_t bar, uint32_t parity) {
  unsigned long long t0 = 0;
  for (;;) {
    uint32_t ok;
    asm volatile("{\n.reg .pred p;\nmbarrier.try_wait.parity.shared::cta.b64 p, [%1], %2;\nselp.u32 %0, 1, 0, p;\n}" : "=r"(ok) : "r"(bar), "r"(parity) : "memory");
    if (ok) break;
    const unsigned long long t1 = gtime();
    if (t0 == 0) t0 = t1;
    if (t1 - t0 > WATCHDOG_NS) __trap();
  }
}
__device__ __forceinline__ void tma2d(uint32_t dst, const CUtensorMap* m, int c0, int c1, uint32_t bar) {
  asm volatile("cp.async.bulk.tensor.2d.shared::cluster.global.mbarrier::complete_tx::bytes [%0], [%1, {%3, %4}], [%2];"
               ::"r"(dst), "l"(m), "r"(bar), "r"(c0), "r"(c1) : "memory");
}
__device__ __forceinline__ void tma3d(uint32_t dst, const CUtensorMap* m, int c0, int c1, int c2, uint32_t bar) {
  asm volatile("cp.async.bulk.tensor.3d.shared::cluster.global.mbarrier::complete_tx::bytes [%0], [%1, {%3, %4, %5}], [%2];"
               ::"r"(dst), "l"(m), "r"(bar), "r"(c0), "r"(c1), "r"(c2) : "memory");
}
__device__ __forceinline__ void bulk_load(uint32_t dst, const void* src, uint32_t bytes, uint32_t bar) {
  asm volatile("cp.async.bulk.shared::cluster.global.mbarrier::complete_tx::bytes [%0], [%1], %2, [%3];" ::"r"(dst), "l"(src), "r"(bytes), "r"(bar) : "memory");
}
__device__ __forceinline__ void bulk_store(void* dst, uint32_t src, uint32_t bytes) {
  asm volatile("cp.async.bulk.global.shared::cta.bulk_group [%0], [%1], %2;" ::"l"(dst), "r"(src), "r"(bytes) : "memory");
}
__device__ __forceinline__ void st_async4(uint32_t dst, const uint32_t (&v)[4], uint32_t bar) {
  asm volatile("st.async.shared::cluster.mbarrier::complete_tx::bytes.v4.b32 [%0], {%1, %2, %3, %4}, [%5];" ::"r"(dst), "r"(v[0]), "r"(v[1]), "r"(v[2]), "r"(v[3]), "r"(bar) : "memory");
}
__device__ __forceinline__ void bulk_commit() { asm volatile("cp.async.bulk.commit_group;" ::: "memory"); }
__device__ __forceinline__ void bulk_prefetch(const void* p, uint32_t bytes) {
  asm volatile("cp.async.bulk.prefetch.L2.global [%0], %1;" ::"l"(p), "r"(bytes) : "memory");
}
__device__ __forceinline__ void tma2d_store(const CUtensorMap* m, uint32_t src, int c0, int c1) {
  asm volatile("cp.async.bulk.tensor.2d.global.shared::cta.bulk_group [%0, {%2, %3}], [%1];" ::"l"(m), "r"(src), "r"(c0), "r"(c1) : "memory");
}
__device__ __forceinline__ void wg_fence() { asm volatile("wgmma.fence.sync.aligned;" ::: "memory"); }
__device__ __forceinline__ void wg_commit() { asm volatile("wgmma.commit_group.sync.aligned;" ::: "memory"); }
template <int N> __device__ __forceinline__ void wg_wait() { asm volatile("wgmma.wait_group.sync.aligned %0;" ::"n"(N) : "memory"); }
__device__ __forceinline__ void fence_async_smem() { asm volatile("fence.proxy.async.shared::cta;" ::: "memory"); }
__device__ __forceinline__ void fence_async_global() { asm volatile("fence.proxy.async.global;" ::: "memory"); }
__device__ __forceinline__ void fence_release() { asm volatile("fence.release.gpu;" ::: "memory"); }
__device__ __forceinline__ void fence_acquire() { asm volatile("fence.acquire.gpu;" ::: "memory"); }
__device__ __forceinline__ void nb_sync(int id, int n) { asm volatile("bar.sync %0, %1;" ::"r"(id), "r"(n) : "memory"); }
__device__ __forceinline__ void nb_arrive(int id, int n) { asm volatile("bar.arrive %0, %1;" ::"r"(id), "r"(n) : "memory"); }
__device__ __forceinline__ void stsm4(uint32_t addr, uint32_t r0, uint32_t r1, uint32_t r2, uint32_t r3) {
  asm volatile("stmatrix.sync.aligned.m8n8.x4.shared.b16 [%0], {%1, %2, %3, %4};" ::"r"(addr), "r"(r0), "r"(r1), "r"(r2), "r"(r3) : "memory");
}
__device__ __forceinline__ void stsm4t(uint32_t addr, uint32_t r0, uint32_t r1, uint32_t r2, uint32_t r3) {
  asm volatile("stmatrix.sync.aligned.m8n8.x4.trans.shared.b16 [%0], {%1, %2, %3, %4};" ::"r"(addr), "r"(r0), "r"(r1), "r"(r2), "r"(r3) : "memory");
}
__device__ __forceinline__ void st_relaxed4(void* p, const uint32_t (&v)[4]) {
  asm volatile("st.relaxed.gpu.global.v4.u32 [%0], {%1, %2, %3, %4};" ::"l"(p), "r"(v[0]), "r"(v[1]), "r"(v[2]), "r"(v[3]) : "memory");
}
__device__ __forceinline__ void sts128(uint32_t addr, uint32_t a, uint32_t b, uint32_t c, uint32_t d) {
  asm volatile("st.shared.v4.b32 [%0], {%1, %2, %3, %4};" ::"r"(addr), "r"(a), "r"(b), "r"(c), "r"(d) : "memory");
}
__device__ __forceinline__ uint32_t pack2(float lo, float hi) {
  uint32_t r; asm("cvt.rn.bf16x2.f32 %0, %1, %2;" : "=r"(r) : "f"(hi), "f"(lo)); return r;
}
__device__ __forceinline__ float bf_lo(uint32_t v) { return __uint_as_float(v << 16); }
__device__ __forceinline__ float bf_hi(uint32_t v) { return __uint_as_float(v & 0xffff0000u); }
__device__ __forceinline__ float bf_round(float v) { return __bfloat162float(__float2bfloat16_rn(v)); }
__device__ __forceinline__ void ldsm4(uint32_t addr, uint32_t (&r)[4]) {
  asm volatile("ldmatrix.sync.aligned.m8n8.x4.shared.b16 {%0, %1, %2, %3}, [%4];" : "=r"(r[0]), "=r"(r[1]), "=r"(r[2]), "=r"(r[3]) : "r"(addr) : "memory");
}
__device__ __forceinline__ uint4 lds128(uint32_t addr) {
  uint4 v; asm volatile("ld.volatile.shared.v4.u32 {%0, %1, %2, %3}, [%4];" : "=r"(v.x), "=r"(v.y), "=r"(v.z), "=r"(v.w) : "r"(addr) : "memory"); return v;
}
__device__ __forceinline__ uint2 lds64(uint32_t addr) { uint2 v; asm volatile("ld.volatile.shared.v2.u32 {%0, %1}, [%2];" : "=r"(v.x), "=r"(v.y) : "r"(addr) : "memory"); return v; }
__device__ __forceinline__ uint32_t lds32(uint32_t addr) { uint32_t v; asm volatile("ld.volatile.shared.u32 %0, [%1];" : "=r"(v) : "r"(addr) : "memory"); return v; }
__device__ __forceinline__ uint32_t ld_generic(const void* p) { uint32_t v; asm volatile("ld.volatile.u32 %0, [%1];" : "=r"(v) : "l"(p) : "memory"); return v; }
__device__ __forceinline__ void sts32(uint32_t addr, uint32_t v) { asm volatile("st.shared.u32 [%0], %1;" ::"r"(addr), "r"(v) : "memory"); }
__device__ __forceinline__ uint32_t fma_bf2(uint32_t a, uint32_t b, uint32_t c) { uint32_t r; asm("fma.rn.bf16x2 %0, %1, %2, %3;" : "=r"(r) : "r"(a), "r"(b), "r"(c)); return r; }
__device__ __forceinline__ uint32_t mul_bf2(uint32_t a, uint32_t b) { uint32_t r; asm("mul.rn.bf16x2 %0, %1, %2;" : "=r"(r) : "r"(a), "r"(b)); return r; }
__device__ __forceinline__ unsigned ld_relaxed(const unsigned* p) { unsigned v; asm volatile("ld.relaxed.gpu.global.u32 %0, [%1];" : "=r"(v) : "l"(p) : "memory"); return v; }
__device__ __forceinline__ void st_relaxed(unsigned* p, unsigned v) { asm volatile("st.relaxed.gpu.global.u32 [%0], %1;" ::"l"(p), "r"(v) : "memory"); }
__device__ __forceinline__ uint4 ld_relaxed4(const void* p) {
  uint4 v; asm volatile("ld.relaxed.gpu.global.v4.u32 {%0, %1, %2, %3}, [%4];" : "=r"(v.x), "=r"(v.y), "=r"(v.z), "=r"(v.w) : "l"(p) : "memory"); return v;
}
__device__ __forceinline__ float4 ld_relaxed_f4(const void* p) {
  float4 v; asm volatile("ld.relaxed.gpu.global.v4.f32 {%0, %1, %2, %3}, [%4];" : "=f"(v.x), "=f"(v.y), "=f"(v.z), "=f"(v.w) : "l"(p) : "memory"); return v;
}
__device__ __forceinline__ void red_add4(void* p, float a, float b, float c, float d) {
  asm volatile("red.relaxed.gpu.global.add.v4.f32 [%0], {%1, %2, %3, %4};" ::"l"(p), "f"(a), "f"(b), "f"(c), "f"(d) : "memory");
}
__device__ __forceinline__ void red_add_bf(void* p, uint32_t a, uint32_t b, uint32_t c) {
  asm volatile("red.relaxed.gpu.global.add.noftz.v4.bf16x2 [%0], {%1, %2, %3, %4};" ::"l"(p), "r"(a), "r"(b), "r"(c), "r"(0x3F803F80u) : "memory");
}
__device__ __forceinline__ void red_add(unsigned* p, unsigned v) { asm volatile("red.relaxed.gpu.global.add.u32 [%0], %1;" ::"l"(p), "r"(v) : "memory"); }
__device__ __forceinline__ float rcp(float v) { float r; asm("rcp.approx.ftz.f32 %0, %1;" : "=f"(r) : "f"(v)); return r; }
__device__ __forceinline__ float sigmoidf_(float v) { return rcp(1.f + __expf(-v)); }
__device__ __forceinline__ uint32_t phi2(float a, float b, float l2e = 1.4426950408889634f) {
  float ea, eb;
  asm("ex2.approx.ftz.f32 %0, %1;" : "=f"(ea) : "f"(a * l2e));
  asm("ex2.approx.ftz.f32 %0, %1;" : "=f"(eb) : "f"(b * l2e));
  uint32_t t = pack2(a, b), e = pack2(ea, eb), r;
  asm("max.NaN.bf16x2 %0, %0, %1;" : "+r"(t) : "r"(0x35863586u));
  asm("min.bf16x2 %0, %0, %1;" : "+r"(e) : "r"(0x3F803F80u));
  asm("add.rn.bf16x2 %0, %1, %2;" : "=r"(r) : "r"(t), "r"(e));
  return r;
}
__device__ __forceinline__ uint64_t mkdesc(uint32_t addr, uint32_t lbo, uint32_t sbo, uint32_t sw) {
  return (uint64_t)(((addr & 0x3FFFF) >> 4) | ((lbo >> 4) << 16)) | ((uint64_t)((sbo >> 4) | (sw << 30)) << 32);
}

template <int TA, int TB>
__device__ __forceinline__ void mma128(float (&d)[64], uint64_t da, uint64_t db, int sc) {
  asm volatile("{\n.reg .pred p;\nsetp.ne.b32 p, %66, 0;\n"
    "wgmma.mma_async.sync.aligned.m64n128k16.f32.bf16.bf16 "
    "{%0,%1,%2,%3,%4,%5,%6,%7,%8,%9,%10,%11,%12,%13,%14,%15,%16,%17,%18,%19,%20,%21,%22,%23,"
    "%24,%25,%26,%27,%28,%29,%30,%31,%32,%33,%34,%35,%36,%37,%38,%39,%40,%41,%42,%43,%44,%45,%46,%47,"
    "%48,%49,%50,%51,%52,%53,%54,%55,%56,%57,%58,%59,%60,%61,%62,%63}, "
    "%64, %65, p, 1, 1, %67, %68;\n}\n"
    : "+f"(d[0]), "+f"(d[1]), "+f"(d[2]), "+f"(d[3]), "+f"(d[4]), "+f"(d[5]), "+f"(d[6]), "+f"(d[7]),
      "+f"(d[8]), "+f"(d[9]), "+f"(d[10]), "+f"(d[11]), "+f"(d[12]), "+f"(d[13]), "+f"(d[14]), "+f"(d[15]),
      "+f"(d[16]), "+f"(d[17]), "+f"(d[18]), "+f"(d[19]), "+f"(d[20]), "+f"(d[21]), "+f"(d[22]), "+f"(d[23]),
      "+f"(d[24]), "+f"(d[25]), "+f"(d[26]), "+f"(d[27]), "+f"(d[28]), "+f"(d[29]), "+f"(d[30]), "+f"(d[31]),
      "+f"(d[32]), "+f"(d[33]), "+f"(d[34]), "+f"(d[35]), "+f"(d[36]), "+f"(d[37]), "+f"(d[38]), "+f"(d[39]),
      "+f"(d[40]), "+f"(d[41]), "+f"(d[42]), "+f"(d[43]), "+f"(d[44]), "+f"(d[45]), "+f"(d[46]), "+f"(d[47]),
      "+f"(d[48]), "+f"(d[49]), "+f"(d[50]), "+f"(d[51]), "+f"(d[52]), "+f"(d[53]), "+f"(d[54]), "+f"(d[55]),
      "+f"(d[56]), "+f"(d[57]), "+f"(d[58]), "+f"(d[59]), "+f"(d[60]), "+f"(d[61]), "+f"(d[62]), "+f"(d[63])
    : "l"(da), "l"(db), "r"(sc), "n"(TA), "n"(TB));
}

__device__ __forceinline__ void mma_ktv(float (&d)[36], const uint32_t (&a)[4], uint64_t db, int sc) {
  asm volatile("{\n.reg .pred p;\nsetp.ne.b32 p, %41, 0;\n"
    "wgmma.mma_async.sync.aligned.m64n72k16.f32.bf16.bf16 "
    "{%0,%1,%2,%3,%4,%5,%6,%7,%8,%9,%10,%11,%12,%13,%14,%15,%16,%17,%18,%19,%20,%21,%22,%23,"
    "%24,%25,%26,%27,%28,%29,%30,%31,%32,%33,%34,%35}, "
    "{%36,%37,%38,%39}, %40, p, 1, 1, 0;\n}\n"
    : "+f"(d[0]), "+f"(d[1]), "+f"(d[2]), "+f"(d[3]), "+f"(d[4]), "+f"(d[5]), "+f"(d[6]), "+f"(d[7]),
      "+f"(d[8]), "+f"(d[9]), "+f"(d[10]), "+f"(d[11]), "+f"(d[12]), "+f"(d[13]), "+f"(d[14]), "+f"(d[15]),
      "+f"(d[16]), "+f"(d[17]), "+f"(d[18]), "+f"(d[19]), "+f"(d[20]), "+f"(d[21]), "+f"(d[22]), "+f"(d[23]),
      "+f"(d[24]), "+f"(d[25]), "+f"(d[26]), "+f"(d[27]), "+f"(d[28]), "+f"(d[29]), "+f"(d[30]), "+f"(d[31]),
      "+f"(d[32]), "+f"(d[33]), "+f"(d[34]), "+f"(d[35])
    : "r"(a[0]), "r"(a[1]), "r"(a[2]), "r"(a[3]), "l"(db), "r"(sc));
}

__device__ __forceinline__ void mma_qkvz(float (&d)[20], uint64_t da, uint64_t db, int sc) {
  asm volatile("{\n.reg .pred p;\nsetp.ne.b32 p, %22, 0;\n"
    "wgmma.mma_async.sync.aligned.m64n40k16.f32.bf16.bf16 "
    "{%0,%1,%2,%3,%4,%5,%6,%7,%8,%9,%10,%11,%12,%13,%14,%15,%16,%17,%18,%19}, "
    "%20, %21, p, 1, 1, 0, 1;\n}\n"
    : "+f"(d[0]), "+f"(d[1]), "+f"(d[2]), "+f"(d[3]), "+f"(d[4]), "+f"(d[5]), "+f"(d[6]), "+f"(d[7]),
      "+f"(d[8]), "+f"(d[9]), "+f"(d[10]), "+f"(d[11]), "+f"(d[12]), "+f"(d[13]), "+f"(d[14]), "+f"(d[15]),
      "+f"(d[16]), "+f"(d[17]), "+f"(d[18]), "+f"(d[19])
    : "l"(da), "l"(db), "r"(sc));
}

template <int N> __device__ __forceinline__ void pin(float (&d)[N]) {
#pragma unroll
  for (int i = 0; i < N; i++) asm volatile("" : "+f"(d[i])::"memory");
}

struct Params {
  CUtensorMap x, w, xr, gate, up, wo, out, down, xh;
};

__device__ __forceinline__ uint32_t dup_lo(uint32_t v) { uint32_t r; asm("{\n.reg .b16 l, h;\nmov.b32 {l, h}, %1;\nmov.b32 %0, {l, l};\n}" : "=r"(r) : "r"(v)); return r; }
__device__ __forceinline__ uint32_t dup_hi(uint32_t v) { uint32_t r; asm("{\n.reg .b16 l, h;\nmov.b32 {l, h}, %1;\nmov.b32 %0, {h, h};\n}" : "=r"(r) : "r"(v)); return r; }
__device__ __forceinline__ float butterfly8(float (&s)[8], int lane, int o) {
#pragma unroll
  for (int k = 1; k < 8; k <<= 1) {
    const bool up = lane & (o * k);
#pragma unroll
    for (int j = 0; j < 4 / k; j++) s[j] = (up ? s[2 * j + 1] : s[2 * j]) + __shfl_xor_sync(~0u, up ? s[2 * j] : s[2 * j + 1], o * k);
  }
  return s[0];
}
constexpr int OWN = 8, PEER = 9;
static_assert((OA_SLOTS >> OWN * 4 & 15) * SLOT == OFF_V && (OA_SLOTS >> PEER * 4 & 15) * SLOT == OFF_PK, "");
constexpr uint64_t OR_SLOTS = (OA_SLOTS & 0xFFFFFFFFu) | OA_SLOTS >> 40 << 32;
template <class F> __device__ __forceinline__ void verify_tiles(uint32_t sb, Scratch* gs, int tm, int tn, int w, int lane, F between) {
  const uint32_t par = lds32(sb + OFF_MISC + 24), fix = sb + BAR_FIX + w * 8;
  uint64_t slots = OR_SLOTS, full = 0x04321021043210ull;
#pragma unroll 1
  for (int i = 0; i < 14; i++, slots >>= 4, full >>= 4) {
    const uint32_t a = sb + OFF_RING + ((uint32_t)slots & 15) * SLOT + w * 1024, cw = a + lane * 32 + (lane >> 2) * 4;
    if (i == 4) mbar_wait(sb + BAR_EMPTY + 7 * 8, 1);
    if (i == 8) between();
    mbar_wait(sb + BAR_LAND + (i & 7) * 8, i >> 3);
    if (i >> 1 == 4) PROF(w == 0 && lane == 0, 33 + i);
    for (;;) {
      const uint32_t u0 = lds32(cw), u1 = lds32(cw + 4096), u2 = lds32(cw + 8192), u3 = lds32(cw + 12288);
      if (__all_sync(~0u, !(mism(mism(u0, u1, par), mism(u2, u3, par), 0) & 1))) break;
      const uint4* src = gs->o[tm][i < 8 + (tn & 6) ? i : i + 2] + w * 64;
      const uint32_t ph = !mbar_test(fix, 1);
      fence_async_smem();
      __syncwarp();
      if (elect()) {
        mbar_expect_tx(fix, 4096);
#pragma unroll 1
        for (int j = 0; j < 4; j++) bulk_load(a + j * 4096, src + j * 256, 1024, fix);
      }
      mbar_wait(fix, ph);
    }
    mbar_arrive_warp(sb + BAR_OFULL + ((uint32_t)full & 7) * 8);
    if (i == 8) PROF(w == 3 && lane == 0, 28);
  }
}
template <bool BY_SM> struct Tile {
  int sm, tm, tn, mu;
  bool spare;
  __device__ __forceinline__ Tile() {
    if (BY_SM) asm volatile("mov.u32 %0, %%smid;" : "=r"(sm));
    else sm = blockIdx.x + (blockIdx.x >= 120) * 4;
    const int tp = sm >> 1, pr = sm & 1;
    const int v = tp < 32 ? tp : tp < 60 ? (tp * 293 - 928) >> 8 : tp * 8 - 464, g = v & 7, i = v >> 3;
    tm = (v & 6) * 2 + (i & 3); tn = (v & 1) * 4 + (v >> 4 & 2) + pr;
    mu = i == 5 ? 112 : g * 14 + (i - (i > 5)) * 2 + pr;
    spare = (tp | 1) == 61;
  }
};

template <bool BY_SM> __global__ void __cluster_dims__(2, 1, 1) __launch_bounds__(NTHREADS, 1) fused_kernel(const __nv_bfloat16* __restrict__ px, Scratch* gs, const __nv_bfloat16* __restrict__ w_gate,
             const __nv_bfloat16* __restrict__ w_up, const __nv_bfloat16* __restrict__ w_r, const __nv_bfloat16* __restrict__ gate_w, __nv_bfloat16* __restrict__ pout,
             const __grid_constant__ Params p) {
  extern __shared__ __align__(1024) uint8_t smem[];
  const uint32_t sb = __shfl_sync(~0u, (uint32_t)__cvta_generic_to_shared(smem), 0);
  const int tid = threadIdx.x, lane = tid & 31;
  const int warp = __shfl_sync(~0u, tid >> 5, 0), wg = warp >> 2;
  const uint32_t t_start = clock32();
  const Tile<BY_SM> tile;
  const int tm = tile.tm, tn = tile.tn, mu = tile.mu, cta = tm * 8 + tn;
  const uint32_t zero = tile.sm >> 12;
  if (warp == 0) {
#pragma unroll
    for (int s = 0; s < PRE; s++)
      if (elect()) mbar_init(sb + BAR_FULL + s * 8, 1);
    asm volatile("fence.mbarrier_init.release.cluster;" ::: "memory");
    if (!tile.spare) {
#pragma unroll
      for (int s = 0; s < PRE; s++) {
        if (elect()) tma3d(sb + OFF_W1 + s * WQKV_BYTES, &p.w, tn * 64, s * 64, 0, sb + BAR_FULL + s * 8);
        if (elect()) tma2d(sb + OFF_RING + s * SLOT, &p.x, s * 64, tm * 128, sb + BAR_FULL + s * 8);
        PROF(lane == 0, 64 + s);
      }
      if (elect()) {
#pragma unroll
        for (int s = 0; s < PRE; s++) mbar_expect_tx(sb + BAR_FULL + s * 8, SLOT + WQKV_BYTES);
      }
    }
  }
  if (warp) {
    const int wi = warp == 15 ? 0 : warp;
    const int cnt = wi < 7 ? 1 : wi < 13 ? 4 : 5;
#pragma unroll
    for (int i = 0; i < 4; i++)
      if ((i >= PRE || wi) && elect()) mbar_init(sb + OFF_BAR + wi * 32 + i * 8, cnt);
    asm volatile("fence.mbarrier_init.release.cluster;" ::: "memory");
  }
  __syncthreads();
  if (tile.spare) {
    if (warp == 0) {
      const unsigned tag = (ld_relaxed(&gs->spare[tile.sm & 3]) + 1) & 0xFFF;
      const unsigned long long t0 = gtime();
      uint4 r4;
      do {
        __nanosleep(2048);
        if (gtime() - t0 > WATCHDOG_NS) __trap();
        r4 = ld_relaxed4(&gs->rslot[tile.sm & 3][lane * 4]);
      } while (!__all_sync(~0u, (((r4.x ^ tag) | (r4.y ^ tag) | (r4.z ^ tag) | (r4.w ^ tag)) & 0xFFF) == 0));
      if (tid == 0) st_relaxed(&gs->spare[tile.sm & 3], tag);
    }
    return;
  }

  auto patch_row = [&](int pw) {
    const unsigned key = lds32(sb + OFF_MISC + 16);
    const int sel = 0xFFFF - (int)(key & 0xFFFF) - tm * 128;
    if (pw == 0 && sel >= 0 && sel < 128) {
      const unsigned k16 = key >> 16;
      const float rs = bf_round(sigmoidf_(__uint_as_float(((k16 & 0x8000u) ? (k16 & 0x7FFFu) : (~k16 & 0xFFFFu)) << 16)));
      float v[12];
      const float4* yp = gs->y[lane >> 4][0] + tn * 16 + (lane & 15);
      for (;;) {
#pragma unroll
        for (int i = 0; i < 3; i++) {
          const float4 u = ld_relaxed_f4(yp + i * 128);
          v[4 * i] = u.x; v[4 * i + 1] = u.y; v[4 * i + 2] = u.z; v[4 * i + 3] = u.w;
        }
        const float n = v[3] + v[7] + v[11];
        if (__all_sync(~0u, n + __shfl_xor_sync(~0u, n, 16) == 3.f * MOD_CTAS)) break;
        __nanosleep(Y_SLEEP);
      }
#pragma unroll
      for (int i = 0; i < 10; i++) v[i] = bf_round(bf_round(v[i] + __shfl_xor_sync(~0u, v[i], 16)) * rs);
      PROF(lane == 0, 24);
      mbar_wait(sb + BAR_X, 0);
      if (lane < 16) {
        uint4* xp = (uint4*)(smem + res_off(lane >> 3, sel >> 6) + (sel & 63) * 128 + (((lane ^ sel) & 7) << 4));
        const uint4 xv = *xp;
        *xp = make_uint4(pack2(bf_lo(xv.x) + v[0], bf_hi(xv.x) + v[1]), pack2(bf_lo(xv.y) + v[2], bf_hi(xv.y) + v[4]),
                         pack2(bf_lo(xv.z) + v[5], bf_hi(xv.z) + v[6]), pack2(bf_lo(xv.w) + v[8], bf_hi(xv.w) + v[9]));
      }
      __syncwarp();
      mbar_arrive_warp(sb + BAR_Y);
    }
  };
  if (wg == 3) {
    asm volatile("setmaxnreg.dec.sync.aligned.u32 24;");
    if (warp == 12) {
      mbar_wait(sb + BAR_GATE, 0);
      uint64_t slots = OR_SLOTS, deps = 0x8CBA98A9877654ull;
      uint32_t seen;
#pragma unroll 1
      for (int i = 0; i < 14; i++, deps >>= 4, slots >>= 4) {
        const uint32_t slab = i < 8 + (tn & 6) ? i : i + 2;
        if (!(i & 7)) { mbar_wait(sb + BAR_PUB + (i & 8), 0); seen = 0; }
        if (!(seen >> (slab & 7) * 4 & 4))
          while (!((seen = __shfl_sync(~0u, ld_relaxed(gs->cnt[(i & 8) * 2 + tm]), 0)) >> (slab & 7) * 4 & 4)) __nanosleep(B_SLEEP);
        if (i == 8) mbar_wait(sb + BAR_OWN, 0);
        mbar_wait(sb + BAR_EMPTY + ((uint32_t)deps & 15) * 8, (i & 7) < 5);
        if (elect()) bulk_load(sb + OFF_RING + ((uint32_t)slots & 15) * SLOT, gs->o[tm][slab], SLOT, sb + BAR_LAND + (i & 7) * 8);
        if (elect()) mbar_expect_tx(sb + BAR_LAND + (i & 7) * 8, SLOT);
        PROF(lane == 0, 44 + i);
        if (i == 8) PROF(lane == 0, 43);
      }
    } else if (warp == 13) {
#pragma unroll 1
      for (int g = PRE; g < 32; g++) {
        const bool reuse = (g >> 2) == 4;
        const uint32_t s = g & 3, full = sb + BAR_FULL + (g & 7) * 8, c0 = tn * 64 + (g & 16) * 32, c1 = (g < 16 ? g : g - 4 & 15) * 64;
        if (g < 4) while ((int)(clock32() - t_start) < g * ST1) {}
        mbar_wait(sb + BAR_EMPTY + (g + 4 & 7) * 8, (g + 4 >> 3 & 1) ^ 1);
        if (!reuse && elect()) tma2d(sb + OFF_RING + s * SLOT, &p.x, c1, tm * 128, full);
        if (elect()) tma3d(sb + OFF_W1 + s * WQKV_BYTES, &p.w, c0, c1, 0, full);
        if (elect()) mbar_expect_tx(full, reuse ? WQKV_BYTES : SLOT + WQKV_BYTES);
        PROF(lane == 0, 64 + g);
        const uint32_t i = g - RT_G0;
        if (i < 4 && elect()) {
          mbar_expect_tx(sb + BAR_RT + i * 8, i ? 8192 : 8192 + 4096);
          tma2d(sb + OFF_PK + i * 8192 + (i == 3) * 1024, &p.xr, ((i + RT_ROT) & 3) * 256, cta * 16, sb + BAR_RT + i * 8);
          if (i == 0) { bulk_load(sb + OFF_KVB, w_r, 2048, sb + BAR_RT); bulk_load(sb + OFF_KVB + 2048, gate_w, 2048, sb + BAR_RT); }
        }
        const uint32_t c = g - MOD_START;
        if (c == MOD_BUFS) mbar_wait(sb + BAR_RTD, 0);
        if (c < MOD_BUFS0 && mu < MOD_CTAS && elect()) {
          PROF(true, 192 + c);
          const uint32_t mb = c < MOD_BUFS ? c + 2 : c - MOD_BUFS, mfull = sb + BAR_MFULL + mb * 8, mdst = sb + OFF_V + mb * MOD_STEP;
          mbar_expect_tx(mfull, c ? 8192 : 8192 + 2048);
          tma3d(mdst, &p.gate, mu * 32, c * 16, 0, mfull); tma3d(mdst + 4096, &p.up, mu * 32, c * 16, 0, mfull);
        }
        const uint32_t pc = g - PF_MOD;
        if (pc < 16 && elect()) bulk_prefetch((cta & 64 ? w_up : w_gate) + (size_t)(pc * 64 + (cta & 63)) * F_, F_ * 2);
      }
      mbar_arrive_warp(sb + BAR_GATE);
      const uint32_t lowb = (1u << (tn & 6) * 4) - 1;
      uint64_t slabs = (uint64_t)((0xFEDCBA98u & lowb) | (0xFEDCBAu & ~lowb)) << 40 | (uint64_t)(8 + (tn ^ 1)) << 36 | (uint64_t)(8 + tn) << 32 | 0x76543210u;
      uint64_t deps = 0x8CBA98CBA9876554ull, ws = OW_SLOTS;
      uint32_t full = sb + BAR_OFULL, ph = 1;
#pragma unroll 1
      for (int g = 0; g < 16; g++, slabs >>= 4, deps >>= 4, ws >>= 4) {
        mbar_wait(sb + BAR_EMPTY + ((uint32_t)deps & 15) * 8, ph);
        if (elect()) tma3d(sb + OFF_RING + ((uint32_t)ws & 15) * SLOT, &p.wo, 0, ((uint32_t)slabs & 15) * 64, tn * 2, full);
        if (elect()) mbar_expect_tx(full, SLOT);
        PROF(lane == 0, 96 + g);
        if (g >> 1 == OWN / 2 && lane < 4) mbar_arrive(full);
        full += 8;
        if (full == sb + BAR_OFULL + 40) { full -= 40; ph ^= 1; }
      }
    } else if (warp == 14) {
      if (mu < MOD_CTAS) {
        uint32_t full = sb + BAR_MFULL + 16, dst = sb + OFF_MOD, ph = 0;
#pragma unroll 1
        for (int c = MOD_BUFS0; c < 24; c++) {
          mbar_wait(full + (BAR_MEMPTY - BAR_MFULL), ph);
          PROF(lane == 0, 192 + c);
          if (c < 16) {
            if (elect()) { tma3d(dst, &p.gate, mu * 32, c * 16, 0, full); tma3d(dst + 4096, &p.up, mu * 32, c * 16, 0, full); }
          } else if (elect()) tma3d(dst, &p.down, 0, mu * 32 + (c - 16) * 4, 0, full);
          if (elect()) mbar_expect_tx(full, 8192);
          full += 8; dst += MOD_STEP;
          if (full == sb + BAR_MFULL + MOD_BUFS0 * 8) { full -= MOD_BUFS * 8; dst = sb + OFF_MOD; ph ^= 1; }
        }
      }
      if (elect()) {
      mbar_wait(sb + BAR_IDX, 0);
      const bool paired = PAIRED && ld_relaxed(&gs->block[cta ^ 1]) == (blockIdx.x ^ 1);
      if (paired) mbar_expect_tx(sb + BAR_PEER, SLOT);
      mbar_expect_tx(sb + BAR_X, 32768);
      {
        if (mu < MOD_CTAS) {
          mbar_wait(sb + BAR_MEMPTY + 3 * 8, 0);
          mbar_wait(sb + BAR_MEMPTY + 4 * 8, 0);
          mbar_wait(sb + BAR_MEMPTY + 2 * 8, 1);
        } else mbar_wait(sb + BAR_GATE, 0);
#pragma unroll
        for (int i = 0; i < 4; i++) {
          if (i == 3) mbar_wait(sb + BAR_OEMPTY + 3 * 8, 0);
          tma2d(sb + res_off(i >> 1, i & 1), &p.xh, tn * 128 + (i >> 1) * 64, tm * 128 + (i & 1) * 64, sb + BAR_X);
        }
      }
      if (!paired) {
        mbar_wait(sb + BAR_OWN, 0);
        while (!(ld_relaxed(gs->cnt[16 + tm]) & 4u << (tn ^ 1) * 4)) __nanosleep(32);
        fence_acquire();
        fence_async_global();
        const uint32_t par = lds32(sb + OFF_MISC + 24);
        for (uint32_t ph = !mbar_test(sb + BAR_MFULL, 1), bad = 1; bad & 1; ph ^= 1) {
          fence_async_smem();
          mbar_expect_tx(sb + BAR_MFULL, SLOT);
          bulk_load(sb + OFF_PK, gs->o[tm][8 + (tn ^ 1)], SLOT, sb + BAR_MFULL);
          mbar_wait(sb + BAR_MFULL, ph);
          bad = 0;
#pragma unroll 1
          for (int i = 0; i < 512; i++) bad |= lds32(sb + OFF_PK + i * 32 + (i & 28)) ^ par;
        }
        mbar_arrive(sb + BAR_PEER);
      }
      }
    } else {
#pragma unroll 1
      for (int i = 2; i < 9; i++)
        if (elect()) asm volatile("prefetch.tensormap [%0];" ::"l"(&p.x + i) : "memory");
      mbar_wait_bounded(sb + BAR_DONE, 0);
    }
  } else if (wg == 2) {
    asm volatile("setmaxnreg.dec.sync.aligned.u32 40;");
    const int mw = warp & 3;
    if (mw == 0) {
      const unsigned tag = (ld_relaxed(&gs->rslot[tn][cta]) + 1) & 0xFFF;
#pragma unroll
      for (int i = 0; i < 2; i++)
        if (lane < 28) ((float4*)gs)[cta * 56 + i * 28 + lane] = make_float4(0.f, 0.f, 0.f, 0.f);
      if (lane == 29) gs->block[cta] = blockIdx.x;
      fence_release();
      nb_sync(NB_KEY, 160);
      const uint4 k4 = lds128(sb + OFF_MISC);
      if (lane < 8) st_relaxed(&gs->rslot[lane][cta], max(max(k4.x, k4.y), max(k4.z, k4.w)) | tag);
      if (lane < 16) st_relaxed(&gs->gslot[cta * 16 + lane], lds32(sb + OFF_G + lane * 4) | tag);
      PROF(lane == 0, 20);
      uint4 r4;
      do {
        __nanosleep(RT_SLEEP);
        r4 = ld_relaxed4(&gs->rslot[tn][lane * 4]);
      } while (!__all_sync(~0u, (((r4.x ^ tag) | (r4.y ^ tag) | (r4.z ^ tag) | (r4.w ^ tag)) & 0xFFF) == 0));
      const int c0 = 0xFFF0 - lane * 64;
      unsigned key = max(max((r4.x & 0xFFFF0000u) | (c0 + ((r4.x >> 12) & 15)), (r4.y & 0xFFFF0000u) | (c0 - 16 + ((r4.y >> 12) & 15))),
                         max((r4.z & 0xFFFF0000u) | (c0 - 32 + ((r4.z >> 12) & 15)), (r4.w & 0xFFFF0000u) | (c0 - 48 + ((r4.w >> 12) & 15))));
      key = __reduce_max_sync(~0u, key);
      if (elect()) {
        sts32(sb + OFF_MISC + 16, key);
        sts32(sb + OFF_MISC + 24, tag & 1);
        if (mu < MOD_CTAS) {
          const __nv_bfloat16* row = px + (size_t)(0xFFFF - (key & 0xFFFF)) * D_;
          bulk_load(sb + OFF_XSEL, row, 1024, sb + BAR_MFULL + 16);
          bulk_load(sb + OFF_XSEL + MOD_STEP, row + 512, 1024, sb + BAR_MFULL + 16);
        }
      }
      PROF(lane == 0, 21);
      do {
        r4 = ld_relaxed4(&gs->gslot[tm * 128 + lane * 4]);
      } while (!__all_sync(~0u, (((r4.x ^ tag) | (r4.y ^ tag) | (r4.z ^ tag) | (r4.w ^ tag)) & 0xFFF) == 0));
      sts128(sb + OFF_G + lane * 16, r4.x & 0xFFFF0000u, r4.y & 0xFFFF0000u, r4.z & 0xFFFF0000u, r4.w & 0xFFFF0000u);
      fence_acquire();
      __syncwarp();
    }
    PROF(tid == 256, 22);
    if (mu >= MOD_CTAS) {
      mbar_arrive_warp(sb + BAR_IDX);
    } else {
      const uint32_t wp = sb + OFF_V + (mw >> 1) * 4096 + (mw & 1) * 512 + lane * 16;
      uint32_t mp = sb + OFF_XSEL + (mw & 1) * 64 + (lane >> 2) * 8, mc = 128;
      float acc[8] = {0.f, 0.f, 0.f, 0.f, 0.f, 0.f, 0.f, 0.f};
      uint32_t b = 2, ph = 0;
#pragma unroll 1
      for (int c = 0; c < 24; c++) {
        mbar_wait(sb + BAR_MFULL + b * 8, ph);
        PROF_C(tid == 256, 216 + c);
        const uint32_t a = wp + b * MOD_STEP;
        const uint2 m = lds64(mp);
        const uint4 w0 = lds128(a), w1 = lds128(a + 1024), w2 = lds128(a + 2048), w3 = lds128(a + 3072);
        mp += c == 7 ? MOD_STEP - 1024 + 128 : mc;
        const uint32_t m0 = dup_lo(m.x), m1 = dup_hi(m.x), m2 = dup_lo(m.y), m3 = dup_hi(m.y);
        uint4 q = make_uint4(mul_bf2(w0.x, m0), mul_bf2(w0.y, m0), mul_bf2(w0.z, m0), mul_bf2(w0.w, m0));
        q = make_uint4(fma_bf2(w1.x, m1, q.x), fma_bf2(w1.y, m1, q.y), fma_bf2(w1.z, m1, q.z), fma_bf2(w1.w, m1, q.w));
        q = make_uint4(fma_bf2(w2.x, m2, q.x), fma_bf2(w2.y, m2, q.y), fma_bf2(w2.z, m2, q.z), fma_bf2(w2.w, m2, q.w));
        mbar_arrive_warp(sb + BAR_MEMPTY + b * 8 + (w3.x & zero));
        q = make_uint4(fma_bf2(w3.x, m3, q.x), fma_bf2(w3.y, m3, q.y), fma_bf2(w3.z, m3, q.z), fma_bf2(w3.w, m3, q.w));
        if (++b == 5) b = c < 3 ? 0 : 2;
        if (b == 2) ph ^= 1;
        acc[0] += bf_lo(q.x); acc[1] += bf_hi(q.x); acc[2] += bf_lo(q.y); acc[3] += bf_hi(q.y);
        acc[4] += bf_lo(q.z); acc[5] += bf_hi(q.z); acc[6] += bf_lo(q.w); acc[7] += bf_hi(q.w);
        if (c == 15) {
          const uint32_t ft = fresh_tid(), fl = ft & 31;
          sts32(sb + OFF_PART + (ft & 96) * 4 + ((ft & 3) * 8 + (fl >> 2)) * 4, __float_as_uint(butterfly8(acc, fl, 4)));
          nb_sync(NB_MODW, 128);
          const float* part = (const float*)(smem + OFF_PART) + fl;
          const float gp = bf_round(part[0] + part[32]), up = bf_round(part[64] + part[96]);
          *(__nv_bfloat16*)(smem + OFF_PART + 512 + fl * 2) = __float2bfloat16_rn(bf_round(gp * sigmoidf_(gp)) * up);
          __syncwarp();
          mp = sb + OFF_PART + 512; mc = 8;
#pragma unroll
          for (int i = 0; i < 8; i++) acc[i] = 0.f;
          PROF(lane == 0 && mw == 0, 23);
        }
      }
      float4* yacc = gs->y[tn & 1][0] + (fresh_tid() & 127);
      red_add4(yacc, acc[0], acc[1], acc[2], 1.f);
      red_add4(yacc + 128, acc[3], acc[4], acc[5], 1.f);
      red_add4(yacc + 256, acc[6], acc[7], 0.f, 1.f);
      PROF(lane == 0 && mw == 0, 25);
    }
    mbar_wait(sb + BAR_GATE, 0);
    mbar_wait(sb + BAR_IDX, 0);
    verify_tiles(sb, gs, tm, tn, mw, lane, [&]() { patch_row(mw); });
  } else {
    asm volatile("setmaxnreg.inc.sync.aligned.u32 224;");
    const int w = warp & 3, wt = tid & 127;
    const int nb_self = NB_WG0 + wg;
    const uint64_t da0 = mkdesc(sb + OFF_RING, 16, 1024, 1), db0 = mkdesc(sb + OFF_RING, 8192, 1024, 1);

    if (wg == 1) {
      sts128(sb + OFF_ONES - (w >> 1) * 9216 + (w & 1) * 512 + lane * 16, 0x3F803F80u, 0x3F803F80u, 0x3F803F80u, 0x3F803F80u);
      sts32(sb + OFF_MISC + 20, 0x3FB8AA3Bu);
      fence_async_smem();
      float s[8] = {0.f, 0.f, 0.f, 0.f, 0.f, 0.f, 0.f, 0.f};
      uint32_t mask = 0xffff0000u;
#pragma unroll 1
      for (int i = 0; i < 4; i++) {
        const uint32_t u = (i + RT_ROT) & 3;
        mbar_wait(sb + BAR_RT + i * 8, 0);
        const uint4 wr = lds128(sb + OFF_KVB + u * 512 + lane * 16), gw = lds128(sb + OFF_KVB + 2048 + u * 512 + lane * 16);
        uint4 xv[4];
#pragma unroll
        for (int r = 0; r < 4; r++) xv[r] = lds128(sb + OFF_PK + i * 8192 + (i == 3) * 1024 + (w * 4 + r) * 512 + lane * 16);
        const float wf[16] = {bf_lo(wr.x), bf_hi(wr.x), bf_lo(wr.y), bf_hi(wr.y), bf_lo(wr.z), bf_hi(wr.z), bf_lo(wr.w), bf_hi(wr.w),
                              bf_lo(gw.x), bf_hi(gw.x), bf_lo(gw.y), bf_hi(gw.y), bf_lo(gw.z), bf_hi(gw.z), bf_lo(gw.w), bf_hi(gw.w)};
#pragma unroll
        for (int r = 0; r < 4; r++) {
          const uint4 xq = xv[r];
          const float xf[8] = {bf_lo(xq.x), __uint_as_float(xq.x & mask), bf_lo(xq.y), bf_hi(xq.y), bf_lo(xq.z), bf_hi(xq.z), bf_lo(xq.w), bf_hi(xq.w)};
#pragma unroll
          for (int j = 0; j < 8; j++) { s[2 * r] = fmaf(xf[j ^ 1], wf[j ^ 1], s[2 * r]); s[2 * r + 1] = fmaf(xf[j ^ 1], wf[8 + (j ^ 1)], s[2 * r + 1]); }
          mask = ((__float_as_uint(s[2 * r]) | __float_as_uint(s[2 * r + 1])) & zero) | 0xffff0000u;
        }
      }
      mbar_arrive_warp(sb + BAR_RTD + (__float_as_uint(s[6]) & zero));
      float v = butterfly8(s, lane, 1);
      PROF_C(wt == 0 && v != 12345.f, 19);
      v += __shfl_xor_sync(~0u, v, 8);
      v = bf_round(v + __shfl_xor_sync(~0u, v, 16));
      const unsigned rb = __float_as_uint(v) >> 16, row = w * 4 + ((lane & 7) >> 1);
      unsigned key = (lane & 1) ? 0u : ((((rb & 0x8000u) ? (~rb & 0xFFFFu) : (rb | 0x8000u)) << 16) | ((15 - row) << 12));
      key = __reduce_max_sync(~0u, key);
      if (lane == 0) sts32(sb + OFF_MISC + w * 4, key);
      if (lane < 8 && (lane & 1)) sts32(sb + OFF_G + row * 4, __float_as_uint(bf_round(sigmoidf_(v))));
      nb_arrive(NB_KEY, 160);
      nb_sync(NB_ORDER_AB, 256);
    }
    uint4* const kvacc = &gs->kv[wg][tn][0][wt];
    float aq[64];
    uint32_t su[9];
    {
      float ak[64], av[64], c[36];
      uint32_t pk[8][4];
      PROF_C(wt == 0, 1 + wg * 8);
#pragma unroll 1
      for (int g = 0; g < 16; g++) {
        const uint64_t dx = da0 + (g & 3) * (SLOT >> 4), dw = da0 + ((OFF_W1 >> 4) + (g & 3) * (WQKV_BYTES >> 4));
        mbar_wait(sb + BAR_FULL + (g & 7) * 8, g >> 3);
        if (g == 0) PROF_C(wt == 0, 2 + wg * 8);
        wg_fence();
#pragma unroll
        for (int kk = 0; kk < 4; kk++) mma128<1, 0>(ak, dw + (512 + kk * 128), dx + kk * 2, kk ? 1 : g);
        wg_commit();
        wg_wait<1>();
        if (g) mbar_arrive_warp(sb + BAR_EMPTY + (g - 1 & 7) * 8);
        wg_fence();
#pragma unroll
        for (int kk = 0; kk < 4; kk++) mma128<1, 0>(av, dw + (1024 + kk * 128), dx + kk * 2, kk ? 1 : g);
        wg_commit();
#pragma unroll
        for (int kk = 0; kk < 4; kk++) mma128<1, 0>(aq, dw + kk * 128, dx + kk * 2, kk ? 1 : g);
        wg_commit();
      }
      if (wg == 0) nb_arrive(NB_ORDER_AB, 256);
      mbar_wait(sb + BAR_IDX, 0);
      if (wg == 1) nb_sync(NB_STG, 256);
      wg_wait<2>();
      pin(ak);
      PROF_C(wt == 0, 3 + wg * 8);
      const uint32_t va = sb + OFF_V + (w * 16 + (lane & 15)) * 128;
      uint32_t lk[8];
#pragma unroll
      for (int u = 0; u < KL; u++) lk[u] = 0x3FB8AA3Bu;
#pragma unroll
      for (int u = 0; u < 8; u++) {
#pragma unroll
        for (int i = 0; i < 4; i++) pk[u][i] = phi2(ak[8 * u + 2 * i], ak[8 * u + 2 * i + 1], __uint_as_float(lk[u]));
        if (u == VK) { wg_wait<1>(); pin(av); }
        if (u == MM) { wg_wait<0>(); mbar_arrive_warp(sb + BAR_EMPTY + 7 * 8); }
        const uint32_t z = mism(pk[u][0], pk[u][1], 0) | mism(pk[u][2], pk[u][3], 0);
#pragma unroll
        for (int t = u < VK ? 8 : (u - VK) * 8 / (8 - VK); t < (u - VK + 1) * 8 / (8 - VK); t++) {
          const float* v = &av[8 * t];
          stsm4(va + (t >> 2) * 9216 + ((((lane >> 4) + 2 * (t & 3)) ^ (lane & 7)) << 4) + (z & zero), pack2(v[0], v[1]), pack2(v[2], v[3]), pack2(v[4], v[5]), pack2(v[6], v[7]));
        }
        if (u + KL < 8) lk[u + KL] = lds32(sb + OFF_MISC + 20 + (u < VK ? z & zero : 0));
      }
      fence_async_smem();
      nb_sync(nb_self, 128);
      PROF_C(wt == 0, 8 + wg * 8);
      const uint64_t dv = mkdesc(sb + OFF_V, 16, 1024, 1);
      wg_fence();
#pragma unroll
      for (int kk = 0; kk < 8; kk++) mma_ktv(c, pk[kk], dv + ((kk >> 2) * 576 + (kk & 3) * 2), kk ? 1 : 0);
      wg_commit();
      if (wg == 1) nb_arrive(NB_ORDER_BO, 256);
      wg_wait<0>();
      pin(c); pin(aq);
      PROF_C(wt == 0, 4 + wg * 8);
#pragma unroll
      for (int i = 0; i < 8; i++) {
        const int j = (i & 3) * 4 + (i >> 2) * 2;
        su[i] = w >= 2 ? pack2(c[16 + j], c[17 + j]) : pack2(c[j], c[j + 1]);
      }
      su[8] = pack2(c[32], c[34]);
#pragma unroll
      for (int u = 0; u < 3; u++)
        if (u < R0 || wg) red_add_bf(kvacc + u * 128, su[3 * u], su[3 * u + 1], su[3 * u + 2]);
    }
    const uint32_t par = lds32(sb + OFF_MISC + 24);
    {
      const bool paired = PAIRED && ld_relaxed(&gs->block[cta ^ 1]) == (blockIdx.x ^ 1);
      uint4 kv[3];
      int tries = wg ? 0 : RETRY + 1;
      const uint8_t* gl = smem + OFF_MISC + 20;
      asm volatile("" : "+l"(gl));
      const uint32_t l2e = ld_generic(gl);
    auto stage_kv = [&]() {
      const uint32_t kb = sb + OFF_KVB + w * 256, ka = kb + (lane & 3) * KVB_N + (lane >> 2) * 16;
      sts128(ka, kv[0].x, kv[0].y, kv[0].z, kv[1].x);
      sts128(ka + 128, kv[1].y, kv[1].z, kv[2].x, kv[2].y);
      sts32(kb + 4 * KVB_N + lane * 4, dup_lo(kv[2].z));
      sts32(kb + 4 * KVB_N + 128 + lane * 4, dup_hi(kv[2].z));
      return __all_sync(~0u, (kv[0].w & kv[1].w & kv[2].w) == 0x41804180u && (kv[0].w | kv[1].w | kv[2].w) == 0x41804180u);
    };
      const uint32_t qa = sb + OFF_PK + ((lane >> 4) * 8 + (lane & 7)) * 128 + (((2 * w + ((lane >> 3) & 1)) ^ (lane & 7)) << 4);
      uint32_t lq[8];
#pragma unroll
      for (int u = 0; u < QA; u++) lq[u] = l2e;
#pragma unroll
      for (int u = 0; u < 8; u++) {
        uint32_t r[4];
#pragma unroll
        for (int i = 0; i < 4; i++) r[i] = phi2(aq[8 * u + 2 * i], aq[8 * u + 2 * i + 1], __uint_as_float(lq[u]));
        stsm4t(qa + u * 2048, r[0], r[1], r[2], r[3]);
        if (u + 1 == KF && wg) {
          const uint4* src = kvacc + (r[3] & zero);
#pragma unroll
          for (int i = 0; i < 3; i++) kv[i] = ld_relaxed4(src + i * 128);
        }
        const int ru = u / RS + R0;
        if (u % RS == RS - 1 && ru < 3 && !wg) red_add_bf(kvacc + ru * 128, su[3 * ru], su[3 * ru + 1], su[3 * ru + 2]);
        if (u + QA < 8) lq[u + QA] = lds32(sb + OFF_MISC + 20);
      }
      PROF_C(wt == 0, 34 + wg * 2);
      bool have = wg && stage_kv();
      for (; !have; tries++) {
        if (tries > RETRY)
          while (ld_relaxed((const unsigned*)&(kvacc - lane)[256 + 31].w) != 0x41804180u) __nanosleep(wg ? KV_SLEEP : KV_SLEEP_A);
#pragma unroll
        for (int i = 0; i < 3; i++) kv[i] = ld_relaxed4(kvacc + i * 128);
        have = stage_kv();
      }
      PROF_C(wt == 0, 5 + wg * 8);
      fence_async_smem();
      nb_sync(nb_self, 128);
      float o[2][2][20];
      const uint64_t dq = mkdesc(sb + OFF_PK, 16, 1024, 1), dz = mkdesc(sb + OFF_KVB, 128, KVB_N, 0);
      wg_fence();
#pragma unroll
      for (int m = 0; m < 2; m++) {
#pragma unroll
        for (int h = 0; h < 2; h++)
#pragma unroll
          for (int kk = 0; kk < 2; kk++) mma_qkvz(o[m][h], dq + (m * 512 + h * 4 + kk * 2), dz + (h * 32 + kk * 16), kk);
        wg_commit();
      }
      if (wg && elect()) red_add(gs->cnt[16 + tm], 1u << tn * 4);
      uint32_t tag[2][4];
#pragma unroll
      for (int i = 0; i < 8; i++) tag[i >> 2][i & 3] = (lane >> 3) == (i & 3) && ((lane ^ (lane >> 3)) & 1) == (i >> 2);
      uint32_t gr[8];
      const uint8_t* ga = smem + OFF_G + (w * 16 + (lane >> 2)) * 4;
      asm volatile("" : "+l"(ga));
#pragma unroll
      for (int i = 0; i < OA; i++) gr[i] = ld_generic(ga + (i >> 2) * 256 + (i & 1) * 32);
      const uint32_t oo = w * 1024 + (lane >> 2) * 64 + (((lane ^ (lane >> 3)) & 3) << 4);
      uint8_t* const og = (uint8_t*)gs->o[tm][wg * 8 + tn] + oo;
      uint32_t ob[8][4];
#pragma unroll
      for (int m = 0; m < 2; m++) {
        if (m == 0) wg_wait<1>(); else wg_wait<0>();
        pin(o[m][0]); pin(o[m][1]);
        if (m && wg) mbar_arrive_warp(sb + BAR_PUB + 8);
        if (m && !wg) nb_arrive(NB_STG, 256);
        if (m && wg) nb_arrive(NB_HOLD, 256);
        if (m && wg && paired && elect()) mbar_arrive_peer(peer_addr(sb + BAR_PA));
        if (m == 0) PROF_C(wt == 0, 6 + wg * 8);
#pragma unroll
        for (int u = 0; u < 4; u++) {
          const int h = u >> 1, i = u & 1;
          const float* on = o[m][h];
          const float sc = __uint_as_float(gr[m * 4 + u]) * rcp(on[16 + 2 * i] + 1e-6f);
          const uint32_t sc2 = pack2(sc, sc);
#pragma unroll
          for (int j = 0; j < 4; j++) {
            const uint32_t v = mul_bf2(pack2(on[4 * j + 2 * i], on[4 * j + 2 * i + 1]), sc2);
            asm("lop3.b32 %0, %1, %2, %3, 0xB8;" : "=r"(ob[m * 4 + u][j]) : "r"(v), "r"(tag[i][j]), "r"(par));
          }
          st_relaxed4(og + (h * 8192 + m * 4096 + i * 512), ob[m * 4 + u]);
          if (wg) sts128(sb + OFF_V + oo + (h * 8192 + m * 4096 + i * 512), ob[m * 4 + u][0], ob[m * 4 + u][1], ob[m * 4 + u][2], ob[m * 4 + u][3]);
          const int n = m * 4 + u + OA;
          if (n < 8) gr[n] = ld_generic(ga + (n >> 2) * 256 + (n & 1) * 32);
        }
      }
      if (!wg) {
        if (elect()) red_add(gs->cnt[tm], 1u << tn * 4);
        mbar_arrive_warp(sb + BAR_PUB);
      }
      PROF(wt == 0, 17 + wg);
      if (wg) {
        fence_async_smem();
        __syncwarp();
        mbar_arrive_warp(sb + BAR_OWN);
        PROF(wt == 0, 15);
        if (paired) {
          const uint32_t pb = peer_addr(sb);
          mbar_wait(sb + BAR_PA, 0);
#pragma unroll
          for (int u = 0, z = 0; u < 8; u++) {
            if (u) z = lds32(sb + OFF_ONES) & zero;
            st_async4(pb + OFF_PK + oo + ((u >> 1 & 1) * 8192 + (u >> 2) * 4096 + (u & 1) * 512) + z, ob[u], pb + BAR_PEER);
          }
        }
      }
    }
    if (wg == 0) {
      float acc[2][64];
      nb_sync(NB_ORDER_BO, 256);
      PROF_C(wt == 0, 26);
      uint32_t xr[2][8][4], q[2][2];
      const uint32_t ta = sb + (uint32_t)(w * 16 + (lane & 15)) * 128;
      const uint64_t do0 = mkdesc(sb + OFF_RING, 16, 512, 2);
      uint64_t xs = OA_SLOTS, ws = OW_SLOTS;
#pragma unroll 1
      for (int g = 0; g < 13 - TL; g++, xs >>= 4, ws >>= 4) {
        const uint32_t r = g * 52 >> 8, s = g - r * 5;
        const uint64_t da = do0 + ((uint32_t)xs & 15) * (SLOT >> 4), db = db0 + ((uint32_t)ws & 15) * (SLOT >> 4);
        if (g == OWN) mbar_wait(sb + BAR_OWN, 0);
        if (g == PEER) { PROF(wt == 0, 39); mbar_wait(sb + BAR_PEER, 0); PROF(wt == 0, 40); fence_async_smem(); }
        if (g == HOLD) nb_sync(NB_HOLD, 256);
        mbar_wait(sb + BAR_OFULL + s * 8, r & 1);
        wg_fence();
#pragma unroll
        for (int kk = 0; kk < 4; kk++)
#pragma unroll
          for (int m = 0; m < 2; m++) mma128<0, 1>(acc[m], da + (m * 256 + (kk >> 1) * 512 + (kk & 1) * 2), db + kk * 128, kk ? 1 : g);
        wg_commit();
        wg_wait<1>();
        if (g) mbar_arrive_warp(sb + BAR_OEMPTY + (s ? s - 1 : 4) * 8);
      }
      PROF(wt == 0, 29);
      mbar_wait(sb + BAR_X, 0);
      PROF(wt == 0, 30);
      const int selw = ((0xFFFF - (int)(lds32(sb + OFF_MISC + 16) & 0xFFFF)) >> 4) - tm * 8 - w;
#pragma unroll
      for (int u = 0; u < 4; u++) {
        const int m = u >> 1, g = 13 - TL + u;
        const float g1 = 1.f - __uint_as_float(lds32(sb + OFF_G + (m * 64 + w * 16 + (u & 1) * 8 + (lane >> 2)) * 4));
        q[m][u & 1] = pack2(g1, g1);
#pragma unroll
        for (int j = 0; j < 4; j++) ldsm4(ta + res_off(u & 1, m) + ((((lane >> 4) + 2 * j) ^ (lane & 7)) << 4), xr[m][(u & 1) * 4 + j]);
        if (u == 3) break;
        mbar_wait(sb + BAR_OFULL + g % 5 * 8, g / 5 & 1);
        wg_fence();
#pragma unroll
        for (int kk = 0; kk < 4; kk++)
#pragma unroll
          for (int mm = 0; mm < 2; mm++)
            mma128<0, 1>(acc[mm], do0 + ((OA_SLOTS >> g * 4 & 15) * (SLOT >> 4) + mm * 256 + (kk >> 1) * 512 + (kk & 1) * 2), db0 + ((OW_SLOTS >> g * 4 & 15) * (SLOT >> 4) + kk * 128), 1);
        wg_commit();
        wg_wait<1>();
        if (g <= 11) mbar_arrive_warp(sb + BAR_OEMPTY + (g + 4) % 5 * 8);
      }
#pragma unroll
      for (int m = 0; m < 2; m++) {
#pragma unroll
        for (int g = 16 - TL; g < 16; g++) {
          if (m == 0) { mbar_wait(sb + BAR_OFULL + g % 5 * 8, g / 5 & 1); wg_fence(); }
#pragma unroll
          for (int kk = 0; kk < 4; kk++)
            mma128<0, 1>(acc[m], do0 + ((OA_SLOTS >> g * 4 & 15) * (SLOT >> 4) + m * 256 + (kk >> 1) * 512 + (kk & 1) * 2), db0 + ((OW_SLOTS >> g * 4 & 15) * (SLOT >> 4) + kk * 128), 1);
        }
        wg_commit();
      }
      mbar_arrive_warp(sb + BAR_DONE);
      const uint32_t tb = sb + w * 2048 + (lane >> 3) * 128 + (((lane ^ (lane >> 3)) & 7) << 4), tx = lane & 4 ? 64 : -64;
      uint8_t* const og = (uint8_t*)pout + (size_t)(tm * 128 + w * 16 + (lane >> 3)) * 2048 + tn * 256 + (lane & 7) * 16;
#pragma unroll
      for (int m = 0; m < 2; m++) {
        if (selw == 4 * m) {
          mbar_wait(sb + BAR_Y, 0);
#pragma unroll
          for (int j = 0; j < 8; j++) ldsm4(ta + res_off(j >> 2, m) + ((((lane >> 4) + 2 * (j & 3)) ^ (lane & 7)) << 4), xr[m][j]);
        }
        if (m == 0) wg_wait<1>(); else wg_wait<0>();
        if (m) PROF(wt == 0, 31);
#pragma unroll
        for (int h = 0; h < 2; h++) {
#pragma unroll
          for (int j = 4 * h; j < 4 * h + 4; j++) {
            const float* v = &acc[m][8 * j];
            stsm4(ta + res_off(h, m) + ((((lane >> 4) + 2 * (j & 3)) ^ (lane & 7)) << 4),
                  fma_bf2(xr[m][j][0], q[m][0], pack2(v[0], v[1])), fma_bf2(xr[m][j][1], q[m][1], pack2(v[2], v[3])),
                  fma_bf2(xr[m][j][2], q[m][0], pack2(v[4], v[5])), fma_bf2(xr[m][j][3], q[m][1], pack2(v[6], v[7])));
          }
          if (m) {
            __syncwarp();
            uint4 t[4];
#pragma unroll
            for (int j = 0; j < 4; j++) t[j] = lds128(tb + res_off(h, m) + j * 512 - (j & 1) * tx);
#pragma unroll
            for (int j = 0; j < 4; j++) *(uint4*)(og + (m * 64 + j * 4) * 2048 + h * 128) = t[j];
          } else {
            fence_async_smem();
            __syncwarp();
            if (elect()) tma2d_store(&p.out, sb + res_off(h, m) + w * 2048, tn * 128 + h * 64, tm * 128 + m * 64 + w * 16);
          }
          if (m && h && elect()) { bulk_commit(); asm volatile("cp.async.bulk.wait_group.read 0;" ::: "memory"); }
        }
        if (!m) PROF(wt == 0, 33);
      }
      PROF(wt == 0, 32);
    }
  }
}

typedef CUresult (*EncodeFn)(CUtensorMap*, CUtensorMapDataType, cuuint32_t, void*, const cuuint64_t*, const cuuint64_t*, const cuuint32_t*,
                             const cuuint32_t*, CUtensorMapInterleave, CUtensorMapSwizzle, CUtensorMapL2promotion, CUtensorMapFloatOOBfill);

void encode(EncodeFn fn, CUtensorMap* m, const void* ptr, int rank, const cuuint64_t* dims, const cuuint64_t* strides, const cuuint32_t* box,
            CUtensorMapSwizzle sw, CUtensorMapDataType dt = CU_TENSOR_MAP_DATA_TYPE_BFLOAT16) {
  const cuuint32_t es[3] = {1, 1, 1};
  fn(m, dt, rank, const_cast<void*>(ptr), dims, strides, box, es, CU_TENSOR_MAP_INTERLEAVE_NONE, sw,
     CU_TENSOR_MAP_L2_PROMOTION_L2_128B, CU_TENSOR_MAP_FLOAT_OOB_FILL_NONE);
}

}

extern "C" void kernel_launch(void* const* d_in, const int* in_sizes, int n_in, void* d_out, int out_size) {
  (void)in_sizes; (void)n_in; (void)out_size;
  EncodeFn fn = nullptr;
  cudaDriverEntryPointQueryResult qr;
  cudaGetDriverEntryPoint("cuTensorMapEncodeTiled", (void**)&fn, cudaEnableDefault, &qr);

  Params p;
  {
    const cuuint64_t dims[2] = {D_, S_}, str[1] = {D_ * 2};
    const cuuint32_t box[2] = {64, 128}, box_st[2] = {64, 16}, box_r[2] = {256, 16}, box_h[2] = {64, 64};
    encode(fn, &p.xh, d_in[0], 2, dims, str, box_h, CU_TENSOR_MAP_SWIZZLE_128B);
    encode(fn, &p.xr, d_in[0], 2, dims, str, box_r, CU_TENSOR_MAP_SWIZZLE_NONE);
    encode(fn, &p.x, d_in[0], 2, dims, str, box, CU_TENSOR_MAP_SWIZZLE_128B);
    encode(fn, &p.out, d_out, 2, dims, str, box_st, CU_TENSOR_MAP_SWIZZLE_128B);
  }
  {
    const cuuint64_t dims[3] = {D_, D_, 3}, str[2] = {3 * D_ * 2, D_ * 2};
    const cuuint32_t box[3] = {64, 64, 3};
    encode(fn, &p.w, d_in[1], 3, dims, str, box, CU_TENSOR_MAP_SWIZZLE_128B);
  }
  {
    const cuuint64_t dims[3] = {64, D_, D_ / 64}, str[2] = {D_ * 2, 128};
    const cuuint32_t box[3] = {64, 64, 2};
    encode(fn, &p.wo, d_in[2], 3, dims, str, box, CU_TENSOR_MAP_SWIZZLE_128B);
  }
  {
    const cuuint64_t dims[3] = {F_, D_ / 4, 4}, str[2] = {F_ * 8, F_ * 2};
    const cuuint32_t box[3] = {32, 16, 4};
    encode(fn, &p.gate, d_in[5], 3, dims, str, box, CU_TENSOR_MAP_SWIZZLE_NONE);
    encode(fn, &p.up, d_in[6], 3, dims, str, box, CU_TENSOR_MAP_SWIZZLE_NONE);
  }
  {
    const cuuint64_t dims[3] = {D_ / 4, F_, 2}, str[2] = {D_ * 2, D_};
    const cuuint32_t box[3] = {256, 4, 2};
    encode(fn, &p.down, d_in[7], 3, dims, str, box, CU_TENSOR_MAP_SWIZZLE_NONE, CU_TENSOR_MAP_DATA_TYPE_UINT32);
  }
  void* gs = nullptr;
  cudaGetSymbolAddress(&gs, g_scratch);
  typedef const __nv_bfloat16* bp;
  int dev = 0, sms = 0;
  cudaGetDevice(&dev);
  cudaDeviceGetAttribute(&sms, cudaDevAttrMultiProcessorCount, dev);
  const bool by_sm = BYSM && sms == NGRID;
  const auto kernel = by_sm ? fused_kernel<true> : fused_kernel<false>;
  cudaFuncSetAttribute(kernel, cudaFuncAttributeMaxDynamicSharedMemorySize, SMEM_BYTES);
  kernel<<<by_sm ? NGRID : NCTA, NTHREADS, SMEM_BYTES, cudaStreamPerThread>>>((bp)d_in[0], (Scratch*)gs, (bp)d_in[5], (bp)d_in[6], (bp)d_in[4], (bp)d_in[8], (__nv_bfloat16*)d_out, p);
}
```

```cpp
#include <cuda_runtime.h>
#include <cuda.h>
#include <cuda_bf16.h>
#include <stdint.h>
#include <stddef.h>

namespace {

constexpr int S_ = 2048, D_ = 1024, F_ = 3584;
constexpr int NCTA = 128, NGRID = 132, NTHREADS = 512;
#define NOMOD 0
constexpr int MOD_CTAS = NOMOD ? 0 : F_ / 32;

#define PRE 2
#define ST1 800
#define RT_G0 2
#define RT_ROT 1
#define RT_SLEEP 500
#define PF_MOD 8
#define MOD_START 10
#define MM 3
#define HOLD 5
#define KF 6
#define QA 3
#define R0 1
#define OA 3
#define Y_SLEEP 200
#define VK 1
#define EC 2
#define KL 3
#define RS 2
#define RETRY 1
#define KV_SLEEP_A 64
#define KV_SLEEP 50
#define TL 3
#define B_SLEEP 32
#define PAIRED 1
#define BYSM 1

constexpr uint32_t SLOT = 16384, WQKV_BYTES = 24576;
constexpr int MOD_BUFS = 3, MOD_BUFS0 = MOD_BUFS + 2;
static_assert(MOD_START + MOD_BUFS0 <= 16, "first FFN round is requested during W1");
constexpr uint32_t OFF_RING = 0, OFF_W1 = 4 * SLOT;
constexpr uint64_t OA_SLOTS = 0x0AB210AB21098210ull, OW_SLOTS = 0x4376543765437654ull;
constexpr uint32_t OFF_RES = OFF_RING + 8 * SLOT;
constexpr uint32_t OFF_PK = 10 * SLOT;
constexpr uint32_t OFF_V = 11 * SLOT;
constexpr uint32_t OFF_ONES = OFF_V + 9216 + 8192;
constexpr uint32_t MOD_STEP = 9216, OFF_MOD = OFF_V + 2 * MOD_STEP;
constexpr __host__ __device__ uint32_t res_off(int h, int m) { return h & m ? OFF_RES : OFF_MOD + (h * 2 + m) * MOD_STEP; }
constexpr uint32_t OFF_XSEL = OFF_MOD + 8192;
constexpr uint32_t OFF_KVB = OFF_MOD + 2 * MOD_STEP + 8192;
constexpr uint32_t KVB_N = 1056;
constexpr uint32_t OFF_G = OFF_KVB + 4 * KVB_N + 1024;
constexpr uint32_t OFF_PART = OFF_G + 512;
constexpr uint32_t OFF_MISC = OFF_PART + 576;
constexpr uint32_t OFF_BAR = OFF_MISC + 32;
constexpr uint32_t SMEM_BYTES = OFF_BAR + 488;
constexpr uint32_t BAR_FULL = OFF_BAR, BAR_Y = BAR_FULL + 64, BAR_X = BAR_Y + 8, BAR_PEER = BAR_X + 8, BAR_GATE = BAR_PEER + 8, BAR_RT = BAR_GATE + 8,
                   BAR_FIX = BAR_RT,
                   BAR_MFULL = BAR_FIX + 32, BAR_LAND = BAR_FULL,
                   BAR_EMPTY = OFF_BAR + 28 * 8, BAR_OEMPTY = BAR_EMPTY + 64, BAR_RTD = BAR_OEMPTY + 40, BAR_DONE = BAR_RTD + 8,
                   BAR_OWN = BAR_DONE + 8, BAR_PA = BAR_OWN + 8, BAR_PUB = BAR_PA + 8, BAR_MEMPTY = BAR_PUB + 16,
                   BAR_IDX = BAR_MEMPTY + 8,
                   BAR_OFULL = OFF_BAR + 52 * 8;
static_assert(BAR_MFULL + MOD_BUFS0 * 8 <= BAR_EMPTY && BAR_MEMPTY + MOD_BUFS0 * 8 == BAR_OFULL, "barrier groups");
static_assert(SMEM_BYTES <= 232448, "smem");
static_assert(TL == 3 && PRE == 2, "schedule");

constexpr int NB_WG0 = 1, NB_ORDER_AB = 3, NB_ORDER_BO = 4, NB_STG = 5, NB_MODW = 6, NB_KEY = 7, NB_HOLD = 8;

struct Scratch {
  uint4 kv[2][8][3][128];
  float4 y[2][3][128];
  unsigned cnt[32][32];
  unsigned gslot[S_];
  unsigned rslot[8][NCTA];
  unsigned spare[128];
  unsigned block[NCTA];
  uint4 o[16][16][1024];
};
static_assert(offsetof(Scratch, gslot) == NCTA * 56 * 16, "clear size");
__device__ __align__(1024) Scratch g_scratch;

#define PROF(cond, i) do {} while (0)
#define PROF_C(cond, i) do {} while (0)

__device__ __forceinline__ void mbar_init(uint32_t bar, int cnt) { asm volatile("mbarrier.init.shared::cta.b64 [%0], %1;" ::"r"(bar), "r"(cnt)); }
__device__ __forceinline__ void mbar_expect_tx(uint32_t bar, uint32_t bytes) { asm volatile("mbarrier.arrive.expect_tx.shared::cta.b64 _, [%0], %1;" ::"r"(bar), "r"(bytes) : "memory"); }
__device__ __forceinline__ void mbar_arrive(uint32_t bar) { asm volatile("mbarrier.arrive.shared::cta.b64 _, [%0];" ::"r"(bar) : "memory"); }
__device__ __forceinline__ uint32_t peer_addr(uint32_t a) {
  uint32_t r;
  asm volatile("{\n.reg .u32 c;\nmov.u32 c, %%cluster_ctarank;\nxor.b32 c, c, 1;\nmapa.shared::cluster.u32 %0, %1, c;\n}" : "=r"(r) : "r"(a));
  return r;
}
__device__ __forceinline__ void mbar_arrive_peer(uint32_t bar) { asm volatile("mbarrier.arrive.shared::cluster.b64 _, [%0];" ::"r"(bar) : "memory"); }
__device__ __forceinline__ uint32_t mism(uint32_t a, uint32_t b, uint32_t p) {
  uint32_t r; asm("lop3.b32 %0, %1, %2, %3, 0x7E;" : "=r"(r) : "r"(a), "r"(b), "r"(p)); return r;
}
__device__ __forceinline__ bool elect() {
  uint32_t r;
  asm volatile("{\n.reg .pred p;\nelect.sync _|p, 0xffffffff;\nselp.u32 %0, 1, 0, p;\n}" : "=r"(r));
  return r;
}
__device__ __forceinline__ uint32_t fresh_tid() { uint32_t r; asm volatile("mov.u32 %0, %%tid.x;" : "=r"(r)); return r; }
__device__ __forceinline__ void mbar_arrive_warp(uint32_t bar) {
  asm volatile("{\n.reg .pred p;\nelect.sync _|p, 0xffffffff;\n@p mbarrier.arrive.shared::cta.b64 _, [%0];\n}" ::"r"(bar) : "memory");
}
__device__ __forceinline__ void mbar_wait(uint32_t bar, uint32_t parity) {
  asm volatile("{\n.reg .pred p;\nWAIT_L:\nmbarrier.try_wait.parity.shared::cta.b64 p, [%0], %1;\n@p bra DONE_L;\nbra WAIT_L;\nDONE_L:\n}"
               ::"r"(bar), "r"(parity) : "memory");
}
__device__ __forceinline__ uint32_t mbar_try(uint32_t bar, uint32_t parity) {
  uint32_t ok;
  asm volatile("{\n.reg .pred p;\nmbarrier.try_wait.parity.shared::cta.b64 p, [%1], %2;\nselp.u32 %0, 1, 0, p;\n}" : "=r"(ok) : "r"(bar), "r"(parity) : "memory");
  return ok;
}
__device__ __forceinline__ uint32_t mbar_test(uint32_t bar, uint32_t parity) {
  uint32_t ok;
  asm volatile("{\n.reg .pred p;\nmbarrier.test_wait.parity.shared::cta.b64 p, [%1], %2;\nselp.u32 %0, 1, 0, p;\n}" : "=r"(ok) : "r"(bar), "r"(parity) : "memory");
  return ok;
}
constexpr unsigned long long WATCHDOG_NS = 2000000000ull;
__device__ __forceinline__ unsigned long long gtime() { unsigned long long t; asm volatile("mov.u64 %0, %%globaltimer;" : "=l"(t)); return t; }
__device__ __forceinline__ uint32_t clock32() { uint32_t t; asm volatile("mov.u32 %0, %%clock;" : "=r"(t)); return t; }
__device__ __forceinline__ void mbar_wait_bounded(uint32_t bar, uint32_t parity) {
  unsigned long long t0 = 0;
  for (;;) {
    uint32_t ok;
    asm volatile("{\n.reg .pred p;\nmbarrier.try_wait.parity.shared::cta.b64 p, [%1], %2;\nselp.u32 %0, 1, 0, p;\n}" : "=r"(ok) : "r"(bar), "r"(parity) : "memory");
    if (ok) break;
    const unsigned long long t1 = gtime();
    if (t0 == 0) t0 = t1;
    if (t1 - t0 > WATCHDOG_NS) __trap();
  }
}
__device__ __forceinline__ void tma2d(uint32_t dst, const CUtensorMap* m, int c0, int c1, uint32_t bar) {
  asm volatile("cp.async.bulk.tensor.2d.shared::cluster.global.mbarrier::complete_tx::bytes [%0], [%1, {%3, %4}], [%2];"
               ::"r"(dst), "l"(m), "r"(bar), "r"(c0), "r"(c1) : "memory");
}
__device__ __forceinline__ void tma3d(uint32_t dst, const CUtensorMap* m, int c0, int c1, int c2, uint32_t bar) {
  asm volatile("cp.async.bulk.tensor.3d.shared::cluster.global.mbarrier::complete_tx::bytes [%0], [%1, {%3, %4, %5}], [%2];"
               ::"r"(dst), "l"(m), "r"(bar), "r"(c0), "r"(c1), "r"(c2) : "memory");
}
__device__ __forceinline__ void bulk_load(uint32_t dst, const void* src, uint32_t bytes, uint32_t bar) {
  asm volatile("cp.async.bulk.shared::cluster.global.mbarrier::complete_tx::bytes [%0], [%1], %2, [%3];" ::"r"(dst), "l"(src), "r"(bytes), "r"(bar) : "memory");
}
__device__ __forceinline__ void bulk_store(void* dst, uint32_t src, uint32_t bytes) {
  asm volatile("cp.async.bulk.global.shared::cta.bulk_group [%0], [%1], %2;" ::"l"(dst), "r"(src), "r"(bytes) : "memory");
}
__device__ __forceinline__ void st_async4(uint32_t dst, const uint32_t (&v)[4], uint32_t bar) {
  asm volatile("st.async.shared::cluster.mbarrier::complete_tx::bytes.v4.b32 [%0], {%1, %2, %3, %4}, [%5];" ::"r"(dst), "r"(v[0]), "r"(v[1]), "r"(v[2]), "r"(v[3]), "r"(bar) : "memory");
}
__device__ __forceinline__ void bulk_commit() { asm volatile("cp.async.bulk.commit_group;" ::: "memory"); }
__device__ __forceinline__ void bulk_prefetch(const void* p, uint32_t bytes) {
  asm volatile("cp.async.bulk.prefetch.L2.global [%0], %1;" ::"l"(p), "r"(bytes) : "memory");
}
__device__ __forceinline__ void tma2d_store(const CUtensorMap* m, uint32_t src, int c0, int c1) {
  asm volatile("cp.async.bulk.tensor.2d.global.shared::cta.bulk_group [%0, {%2, %3}], [%1];" ::"l"(m), "r"(src), "r"(c0), "r"(c1) : "memory");
}
__device__ __forceinline__ void wg_fence() { asm volatile("wgmma.fence.sync.aligned;" ::: "memory"); }
__device__ __forceinline__ void wg_commit() { asm volatile("wgmma.commit_group.sync.aligned;" ::: "memory"); }
template <int N> __device__ __forceinline__ void wg_wait() { asm volatile("wgmma.wait_group.sync.aligned %0;" ::"n"(N) : "memory"); }
__device__ __forceinline__ void fence_async_smem() { asm volatile("fence.proxy.async.shared::cta;" ::: "memory"); }
__device__ __forceinline__ void fence_async_global() { asm volatile("fence.proxy.async.global;" ::: "memory"); }
__device__ __forceinline__ void fence_release() { asm volatile("fence.release.gpu;" ::: "memory"); }
__device__ __forceinline__ void fence_acquire() { asm volatile("fence.acquire.gpu;" ::: "memory"); }
__device__ __forceinline__ void nb_sync(int id, int n) { asm volatile("bar.sync %0, %1;" ::"r"(id), "r"(n) : "memory"); }
__device__ __forceinline__ void nb_arrive(int id, int n) { asm volatile("bar.arrive %0, %1;" ::"r"(id), "r"(n) : "memory"); }
__device__ __forceinline__ void stsm4(uint32_t addr, uint32_t r0, uint32_t r1, uint32_t r2, uint32_t r3) {
  asm volatile("stmatrix.sync.aligned.m8n8.x4.shared.b16 [%0], {%1, %2, %3, %4};" ::"r"(addr), "r"(r0), "r"(r1), "r"(r2), "r"(r3) : "memory");
}
__device__ __forceinline__ void stsm4t(uint32_t addr, uint32_t r0, uint32_t r1, uint32_t r2, uint32_t r3) {
  asm volatile("stmatrix.sync.aligned.m8n8.x4.trans.shared.b16 [%0], {%1, %2, %3, %4};" ::"r"(addr), "r"(r0), "r"(r1), "r"(r2), "r"(r3) : "memory");
}
__device__ __forceinline__ void st_relaxed4(void* p, const uint32_t (&v)[4]) {
  asm volatile("st.relaxed.gpu.global.v4.u32 [%0], {%1, %2, %3, %4};" ::"l"(p), "r"(v[0]), "r"(v[1]), "r"(v[2]), "r"(v[3]) : "memory");
}
__device__ __forceinline__ void sts128(uint32_t addr, uint32_t a, uint32_t b, uint32_t c, uint32_t d) {
  asm volatile("st.shared.v4.b32 [%0], {%1, %2, %3, %4};" ::"r"(addr), "r"(a), "r"(b), "r"(c), "r"(d) : "memory");
}
__device__ __forceinline__ uint32_t pack2(float lo, float hi) {
  uint32_t r; asm("cvt.rn.bf16x2.f32 %0, %1, %2;" : "=r"(r) : "f"(hi), "f"(lo)); return r;
}
__device__ __forceinline__ float bf_lo(uint32_t v) { return __uint_as_float(v << 16); }
__device__ __forceinline__ float bf_hi(uint32_t v) { return __uint_as_float(v & 0xffff0000u); }
__device__ __forceinline__ float bf_round(float v) { return __bfloat162float(__float2bfloat16_rn(v)); }
__device__ __forceinline__ void ldsm4(uint32_t addr, uint32_t (&r)[4]) {
  asm volatile("ldmatrix.sync.aligned.m8n8.x4.shared.b16 {%0, %1, %2, %3}, [%4];" : "=r"(r[0]), "=r"(r[1]), "=r"(r[2]), "=r"(r[3]) : "r"(addr) : "memory");
}
__device__ __forceinline__ uint4 lds128(uint32_t addr) {
  uint4 v; asm volatile("ld.volatile.shared.v4.u32 {%0, %1, %2, %3}, [%4];" : "=r"(v.x), "=r"(v.y), "=r"(v.z), "=r"(v.w) : "r"(addr) : "memory"); return v;
}
__device__ __forceinline__ uint2 lds64(uint32_t addr) { uint2 v; asm volatile("ld.volatile.shared.v2.u32 {%0, %1}, [%2];" : "=r"(v.x), "=r"(v.y) : "r"(addr) : "memory"); return v; }
__device__ __forceinline__ uint32_t lds32(uint32_t addr) { uint32_t v; asm volatile("ld.volatile.shared.u32 %0, [%1];" : "=r"(v) : "r"(addr) : "memory"); return v; }
__device__ __forceinline__ uint32_t ld_generic(const void* p) { uint32_t v; asm volatile("ld.volatile.u32 %0, [%1];" : "=r"(v) : "l"(p) : "memory"); return v; }
__device__ __forceinline__ void sts32(uint32_t addr, uint32_t v) { asm volatile("st.shared.u32 [%0], %1;" ::"r"(addr), "r"(v) : "memory"); }
__device__ __forceinline__ uint32_t fma_bf2(uint32_t a, uint32_t b, uint32_t c) { uint32_t r; asm("fma.rn.bf16x2 %0, %1, %2, %3;" : "=r"(r) : "r"(a), "r"(b), "r"(c)); return r; }
__device__ __forceinline__ uint32_t mul_bf2(uint32_t a, uint32_t b) { uint32_t r; asm("mul.rn.bf16x2 %0, %1, %2;" : "=r"(r) : "r"(a), "r"(b)); return r; }
__device__ __forceinline__ unsigned ld_relaxed(const unsigned* p) { unsigned v; asm volatile("ld.relaxed.gpu.global.u32 %0, [%1];" : "=r"(v) : "l"(p) : "memory"); return v; }
__device__ __forceinline__ void st_relaxed(unsigned* p, unsigned v) { asm volatile("st.relaxed.gpu.global.u32 [%0], %1;" ::"l"(p), "r"(v) : "memory"); }
__device__ __forceinline__ uint4 ld_relaxed4(const void* p) {
  uint4 v; asm volatile("ld.relaxed.gpu.global.v4.u32 {%0, %1, %2, %3}, [%4];" : "=r"(v.x), "=r"(v.y), "=r"(v.z), "=r"(v.w) : "l"(p) : "memory"); return v;
}
__device__ __forceinline__ float4 ld_relaxed_f4(const void* p) {
  float4 v; asm volatile("ld.relaxed.gpu.global.v4.f32 {%0, %1, %2, %3}, [%4];" : "=f"(v.x), "=f"(v.y), "=f"(v.z), "=f"(v.w) : "l"(p) : "memory"); return v;
}
__device__ __forceinline__ void red_add4(void* p, float a, float b, float c, float d) {
  asm volatile("red.relaxed.gpu.global.add.v4.f32 [%0], {%1, %2, %3, %4};" ::"l"(p), "f"(a), "f"(b), "f"(c), "f"(d) : "memory");
}
__device__ __forceinline__ void red_add_bf(void* p, uint32_t a, uint32_t b, uint32_t c) {
  asm volatile("red.relaxed.gpu.global.add.noftz.v4.bf16x2 [%0], {%1, %2, %3, %4};" ::"l"(p), "r"(a), "r"(b), "r"(c), "r"(0x3F803F80u) : "memory");
}
__device__ __forceinline__ void red_add(unsigned* p, unsigned v) { asm volatile("red.relaxed.gpu.global.add.u32 [%0], %1;" ::"l"(p), "r"(v) : "memory"); }
__device__ __forceinline__ float rcp(float v) { float r; asm("rcp.approx.ftz.f32 %0, %1;" : "=f"(r) : "f"(v)); return r; }
__device__ __forceinline__ float sigmoidf_(float v) { return rcp(1.f + __expf(-v)); }
__device__ __forceinline__ uint32_t phi2(float a, float b, float l2e = 1.4426950408889634f) {
  float ea, eb;
  asm("ex2.approx.ftz.f32 %0, %1;" : "=f"(ea) : "f"(a * l2e));
  asm("ex2.approx.ftz.f32 %0, %1;" : "=f"(eb) : "f"(b * l2e));
  uint32_t t = pack2(a, b), e = pack2(ea, eb), r;
  asm("max.NaN.bf16x2 %0, %0, %1;" : "+r"(t) : "r"(0x35863586u));
  asm("min.bf16x2 %0, %0, %1;" : "+r"(e) : "r"(0x3F803F80u));
  asm("add.rn.bf16x2 %0, %1, %2;" : "=r"(r) : "r"(t), "r"(e));
  return r;
}
__device__ __forceinline__ uint64_t mkdesc(uint32_t addr, uint32_t lbo, uint32_t sbo, uint32_t sw) {
  return (uint64_t)(((addr & 0x3FFFF) >> 4) | ((lbo >> 4) << 16)) | ((uint64_t)((sbo >> 4) | (sw << 30)) << 32);
}

template <int TA, int TB>
__device__ __forceinline__ void mma128(float (&d)[64], uint64_t da, uint64_t db, int sc) {
  asm volatile("{\n.reg .pred p;\nsetp.ne.b32 p, %66, 0;\n"
    "wgmma.mma_async.sync.aligned.m64n128k16.f32.bf16.bf16 "
    "{%0,%1,%2,%3,%4,%5,%6,%7,%8,%9,%10,%11,%12,%13,%14,%15,%16,%17,%18,%19,%20,%21,%22,%23,"
    "%24,%25,%26,%27,%28,%29,%30,%31,%32,%33,%34,%35,%36,%37,%38,%39,%40,%41,%42,%43,%44,%45,%46,%47,"
    "%48,%49,%50,%51,%52,%53,%54,%55,%56,%57,%58,%59,%60,%61,%62,%63}, "
    "%64, %65, p, 1, 1, %67, %68;\n}\n"
    : "+f"(d[0]), "+f"(d[1]), "+f"(d[2]), "+f"(d[3]), "+f"(d[4]), "+f"(d[5]), "+f"(d[6]), "+f"(d[7]),
      "+f"(d[8]), "+f"(d[9]), "+f"(d[10]), "+f"(d[11]), "+f"(d[12]), "+f"(d[13]), "+f"(d[14]), "+f"(d[15]),
      "+f"(d[16]), "+f"(d[17]), "+f"(d[18]), "+f"(d[19]), "+f"(d[20]), "+f"(d[21]), "+f"(d[22]), "+f"(d[23]),
      "+f"(d[24]), "+f"(d[25]), "+f"(d[26]), "+f"(d[27]), "+f"(d[28]), "+f"(d[29]), "+f"(d[30]), "+f"(d[31]),
      "+f"(d[32]), "+f"(d[33]), "+f"(d[34]), "+f"(d[35]), "+f"(d[36]), "+f"(d[37]), "+f"(d[38]), "+f"(d[39]),
      "+f"(d[40]), "+f"(d[41]), "+f"(d[42]), "+f"(d[43]), "+f"(d[44]), "+f"(d[45]), "+f"(d[46]), "+f"(d[47]),
      "+f"(d[48]), "+f"(d[49]), "+f"(d[50]), "+f"(d[51]), "+f"(d[52]), "+f"(d[53]), "+f"(d[54]), "+f"(d[55]),
      "+f"(d[56]), "+f"(d[57]), "+f"(d[58]), "+f"(d[59]), "+f"(d[60]), "+f"(d[61]), "+f"(d[62]), "+f"(d[63])
    : "l"(da), "l"(db), "r"(sc), "n"(TA), "n"(TB));
}

__device__ __forceinline__ void mma_ktv(float (&d)[36], const uint32_t (&a)[4], uint64_t db, int sc) {
  asm volatile("{\n.reg .pred p;\nsetp.ne.b32 p, %41, 0;\n"
    "wgmma.mma_async.sync.aligned.m64n72k16.f32.bf16.bf16 "
    "{%0,%1,%2,%3,%4,%5,%6,%7,%8,%9,%10,%11,%12,%13,%14,%15,%16,%17,%18,%19,%20,%21,%22,%23,"
    "%24,%25,%26,%27,%28,%29,%30,%31,%32,%33,%34,%35}, "
    "{%36,%37,%38,%39}, %40, p, 1, 1, 0;\n}\n"
    : "+f"(d[0]), "+f"(d[1]), "+f"(d[2]), "+f"(d[3]), "+f"(d[4]), "+f"(d[5]), "+f"(d[6]), "+f"(d[7]),
      "+f"(d[8]), "+f"(d[9]), "+f"(d[10]), "+f"(d[11]), "+f"(d[12]), "+f"(d[13]), "+f"(d[14]), "+f"(d[15]),
      "+f"(d[16]), "+f"(d[17]), "+f"(d[18]), "+f"(d[19]), "+f"(d[20]), "+f"(d[21]), "+f"(d[22]), "+f"(d[23]),
      "+f"(d[24]), "+f"(d[25]), "+f"(d[26]), "+f"(d[27]), "+f"(d[28]), "+f"(d[29]), "+f"(d[30]), "+f"(d[31]),
      "+f"(d[32]), "+f"(d[33]), "+f"(d[34]), "+f"(d[35])
    : "r"(a[0]), "r"(a[1]), "r"(a[2]), "r"(a[3]), "l"(db), "r"(sc));
}

__device__ __forceinline__ void mma_qkvz(float (&d)[20], uint64_t da, uint64_t db, int sc) {
  asm volatile("{\n.reg .pred p;\nsetp.ne.b32 p, %22, 0;\n"
    "wgmma.mma_async.sync.aligned.m64n40k16.f32.bf16.bf16 "
    "{%0,%1,%2,%3,%4,%5,%6,%7,%8,%9,%10,%11,%12,%13,%14,%15,%16,%17,%18,%19}, "
    "%20, %21, p, 1, 1, 0, 1;\n}\n"
    : "+f"(d[0]), "+f"(d[1]), "+f"(d[2]), "+f"(d[3]), "+f"(d[4]), "+f"(d[5]), "+f"(d[6]), "+f"(d[7]),
      "+f"(d[8]), "+f"(d[9]), "+f"(d[10]), "+f"(d[11]), "+f"(d[12]), "+f"(d[13]), "+f"(d[14]), "+f"(d[15]),
      "+f"(d[16]), "+f"(d[17]), "+f"(d[18]), "+f"(d[19])
    : "l"(da), "l"(db), "r"(sc));
}

template <int N> __device__ __forceinline__ void pin(float (&d)[N]) {
#pragma unroll
  for (int i = 0; i < N; i++) asm volatile("" : "+f"(d[i])::"memory");
}

struct Params {
  CUtensorMap x, w, xr, gate, up, wo, out, down, xh;
};

__device__ __forceinline__ uint32_t dup_lo(uint32_t v) { uint32_t r; asm("{\n.reg .b16 l, h;\nmov.b32 {l, h}, %1;\nmov.b32 %0, {l, l};\n}" : "=r"(r) : "r"(v)); return r; }
__device__ __forceinline__ uint32_t dup_hi(uint32_t v) { uint32_t r; asm("{\n.reg .b16 l, h;\nmov.b32 {l, h}, %1;\nmov.b32 %0, {h, h};\n}" : "=r"(r) : "r"(v)); return r; }
__device__ __forceinline__ float butterfly8(float (&s)[8], int lane, int o) {
#pragma unroll
  for (int k = 1; k < 8; k <<= 1) {
    const bool up = lane & (o * k);
#pragma unroll
    for (int j = 0; j < 4 / k; j++) s[j] = (up ? s[2 * j + 1] : s[2 * j]) + __shfl_xor_sync(~0u, up ? s[2 * j] : s[2 * j + 1], o * k);
  }
  return s[0];
}
constexpr int OWN = 8, PEER = 9;
static_assert((OA_SLOTS >> OWN * 4 & 15) * SLOT == OFF_V && (OA_SLOTS >> PEER * 4 & 15) * SLOT == OFF_PK, "");
constexpr uint64_t OR_SLOTS = (OA_SLOTS & 0xFFFFFFFFu) | OA_SLOTS >> 40 << 32;
template <class F> __device__ __forceinline__ void verify_tiles(uint32_t sb, Scratch* gs, int tm, int tn, int w, int lane, F between) {
  const uint32_t par = lds32(sb + OFF_MISC + 24), fix = sb + BAR_FIX + w * 8;
  uint64_t slots = OR_SLOTS, full = 0x04321021043210ull;
#pragma unroll 1
  for (int i = 0; i < 14; i++, slots >>= 4, full >>= 4) {
    const uint32_t a = sb + OFF_RING + ((uint32_t)slots & 15) * SLOT + w * 1024, cw = a + lane * 32 + (lane >> 2) * 4;
    if (i == 4) mbar_wait(sb + BAR_EMPTY + 7 * 8, 1);
    if (i == 8) between();
    mbar_wait(sb + BAR_LAND + (i & 7) * 8, i >> 3);
    if (i >> 1 == 4) PROF(w == 0 && lane == 0, 33 + i);
    for (;;) {
      const uint32_t u0 = lds32(cw), u1 = lds32(cw + 4096), u2 = lds32(cw + 8192), u3 = lds32(cw + 12288);
      if (__all_sync(~0u, !(mism(mism(u0, u1, par), mism(u2, u3, par), 0) & 1))) break;
      const uint4* src = gs->o[tm][i < 8 + (tn & 6) ? i : i + 2] + w * 64;
      const uint32_t ph = !mbar_test(fix, 1);
      fence_async_smem();
      __syncwarp();
      if (elect()) {
        mbar_expect_tx(fix, 4096);
#pragma unroll 1
        for (int j = 0; j < 4; j++) bulk_load(a + j * 4096, src + j * 256, 1024, fix);
      }
      mbar_wait(fix, ph);
    }
    mbar_arrive_warp(sb + BAR_OFULL + ((uint32_t)full & 7) * 8);
    if (i == 8) PROF(w == 3 && lane == 0, 28);
  }
}
template <bool BY_SM> struct Tile {
  int sm, tm, tn, mu;
  bool spare;
  __device__ __forceinline__ Tile() {
    if (BY_SM) asm volatile("mov.u32 %0, %%smid;" : "=r"(sm));
    else sm = blockIdx.x + (blockIdx.x >= 120) * 4;
    const int tp = sm >> 1, pr = sm & 1;
    const int v = tp < 32 ? tp : tp < 60 ? (tp * 293 - 928) >> 8 : tp * 8 - 464, g = v & 7, i = v >> 3;
    tm = (v & 6) * 2 + (i & 3); tn = (v & 1) * 4 + (v >> 4 & 2) + pr;
    mu = i == 5 ? 112 : g * 14 + (i - (i > 5)) * 2 + pr;
    spare = (tp | 1) == 61;
  }
};

template <bool BY_SM> __global__ void __cluster_dims__(2, 1, 1) __launch_bounds__(NTHREADS, 1) fused_kernel(const __nv_bfloat16* __restrict__ px, Scratch* gs, const __nv_bfloat16* __restrict__ w_gate,
             const __nv_bfloat16* __restrict__ w_up, const __nv_bfloat16* __restrict__ w_r, const __nv_bfloat16* __restrict__ gate_w, __nv_bfloat16* __restrict__ pout,
             const __grid_constant__ Params p) {
  extern __shared__ __align__(1024) uint8_t smem[];
  const uint32_t sb = __shfl_sync(~0u, (uint32_t)__cvta_generic_to_shared(smem), 0);
  const int tid = threadIdx.x, lane = tid & 31;
  const int warp = __shfl_sync(~0u, tid >> 5, 0), wg = warp >> 2;
  const uint32_t t_start = clock32();
  const Tile<BY_SM> tile;
  const int tm = tile.tm, tn = tile.tn, mu = tile.mu, cta = tm * 8 + tn;
  const uint32_t zero = tile.sm >> 12;
  if (warp == 0) {
#pragma unroll
    for (int s = 0; s < PRE; s++)
      if (elect()) mbar_init(sb + BAR_FULL + s * 8, 1);
    asm volatile("fence.mbarrier_init.release.cluster;" ::: "memory");
    if (!tile.spare) {
#pragma unroll
      for (int s = 0; s < PRE; s++) {
        if (elect()) tma3d(sb + OFF_W1 + s * WQKV_BYTES, &p.w, tn * 64, s * 64, 0, sb + BAR_FULL + s * 8);
        if (elect()) tma2d(sb + OFF_RING + s * SLOT, &p.x, s * 64, tm * 128, sb + BAR_FULL + s * 8);
        PROF(lane == 0, 64 + s);
      }
      if (elect()) {
#pragma unroll
        for (int s = 0; s < PRE; s++) mbar_expect_tx(sb + BAR_FULL + s * 8, SLOT + WQKV_BYTES);
      }
    }
  }
  if (warp) {
    const int wi = warp == 15 ? 0 : warp;
    const int cnt = wi < 7 ? 1 : wi < 13 ? 4 : 5;
#pragma unroll
    for (int i = 0; i < 4; i++)
      if ((i >= PRE || wi) && elect()) mbar_init(sb + OFF_BAR + wi * 32 + i * 8, cnt);
    asm volatile("fence.mbarrier_init.release.cluster;" ::: "memory");
  }
  __syncthreads();
  if (tile.spare) {
    if (warp == 0) {
      const unsigned tag = (ld_relaxed(&gs->spare[tile.sm & 3]) + 1) & 0xFFF;
      const unsigned long long t0 = gtime();
      uint4 r4;
      do {
        __nanosleep(2048);
        if (gtime() - t0 > WATCHDOG_NS) __trap();
        r4 = ld_relaxed4(&gs->rslot[tile.sm & 3][lane * 4]);
      } while (!__all_sync(~0u, (((r4.x ^ tag) | (r4.y ^ tag) | (r4.z ^ tag) | (r4.w ^ tag)) & 0xFFF) == 0));
      if (tid == 0) st_relaxed(&gs->spare[tile.sm & 3], tag);
    }
    return;
  }

  auto patch_row = [&](int pw) {
    const unsigned key = lds32(sb + OFF_MISC + 16);
    const int sel = 0xFFFF - (int)(key & 0xFFFF) - tm * 128;
    if (pw == 0 && sel >= 0 && sel < 128) {
      const unsigned k16 = key >> 16;
      const float rs = bf_round(sigmoidf_(__uint_as_float(((k16 & 0x8000u) ? (k16 & 0x7FFFu) : (~k16 & 0xFFFFu)) << 16)));
      float v[12];
      const float4* yp = gs->y[lane >> 4][0] + tn * 16 + (lane & 15);
      for (;;) {
#pragma unroll
        for (int i = 0; i < 3; i++) {
          const float4 u = ld_relaxed_f4(yp + i * 128);
          v[4 * i] = u.x; v[4 * i + 1] = u.y; v[4 * i + 2] = u.z; v[4 * i + 3] = u.w;
        }
        const float n = v[3] + v[7] + v[11];
        if (__all_sync(~0u, n + __shfl_xor_sync(~0u, n, 16) == 3.f * MOD_CTAS)) break;
        __nanosleep(Y_SLEEP);
      }
#pragma unroll
      for (int i = 0; i < 10; i++) v[i] = bf_round(bf_round(v[i] + __shfl_xor_sync(~0u, v[i], 16)) * rs);
      PROF(lane == 0, 24);
      mbar_wait(sb + BAR_X, 0);
      if (lane < 16) {
        uint4* xp = (uint4*)(smem + res_off(lane >> 3, sel >> 6) + (sel & 63) * 128 + (((lane ^ sel) & 7) << 4));
        const uint4 xv = *xp;
        *xp = make_uint4(pack2(bf_lo(xv.x) + v[0], bf_hi(xv.x) + v[1]), pack2(bf_lo(xv.y) + v[2], bf_hi(xv.y) + v[4]),
                         pack2(bf_lo(xv.z) + v[5], bf_hi(xv.z) + v[6]), pack2(bf_lo(xv.w) + v[8], bf_hi(xv.w) + v[9]));
      }
      __syncwarp();
      mbar_arrive_warp(sb + BAR_Y);
    }
  };
  if (wg == 3) {
    asm volatile("setmaxnreg.dec.sync.aligned.u32 24;");
    if (warp == 12) {
      mbar_wait(sb + BAR_GATE, 0);
      uint64_t slots = OR_SLOTS, deps = 0x8CBA98A9877654ull;
      uint32_t seen;
#pragma unroll 1
      for (int i = 0; i < 14; i++, deps >>= 4, slots >>= 4) {
        const uint32_t slab = i < 8 + (tn & 6) ? i : i + 2;
        if (!(i & 7)) { mbar_wait(sb + BAR_PUB + (i & 8), 0); seen = 0; }
        if (!(seen >> (slab & 7) * 4 & 4))
          while (!((seen = __shfl_sync(~0u, ld_relaxed(gs->cnt[(i & 8) * 2 + tm]), 0)) >> (slab & 7) * 4 & 4)) __nanosleep(B_SLEEP);
        if (i == 8) mbar_wait(sb + BAR_OWN, 0);
        mbar_wait(sb + BAR_EMPTY + ((uint32_t)deps & 15) * 8, (i & 7) < 5);
        if (elect()) bulk_load(sb + OFF_RING + ((uint32_t)slots & 15) * SLOT, gs->o[tm][slab], SLOT, sb + BAR_LAND + (i & 7) * 8);
        if (elect()) mbar_expect_tx(sb + BAR_LAND + (i & 7) * 8, SLOT);
        PROF(lane == 0, 44 + i);
        if (i == 8) PROF(lane == 0, 43);
      }
    } else if (warp == 13) {
#pragma unroll 1
      for (int g = PRE; g < 32; g++) {
        const bool reuse = (g >> 2) == 4;
        const uint32_t s = g & 3, full = sb + BAR_FULL + (g & 7) * 8, c0 = tn * 64 + (g & 16) * 32, c1 = (g < 16 ? g : g - 4 & 15) * 64;
        if (g < 4) while ((int)(clock32() - t_start) < g * ST1) {}
        mbar_wait(sb + BAR_EMPTY + (g + 4 & 7) * 8, (g + 4 >> 3 & 1) ^ 1);
        if (!reuse && elect()) tma2d(sb + OFF_RING + s * SLOT, &p.x, c1, tm * 128, full);
        if (elect()) tma3d(sb + OFF_W1 + s * WQKV_BYTES, &p.w, c0, c1, 0, full);
        if (elect()) mbar_expect_tx(full, reuse ? WQKV_BYTES : SLOT + WQKV_BYTES);
        PROF(lane == 0, 64 + g);
        const uint32_t i = g - RT_G0;
        if (i < 4 && elect()) {
          mbar_expect_tx(sb + BAR_RT + i * 8, i ? 8192 : 8192 + 4096);
          tma2d(sb + OFF_PK + i * 8192 + (i == 3) * 1024, &p.xr, ((i + RT_ROT) & 3) * 256, cta * 16, sb + BAR_RT + i * 8);
          if (i == 0) { bulk_load(sb + OFF_KVB, w_r, 2048, sb + BAR_RT); bulk_load(sb + OFF_KVB + 2048, gate_w, 2048, sb + BAR_RT); }
        }
        const uint32_t c = g - MOD_START;
        if (c == MOD_BUFS) mbar_wait(sb + BAR_RTD, 0);
        if (c < MOD_BUFS0 && mu < MOD_CTAS && elect()) {
          PROF(true, 192 + c);
          const uint32_t mb = c < MOD_BUFS ? c + 2 : c - MOD_BUFS, mfull = sb + BAR_MFULL + mb * 8, mdst = sb + OFF_V + mb * MOD_STEP;
          mbar_expect_tx(mfull, c ? 8192 : 8192 + 2048);
          tma3d(mdst, &p.gate, mu * 32, c * 16, 0, mfull); tma3d(mdst + 4096, &p.up, mu * 32, c * 16, 0, mfull);
        }
        const uint32_t pc = g - PF_MOD;
        if (pc < 16 && elect()) bulk_prefetch((cta & 64 ? w_up : w_gate) + (size_t)(pc * 64 + (cta & 63)) * F_, F_ * 2);
      }
      mbar_arrive_warp(sb + BAR_GATE);
      const uint32_t lowb = (1u << (tn & 6) * 4) - 1;
      uint64_t slabs = (uint64_t)((0xFEDCBA98u & lowb) | (0xFEDCBAu & ~lowb)) << 40 | (uint64_t)(8 + (tn ^ 1)) << 36 | (uint64_t)(8 + tn) << 32 | 0x76543210u;
      uint64_t deps = 0x8CBA98CBA9876554ull, ws = OW_SLOTS;
      uint32_t full = sb + BAR_OFULL, ph = 1;
#pragma unroll 1
      for (int g = 0; g < 16; g++, slabs >>= 4, deps >>= 4, ws >>= 4) {
        mbar_wait(sb + BAR_EMPTY + ((uint32_t)deps & 15) * 8, ph);
        if (elect()) tma3d(sb + OFF_RING + ((uint32_t)ws & 15) * SLOT, &p.wo, 0, ((uint32_t)slabs & 15) * 64, tn * 2, full);
        if (elect()) mbar_expect_tx(full, SLOT);
        PROF(lane == 0, 96 + g);
        if (g >> 1 == OWN / 2 && lane < 4) mbar_arrive(full);
        full += 8;
        if (full == sb + BAR_OFULL + 40) { full -= 40; ph ^= 1; }
      }
    } else if (warp == 14) {
      if (mu < MOD_CTAS) {
        uint32_t full = sb + BAR_MFULL + 16, dst = sb + OFF_MOD, ph = 0;
#pragma unroll 1
        for (int c = MOD_BUFS0; c < 24; c++) {
          mbar_wait(full + (BAR_MEMPTY - BAR_MFULL), ph);
          PROF(lane == 0, 192 + c);
          if (c < 16) {
            if (elect()) { tma3d(dst, &p.gate, mu * 32, c * 16, 0, full); tma3d(dst + 4096, &p.up, mu * 32, c * 16, 0, full); }
          } else if (elect()) tma3d(dst, &p.down, 0, mu * 32 + (c - 16) * 4, 0, full);
          if (elect()) mbar_expect_tx(full, 8192);
          full += 8; dst += MOD_STEP;
          if (full == sb + BAR_MFULL + MOD_BUFS0 * 8) { full -= MOD_BUFS * 8; dst = sb + OFF_MOD; ph ^= 1; }
        }
      }
      if (elect()) {
      mbar_wait(sb + BAR_IDX, 0);
      const bool paired = PAIRED && ld_relaxed(&gs->block[cta ^ 1]) == (blockIdx.x ^ 1);
      if (paired) mbar_expect_tx(sb + BAR_PEER, SLOT);
      mbar_expect_tx(sb + BAR_X, 32768);
      {
        if (mu < MOD_CTAS) {
          mbar_wait(sb + BAR_MEMPTY + 3 * 8, 0);
          mbar_wait(sb + BAR_MEMPTY + 4 * 8, 0);
          mbar_wait(sb + BAR_MEMPTY + 2 * 8, 1);
        } else mbar_wait(sb + BAR_GATE, 0);
#pragma unroll
        for (int i = 0; i < 4; i++) {
          if (i == 3) mbar_wait(sb + BAR_OEMPTY + 3 * 8, 0);
          tma2d(sb + res_off(i >> 1, i & 1), &p.xh, tn * 128 + (i >> 1) * 64, tm * 128 + (i & 1) * 64, sb + BAR_X);
        }
      }
      if (!paired) {
        mbar_wait(sb + BAR_OWN, 0);
        while (!(ld_relaxed(gs->cnt[16 + tm]) & 4u << (tn ^ 1) * 4)) __nanosleep(32);
        fence_acquire();
        fence_async_global();
        const uint32_t par = lds32(sb + OFF_MISC + 24);
        for (uint32_t ph = !mbar_test(sb + BAR_MFULL, 1), bad = 1; bad & 1; ph ^= 1) {
          fence_async_smem();
          mbar_expect_tx(sb + BAR_MFULL, SLOT);
          bulk_load(sb + OFF_PK, gs->o[tm][8 + (tn ^ 1)], SLOT, sb + BAR_MFULL);
          mbar_wait(sb + BAR_MFULL, ph);
          bad = 0;
#pragma unroll 1
          for (int i = 0; i < 512; i++) bad |= lds32(sb + OFF_PK + i * 32 + (i & 28)) ^ par;
        }
        mbar_arrive(sb + BAR_PEER);
      }
      }
    } else {
#pragma unroll 1
      for (int i = 2; i < 9; i++)
        if (elect()) asm volatile("prefetch.tensormap [%0];" ::"l"(&p.x + i) : "memory");
      mbar_wait_bounded(sb + BAR_DONE, 0);
    }
  } else if (wg == 2) {
    asm volatile("setmaxnreg.dec.sync.aligned.u32 40;");
    const int mw = warp & 3;
    if (mw == 0) {
      const unsigned tag = (ld_relaxed(&gs->rslot[tn][cta]) + 1) & 0xFFF;
#pragma unroll
      for (int i = 0; i < 2; i++)
        if (lane < 28) ((float4*)gs)[cta * 56 + i * 28 + lane] = make_float4(0.f, 0.f, 0.f, 0.f);
      if (lane == 29) gs->block[cta] = blockIdx.x;
      fence_release();
      nb_sync(NB_KEY, 160);
      const uint4 k4 = lds128(sb + OFF_MISC);
      if (lane < 8) st_relaxed(&gs->rslot[lane][cta], max(max(k4.x, k4.y), max(k4.z, k4.w)) | tag);
      if (lane < 16) st_relaxed(&gs->gslot[cta * 16 + lane], lds32(sb + OFF_G + lane * 4) | tag);
      PROF(lane == 0, 20);
      uint4 r4;
      do {
        __nanosleep(RT_SLEEP);
        r4 = ld_relaxed4(&gs->rslot[tn][lane * 4]);
      } while (!__all_sync(~0u, (((r4.x ^ tag) | (r4.y ^ tag) | (r4.z ^ tag) | (r4.w ^ tag)) & 0xFFF) == 0));
      const int c0 = 0xFFF0 - lane * 64;
      unsigned key = max(max((r4.x & 0xFFFF0000u) | (c0 + ((r4.x >> 12) & 15)), (r4.y & 0xFFFF0000u) | (c0 - 16 + ((r4.y >> 12) & 15))),
                         max((r4.z & 0xFFFF0000u) | (c0 - 32 + ((r4.z >> 12) & 15)), (r4.w & 0xFFFF0000u) | (c0 - 48 + ((r4.w >> 12) & 15))));
      key = __reduce_max_sync(~0u, key);
      if (elect()) {
        sts32(sb + OFF_MISC + 16, key);
        sts32(sb + OFF_MISC + 24, tag & 1);
        if (mu < MOD_CTAS) {
          const __nv_bfloat16* row = px + (size_t)(0xFFFF - (key & 0xFFFF)) * D_;
          bulk_load(sb + OFF_XSEL, row, 1024, sb + BAR_MFULL + 16);
          bulk_load(sb + OFF_XSEL + MOD_STEP, row + 512, 1024, sb + BAR_MFULL + 16);
        }
      }
      PROF(lane == 0, 21);
      do {
        r4 = ld_relaxed4(&gs->gslot[tm * 128 + lane * 4]);
      } while (!__all_sync(~0u, (((r4.x ^ tag) | (r4.y ^ tag) | (r4.z ^ tag) | (r4.w ^ tag)) & 0xFFF) == 0));
      sts128(sb + OFF_G + lane * 16, r4.x & 0xFFFF0000u, r4.y & 0xFFFF0000u, r4.z & 0xFFFF0000u, r4.w & 0xFFFF0000u);
      fence_acquire();
      __syncwarp();
    }
    PROF(tid == 256, 22);
    if (mu >= MOD_CTAS) {
      mbar_arrive_warp(sb + BAR_IDX);
    } else {
      const uint32_t wp = sb + OFF_V + (mw >> 1) * 4096 + (mw & 1) * 512 + lane * 16;
      uint32_t mp = sb + OFF_XSEL + (mw & 1) * 64 + (lane >> 2) * 8, mc = 128;
      float acc[8] = {0.f, 0.f, 0.f, 0.f, 0.f, 0.f, 0.f, 0.f};
      uint32_t b = 2, ph = 0;
#pragma unroll 1
      for (int c = 0; c < 24; c++) {
        mbar_wait(sb + BAR_MFULL + b * 8, ph);
        PROF_C(tid == 256, 216 + c);
        const uint32_t a = wp + b * MOD_STEP;
        const uint2 m = lds64(mp);
        const uint4 w0 = lds128(a), w1 = lds128(a + 1024), w2 = lds128(a + 2048), w3 = lds128(a + 3072);
        mp += c == 7 ? MOD_STEP - 1024 + 128 : mc;
        const uint32_t m0 = dup_lo(m.x), m1 = dup_hi(m.x), m2 = dup_lo(m.y), m3 = dup_hi(m.y);
        uint4 q = make_uint4(mul_bf2(w0.x, m0), mul_bf2(w0.y, m0), mul_bf2(w0.z, m0), mul_bf2(w0.w, m0));
        q = make_uint4(fma_bf2(w1.x, m1, q.x), fma_bf2(w1.y, m1, q.y), fma_bf2(w1.z, m1, q.z), fma_bf2(w1.w, m1, q.w));
        q = make_uint4(fma_bf2(w2.x, m2, q.x), fma_bf2(w2.y, m2, q.y), fma_bf2(w2.z, m2, q.z), fma_bf2(w2.w, m2, q.w));
        mbar_arrive_warp(sb + BAR_MEMPTY + b * 8 + (w3.x & zero));
        q = make_uint4(fma_bf2(w3.x, m3, q.x), fma_bf2(w3.y, m3, q.y), fma_bf2(w3.z, m3, q.z), fma_bf2(w3.w, m3, q.w));
        if (++b == 5) b = c < 3 ? 0 : 2;
        if (b == 2) ph ^= 1;
        acc[0] += bf_lo(q.x); acc[1] += bf_hi(q.x); acc[2] += bf_lo(q.y); acc[3] += bf_hi(q.y);
        acc[4] += bf_lo(q.z); acc[5] += bf_hi(q.z); acc[6] += bf_lo(q.w); acc[7] += bf_hi(q.w);
        if (c == 15) {
          const uint32_t ft = fresh_tid(), fl = ft & 31;
          sts32(sb + OFF_PART + (ft & 96) * 4 + ((ft & 3) * 8 + (fl >> 2)) * 4, __float_as_uint(butterfly8(acc, fl, 4)));
          nb_sync(NB_MODW, 128);
          const float* part = (const float*)(smem + OFF_PART) + fl;
          const float gp = bf_round(part[0] + part[32]), up = bf_round(part[64] + part[96]);
          *(__nv_bfloat16*)(smem + OFF_PART + 512 + fl * 2) = __float2bfloat16_rn(bf_round(gp * sigmoidf_(gp)) * up);
          __syncwarp();
          mp = sb + OFF_PART + 512; mc = 8;
#pragma unroll
          for (int i = 0; i < 8; i++) acc[i] = 0.f;
          PROF(lane == 0 && mw == 0, 23);
        }
      }
      float4* yacc = gs->y[tn & 1][0] + (fresh_tid() & 127);
      red_add4(yacc, acc[0], acc[1], acc[2], 1.f);
      red_add4(yacc + 128, acc[3], acc[4], acc[5], 1.f);
      red_add4(yacc + 256, acc[6], acc[7], 0.f, 1.f);
      PROF(lane == 0 && mw == 0, 25);
    }
    mbar_wait(sb + BAR_GATE, 0);
    mbar_wait(sb + BAR_IDX, 0);
    verify_tiles(sb, gs, tm, tn, mw, lane, [&]() { patch_row(mw); });
  } else {
    asm volatile("setmaxnreg.inc.sync.aligned.u32 224;");
    const int w = warp & 3, wt = tid & 127;
    const int nb_self = NB_WG0 + wg;
    const uint64_t da0 = mkdesc(sb + OFF_RING, 16, 1024, 1), db0 = mkdesc(sb + OFF_RING, 8192, 1024, 1);

    if (wg == 1) {
      sts128(sb + OFF_ONES - (w >> 1) * 9216 + (w & 1) * 512 + lane * 16, 0x3F803F80u, 0x3F803F80u, 0x3F803F80u, 0x3F803F80u);
      sts32(sb + OFF_MISC + 20, 0x3FB8AA3Bu);
      fence_async_smem();
      float s[8] = {0.f, 0.f, 0.f, 0.f, 0.f, 0.f, 0.f, 0.f};
      uint32_t mask = 0xffff0000u;
#pragma unroll 1
      for (int i = 0; i < 4; i++) {
        const uint32_t u = (i + RT_ROT) & 3;
        mbar_wait(sb + BAR_RT + i * 8, 0);
        const uint4 wr = lds128(sb + OFF_KVB + u * 512 + lane * 16), gw = lds128(sb + OFF_KVB + 2048 + u * 512 + lane * 16);
        uint4 xv[4];
#pragma unroll
        for (int r = 0; r < 4; r++) xv[r] = lds128(sb + OFF_PK + i * 8192 + (i == 3) * 1024 + (w * 4 + r) * 512 + lane * 16);
        const float wf[16] = {bf_lo(wr.x), bf_hi(wr.x), bf_lo(wr.y), bf_hi(wr.y), bf_lo(wr.z), bf_hi(wr.z), bf_lo(wr.w), bf_hi(wr.w),
                              bf_lo(gw.x), bf_hi(gw.x), bf_lo(gw.y), bf_hi(gw.y), bf_lo(gw.z), bf_hi(gw.z), bf_lo(gw.w), bf_hi(gw.w)};
#pragma unroll
        for (int r = 0; r < 4; r++) {
          const uint4 xq = xv[r];
          const float xf[8] = {bf_lo(xq.x), __uint_as_float(xq.x & mask), bf_lo(xq.y), bf_hi(xq.y), bf_lo(xq.z), bf_hi(xq.z), bf_lo(xq.w), bf_hi(xq.w)};
#pragma unroll
          for (int j = 0; j < 8; j++) { s[2 * r] = fmaf(xf[j ^ 1], wf[j ^ 1], s[2 * r]); s[2 * r + 1] = fmaf(xf[j ^ 1], wf[8 + (j ^ 1)], s[2 * r + 1]); }
          mask = ((__float_as_uint(s[2 * r]) | __float_as_uint(s[2 * r + 1])) & zero) | 0xffff0000u;
        }
      }
      mbar_arrive_warp(sb + BAR_RTD + (__float_as_uint(s[6]) & zero));
      float v = butterfly8(s, lane, 1);
      PROF_C(wt == 0 && v != 12345.f, 19);
      v += __shfl_xor_sync(~0u, v, 8);
      v = bf_round(v + __shfl_xor_sync(~0u, v, 16));
      const unsigned rb = __float_as_uint(v) >> 16, row = w * 4 + ((lane & 7) >> 1);
      unsigned key = (lane & 1) ? 0u : ((((rb & 0x8000u) ? (~rb & 0xFFFFu) : (rb | 0x8000u)) << 16) | ((15 - row) << 12));
      key = __reduce_max_sync(~0u, key);
      if (lane == 0) sts32(sb + OFF_MISC + w * 4, key);
      if (lane < 8 && (lane & 1)) sts32(sb + OFF_G + row * 4, __float_as_uint(bf_round(sigmoidf_(v))));
      nb_arrive(NB_KEY, 160);
      nb_sync(NB_ORDER_AB, 256);
    }
    uint4* const kvacc = &gs->kv[wg][tn][0][wt];
    float aq[64];
    uint32_t su[9];
    {
      float ak[64], av[64], c[36];
      uint32_t pk[8][4];
      PROF_C(wt == 0, 1 + wg * 8);
#pragma unroll 1
      for (int g = 0; g < 16; g++) {
        const uint64_t dx = da0 + (g & 3) * (SLOT >> 4), dw = da0 + ((OFF_W1 >> 4) + (g & 3) * (WQKV_BYTES >> 4));
        mbar_wait(sb + BAR_FULL + (g & 7) * 8, g >> 3);
        if (g == 0) PROF_C(wt == 0, 2 + wg * 8);
        wg_fence();
#pragma unroll
        for (int kk = 0; kk < 4; kk++) mma128<1, 0>(ak, dw + (512 + kk * 128), dx + kk * 2, kk ? 1 : g);
        wg_commit();
        wg_wait<1>();
        if (g) mbar_arrive_warp(sb + BAR_EMPTY + (g - 1 & 7) * 8);
        wg_fence();
#pragma unroll
        for (int kk = 0; kk < 4; kk++) mma128<1, 0>(av, dw + (1024 + kk * 128), dx + kk * 2, kk ? 1 : g);
        wg_commit();
#pragma unroll
        for (int kk = 0; kk < 4; kk++) mma128<1, 0>(aq, dw + kk * 128, dx + kk * 2, kk ? 1 : g);
        wg_commit();
      }
      if (wg == 0) nb_arrive(NB_ORDER_AB, 256);
      mbar_wait(sb + BAR_IDX, 0);
      if (wg == 1) nb_sync(NB_STG, 256);
      wg_wait<2>();
      pin(ak);
      PROF_C(wt == 0, 3 + wg * 8);
      const uint32_t va = sb + OFF_V + (w * 16 + (lane & 15)) * 128;
      uint32_t lk[8];
#pragma unroll
      for (int u = 0; u < KL; u++) lk[u] = 0x3FB8AA3Bu;
#pragma unroll
      for (int u = 0; u < 8; u++) {
#pragma unroll
        for (int i = 0; i < 4; i++) pk[u][i] = phi2(ak[8 * u + 2 * i], ak[8 * u + 2 * i + 1], __uint_as_float(lk[u]));
        if (u == VK) { wg_wait<1>(); pin(av); }
        if (u == MM) { wg_wait<0>(); mbar_arrive_warp(sb + BAR_EMPTY + 7 * 8); }
        const uint32_t z = mism(pk[u][0], pk[u][1], 0) | mism(pk[u][2], pk[u][3], 0);
#pragma unroll
        for (int t = u < VK ? 8 : (u - VK) * 8 / (8 - VK); t < (u - VK + 1) * 8 / (8 - VK); t++) {
          const float* v = &av[8 * t];
          stsm4(va + (t >> 2) * 9216 + ((((lane >> 4) + 2 * (t & 3)) ^ (lane & 7)) << 4) + (z & zero), pack2(v[0], v[1]), pack2(v[2], v[3]), pack2(v[4], v[5]), pack2(v[6], v[7]));
        }
        if (u + KL < 8) lk[u + KL] = lds32(sb + OFF_MISC + 20 + (u < VK ? z & zero : 0));
      }
      fence_async_smem();
      nb_sync(nb_self, 128);
      PROF_C(wt == 0, 8 + wg * 8);
      const uint64_t dv = mkdesc(sb + OFF_V, 16, 1024, 1);
      wg_fence();
#pragma unroll
      for (int kk = 0; kk < 8; kk++) mma_ktv(c, pk[kk], dv + ((kk >> 2) * 576 + (kk & 3) * 2), kk ? 1 : 0);
      wg_commit();
      if (wg == 1) nb_arrive(NB_ORDER_BO, 256);
      wg_wait<0>();
      pin(c); pin(aq);
      PROF_C(wt == 0, 4 + wg * 8);
#pragma unroll
      for (int i = 0; i < 8; i++) {
        const int j = (i & 3) * 4 + (i >> 2) * 2;
        su[i] = w >= 2 ? pack2(c[16 + j], c[17 + j]) : pack2(c[j], c[j + 1]);
      }
      su[8] = pack2(c[32], c[34]);
#pragma unroll
      for (int u = 0; u < 3; u++)
        if (u < R0 || wg) red_add_bf(kvacc + u * 128, su[3 * u], su[3 * u + 1], su[3 * u + 2]);
    }
    const uint32_t par = lds32(sb + OFF_MISC + 24);
    {
      const bool paired = PAIRED && ld_relaxed(&gs->block[cta ^ 1]) == (blockIdx.x ^ 1);
      uint4 kv[3];
      int tries = wg ? 0 : RETRY + 1;
      const uint8_t* gl = smem + OFF_MISC + 20;
      asm volatile("" : "+l"(gl));
      const uint32_t l2e = ld_generic(gl);
    auto stage_kv = [&]() {
      const uint32_t kb = sb + OFF_KVB + w * 256, ka = kb + (lane & 3) * KVB_N + (lane >> 2) * 16;
      sts128(ka, kv[0].x, kv[0].y, kv[0].z, kv[1].x);
      sts128(ka + 128, kv[1].y, kv[1].z, kv[2].x, kv[2].y);
      sts32(kb + 4 * KVB_N + lane * 4, dup_lo(kv[2].z));
      sts32(kb + 4 * KVB_N + 128 + lane * 4, dup_hi(kv[2].z));
      return __all_sync(~0u, (kv[0].w & kv[1].w & kv[2].w) == 0x41804180u && (kv[0].w | kv[1].w | kv[2].w) == 0x41804180u);
    };
      const uint32_t qa = sb + OFF_PK + ((lane >> 4) * 8 + (lane & 7)) * 128 + (((2 * w + ((lane >> 3) & 1)) ^ (lane & 7)) << 4);
      uint32_t lq[8];
#pragma unroll
      for (int u = 0; u < QA; u++) lq[u] = l2e;
#pragma unroll
      for (int u = 0; u < 8; u++) {
        uint32_t r[4];
#pragma unroll
        for (int i = 0; i < 4; i++) r[i] = phi2(aq[8 * u + 2 * i], aq[8 * u + 2 * i + 1], __uint_as_float(lq[u]));
        stsm4t(qa + u * 2048, r[0], r[1], r[2], r[3]);
        if (u + 1 == KF && wg) {
          const uint4* src = kvacc + (r[3] & zero);
#pragma unroll
          for (int i = 0; i < 3; i++) kv[i] = ld_relaxed4(src + i * 128);
        }
        const int ru = u / RS + R0;
        if (u % RS == RS - 1 && ru < 3 && !wg) red_add_bf(kvacc + ru * 128, su[3 * ru], su[3 * ru + 1], su[3 * ru + 2]);
        if (u + QA < 8) lq[u + QA] = lds32(sb + OFF_MISC + 20);
      }
      PROF_C(wt == 0, 34 + wg * 2);
      bool have = wg && stage_kv();
      for (; !have; tries++) {
        if (tries > RETRY)
          while (ld_relaxed((const unsigned*)&(kvacc - lane)[256 + 31].w) != 0x41804180u) __nanosleep(wg ? KV_SLEEP : KV_SLEEP_A);
#pragma unroll
        for (int i = 0; i < 3; i++) kv[i] = ld_relaxed4(kvacc + i * 128);
        have = stage_kv();
      }
      PROF_C(wt == 0, 5 + wg * 8);
      fence_async_smem();
      nb_sync(nb_self, 128);
      float o[2][2][20];
      const uint64_t dq = mkdesc(sb + OFF_PK, 16, 1024, 1), dz = mkdesc(sb + OFF_KVB, 128, KVB_N, 0);
      wg_fence();
#pragma unroll
      for (int m = 0; m < 2; m++) {
#pragma unroll
        for (int h = 0; h < 2; h++)
#pragma unroll
          for (int kk = 0; kk < 2; kk++) mma_qkvz(o[m][h], dq + (m * 512 + h * 4 + kk * 2), dz + (h * 32 + kk * 16), kk);
        wg_commit();
      }
      if (wg && elect()) red_add(gs->cnt[16 + tm], 1u << tn * 4);
      uint32_t tag[2][4];
#pragma unroll
      for (int i = 0; i < 8; i++) tag[i >> 2][i & 3] = (lane >> 3) == (i & 3) && ((lane ^ (lane >> 3)) & 1) == (i >> 2);
      uint32_t gr[8];
      const uint8_t* ga = smem + OFF_G + (w * 16 + (lane >> 2)) * 4;
      asm volatile("" : "+l"(ga));
#pragma unroll
      for (int i = 0; i < OA; i++) gr[i] = ld_generic(ga + (i >> 2) * 256 + (i & 1) * 32);
      const uint32_t oo = w * 1024 + (lane >> 2) * 64 + (((lane ^ (lane >> 3)) & 3) << 4);
      uint8_t* const og = (uint8_t*)gs->o[tm][wg * 8 + tn] + oo;
      uint32_t ob[8][4];
#pragma unroll
      for (int m = 0; m < 2; m++) {
        if (m == 0) wg_wait<1>(); else wg_wait<0>();
        pin(o[m][0]); pin(o[m][1]);
        if (m && wg) mbar_arrive_warp(sb + BAR_PUB + 8);
        if (m && !wg) nb_arrive(NB_STG, 256);
        if (m && wg) nb_arrive(NB_HOLD, 256);
        if (m && wg && paired && elect()) mbar_arrive_peer(peer_addr(sb + BAR_PA));
        if (m == 0) PROF_C(wt == 0, 6 + wg * 8);
#pragma unroll
        for (int u = 0; u < 4; u++) {
          const int h = u >> 1, i = u & 1;
          const float* on = o[m][h];
          const float sc = __uint_as_float(gr[m * 4 + u]) * rcp(on[16 + 2 * i] + 1e-6f);
          const uint32_t sc2 = pack2(sc, sc);
#pragma unroll
          for (int j = 0; j < 4; j++) {
            const uint32_t v = mul_bf2(pack2(on[4 * j + 2 * i], on[4 * j + 2 * i + 1]), sc2);
            asm("lop3.b32 %0, %1, %2, %3, 0xB8;" : "=r"(ob[m * 4 + u][j]) : "r"(v), "r"(tag[i][j]), "r"(par));
          }
          st_relaxed4(og + (h * 8192 + m * 4096 + i * 512), ob[m * 4 + u]);
          if (wg) sts128(sb + OFF_V + oo + (h * 8192 + m * 4096 + i * 512), ob[m * 4 + u][0], ob[m * 4 + u][1], ob[m * 4 + u][2], ob[m * 4 + u][3]);
          const int n = m * 4 + u + OA;
          if (n < 8) gr[n] = ld_generic(ga + (n >> 2) * 256 + (n & 1) * 32);
        }
      }
      if (!wg) {
        if (elect()) red_add(gs->cnt[tm], 1u << tn * 4);
        mbar_arrive_warp(sb + BAR_PUB);
      }
      PROF(wt == 0, 17 + wg);
      if (wg) {
        fence_async_smem();
        __syncwarp();
        mbar_arrive_warp(sb + BAR_OWN);
        PROF(wt == 0, 15);
        if (paired) {
          const uint32_t pb = peer_addr(sb);
          mbar_wait(sb + BAR_PA, 0);
#pragma unroll
          for (int u = 0, z = 0; u < 8; u++) {
            if (u) z = lds32(sb + OFF_ONES) & zero;
            st_async4(pb + OFF_PK + oo + ((u >> 1 & 1) * 8192 + (u >> 2) * 4096 + (u & 1) * 512) + z, ob[u], pb + BAR_PEER);
          }
        }
      }
    }
    if (wg == 0) {
      float acc[2][64];
      nb_sync(NB_ORDER_BO, 256);
      PROF_C(wt == 0, 26);
      uint32_t xr[2][8][4], q[2][2];
      const uint32_t ta = sb + (uint32_t)(w * 16 + (lane & 15)) * 128;
      const uint64_t do0 = mkdesc(sb + OFF_RING, 16, 512, 2);
      uint64_t xs = OA_SLOTS, ws = OW_SLOTS;
#pragma unroll 1
      for (int g = 0; g < 13 - TL; g++, xs >>= 4, ws >>= 4) {
        const uint32_t r = g * 52 >> 8, s = g - r * 5;
        const uint64_t da = do0 + ((uint32_t)xs & 15) * (SLOT >> 4), db = db0 + ((uint32_t)ws & 15) * (SLOT >> 4);
        if (g == OWN) mbar_wait(sb + BAR_OWN, 0);
        if (g == PEER) { PROF(wt == 0, 39); mbar_wait(sb + BAR_PEER, 0); PROF(wt == 0, 40); fence_async_smem(); }
        if (g == HOLD) nb_sync(NB_HOLD, 256);
        mbar_wait(sb + BAR_OFULL + s * 8, r & 1);
        wg_fence();
#pragma unroll
        for (int kk = 0; kk < 4; kk++)
#pragma unroll
          for (int m = 0; m < 2; m++) mma128<0, 1>(acc[m], da + (m * 256 + (kk >> 1) * 512 + (kk & 1) * 2), db + kk * 128, kk ? 1 : g);
        wg_commit();
        wg_wait<1>();
        if (g) mbar_arrive_warp(sb + BAR_OEMPTY + (s ? s - 1 : 4) * 8);
      }
      PROF(wt == 0, 29);
      mbar_wait(sb + BAR_X, 0);
      PROF(wt == 0, 30);
      const int selw = ((0xFFFF - (int)(lds32(sb + OFF_MISC + 16) & 0xFFFF)) >> 4) - tm * 8 - w;
#pragma unroll
      for (int u = 0; u < 4; u++) {
        const int m = u >> 1, g = 13 - TL + u;
        const float g1 = 1.f - __uint_as_float(lds32(sb + OFF_G + (m * 64 + w * 16 + (u & 1) * 8 + (lane >> 2)) * 4));
        q[m][u & 1] = pack2(g1, g1);
#pragma unroll
        for (int j = 0; j < 4; j++) ldsm4(ta + res_off(u & 1, m) + ((((lane >> 4) + 2 * j) ^ (lane & 7)) << 4), xr[m][(u & 1) * 4 + j]);
        if (u == 3) break;
        mbar_wait(sb + BAR_OFULL + g % 5 * 8, g / 5 & 1);
        wg_fence();
#pragma unroll
        for (int kk = 0; kk < 4; kk++)
#pragma unroll
          for (int mm = 0; mm < 2; mm++)
            mma128<0, 1>(acc[mm], do0 + ((OA_SLOTS >> g * 4 & 15) * (SLOT >> 4) + mm * 256 + (kk >> 1) * 512 + (kk & 1) * 2), db0 + ((OW_SLOTS >> g * 4 & 15) * (SLOT >> 4) + kk * 128), 1);
        wg_commit();
        wg_wait<1>();
        if (g <= 11) mbar_arrive_warp(sb + BAR_OEMPTY + (g + 4) % 5 * 8);
      }
#pragma unroll
      for (int m = 0; m < 2; m++) {
#pragma unroll
        for (int g = 16 - TL; g < 16; g++) {
          if (m == 0) { mbar_wait(sb + BAR_OFULL + g % 5 * 8, g / 5 & 1); wg_fence(); }
#pragma unroll
          for (int kk = 0; kk < 4; kk++)
            mma128<0, 1>(acc[m], do0 + ((OA_SLOTS >> g * 4 & 15) * (SLOT >> 4) + m * 256 + (kk >> 1) * 512 + (kk & 1) * 2), db0 + ((OW_SLOTS >> g * 4 & 15) * (SLOT >> 4) + kk * 128), 1);
        }
        wg_commit();
      }
      mbar_arrive_warp(sb + BAR_DONE);
      const uint32_t tb = sb + w * 2048 + (lane >> 3) * 128 + (((lane ^ (lane >> 3)) & 7) << 4), tx = lane & 4 ? 64 : -64;
      uint8_t* og = (uint8_t*)pout + (size_t)(tm * 128 + w * 16 + (lane >> 3)) * 2048 + tn * 256 + (lane & 7) * 16;
      if (EC > 1) asm volatile("" : "+l"(og)::"memory");
#pragma unroll
      for (int m = 0; m < 2; m++) {
        if (selw == 4 * m) {
          mbar_wait(sb + BAR_Y, 0);
#pragma unroll
          for (int j = 0; j < 8; j++) ldsm4(ta + res_off(j >> 2, m) + ((((lane >> 4) + 2 * (j & 3)) ^ (lane & 7)) << 4), xr[m][j]);
        }
        if (m == 0) wg_wait<1>(); else wg_wait<0>();
        if (m) PROF(wt == 0, 31);
#pragma unroll
        for (int h = 0; h < 2; h++) {
#pragma unroll
          for (int j = 4 * h; j < 4 * h + 4; j++) {
            const float* v = &acc[m][8 * j];
            stsm4(ta + res_off(h, m) + ((((lane >> 4) + 2 * (j & 3)) ^ (lane & 7)) << 4),
                  fma_bf2(xr[m][j][0], q[m][0], pack2(v[0], v[1])), fma_bf2(xr[m][j][1], q[m][1], pack2(v[2], v[3])),
                  fma_bf2(xr[m][j][2], q[m][0], pack2(v[4], v[5])), fma_bf2(xr[m][j][3], q[m][1], pack2(v[6], v[7])));
          }
          if (m) {
            __syncwarp();
            uint4 t[4];
#pragma unroll
            for (int j = 0; j < 4; j++) t[j] = lds128(tb + res_off(h, m) + j * 512 - (j & 1) * tx);
#pragma unroll
            for (int j = 0; j < 4; j++) *(uint4*)(og + (m * 64 + j * 4) * 2048 + h * 128) = t[j];
          } else {
            fence_async_smem();
            __syncwarp();
            if (elect()) tma2d_store(&p.out, sb + res_off(h, m) + w * 2048, tn * 128 + h * 64, tm * 128 + m * 64 + w * 16);
          }
          if (!EC && m && h && elect()) { bulk_commit(); asm volatile("cp.async.bulk.wait_group.read 0;" ::: "memory"); }
          if (EC && !m && h && elect()) bulk_commit();
          if (EC && m && h && elect()) asm volatile("cp.async.bulk.wait_group.read 0;" ::: "memory");
        }
        if (!m) PROF(wt == 0, 33);
      }
      PROF(wt == 0, 32);
    }
  }
}

typedef CUresult (*EncodeFn)(CUtensorMap*, CUtensorMapDataType, cuuint32_t, void*, const cuuint64_t*, const cuuint64_t*, const cuuint32_t*,
                             const cuuint32_t*, CUtensorMapInterleave, CUtensorMapSwizzle, CUtensorMapL2promotion, CUtensorMapFloatOOBfill);

void encode(EncodeFn fn, CUtensorMap* m, const void* ptr, int rank, const cuuint64_t* dims, const cuuint64_t* strides, const cuuint32_t* box,
            CUtensorMapSwizzle sw, CUtensorMapDataType dt = CU_TENSOR_MAP_DATA_TYPE_BFLOAT16) {
  const cuuint32_t es[3] = {1, 1, 1};
  fn(m, dt, rank, const_cast<void*>(ptr), dims, strides, box, es, CU_TENSOR_MAP_INTERLEAVE_NONE, sw,
     CU_TENSOR_MAP_L2_PROMOTION_L2_128B, CU_TENSOR_MAP_FLOAT_OOB_FILL_NONE);
}

}

extern "C" void kernel_launch(void* const* d_in, const int* in_sizes, int n_in, void* d_out, int out_size) {
  (void)in_sizes; (void)n_in; (void)out_size;
  EncodeFn fn = nullptr;
  cudaDriverEntryPointQueryResult qr;
  cudaGetDriverEntryPoint("cuTensorMapEncodeTiled", (void**)&fn, cudaEnableDefault, &qr);

  Params p;
  {
    const cuuint64_t dims[2] = {D_, S_}, str[1] = {D_ * 2};
    const cuuint32_t box[2] = {64, 128}, box_st[2] = {64, 16}, box_r[2] = {256, 16}, box_h[2] = {64, 64};
    encode(fn, &p.xh, d_in[0], 2, dims, str, box_h, CU_TENSOR_MAP_SWIZZLE_128B);
    encode(fn, &p.xr, d_in[0], 2, dims, str, box_r, CU_TENSOR_MAP_SWIZZLE_NONE);
    encode(fn, &p.x, d_in[0], 2, dims, str, box, CU_TENSOR_MAP_SWIZZLE_128B);
    encode(fn, &p.out, d_out, 2, dims, str, box_st, CU_TENSOR_MAP_SWIZZLE_128B);
  }
  {
    const cuuint64_t dims[3] = {D_, D_, 3}, str[2] = {3 * D_ * 2, D_ * 2};
    const cuuint32_t box[3] = {64, 64, 3};
    encode(fn, &p.w, d_in[1], 3, dims, str, box, CU_TENSOR_MAP_SWIZZLE_128B);
  }
  {
    const cuuint64_t dims[3] = {64, D_, D_ / 64}, str[2] = {D_ * 2, 128};
    const cuuint32_t box[3] = {64, 64, 2};
    encode(fn, &p.wo, d_in[2], 3, dims, str, box, CU_TENSOR_MAP_SWIZZLE_128B);
  }
  {
    const cuuint64_t dims[3] = {F_, D_ / 4, 4}, str[2] = {F_ * 8, F_ * 2};
    const cuuint32_t box[3] = {32, 16, 4};
    encode(fn, &p.gate, d_in[5], 3, dims, str, box, CU_TENSOR_MAP_SWIZZLE_NONE);
    encode(fn, &p.up, d_in[6], 3, dims, str, box, CU_TENSOR_MAP_SWIZZLE_NONE);
  }
  {
    const cuuint64_t dims[3] = {D_ / 4, F_, 2}, str[2] = {D_ * 2, D_};
    const cuuint32_t box[3] = {256, 4, 2};
    encode(fn, &p.down, d_in[7], 3, dims, str, box, CU_TENSOR_MAP_SWIZZLE_NONE, CU_TENSOR_MAP_DATA_TYPE_UINT32);
  }
  void* gs = nullptr;
  cudaGetSymbolAddress(&gs, g_scratch);
  typedef const __nv_bfloat16* bp;
  int dev = 0, sms = 0;
  cudaGetDevice(&dev);
  cudaDeviceGetAttribute(&sms, cudaDevAttrMultiProcessorCount, dev);
  const bool by_sm = BYSM && sms == NGRID;
  const auto kernel = by_sm ? fused_kernel<true> : fused_kernel<false>;
  cudaFuncSetAttribute(kernel, cudaFuncAttributeMaxDynamicSharedMemorySize, SMEM_BYTES);
  kernel<<<by_sm ? NGRID : NCTA, NTHREADS, SMEM_BYTES, cudaStreamPerThread>>>((bp)d_in[0], (Scratch*)gs, (bp)d_in[5], (bp)d_in[6], (bp)d_in[4], (bp)d_in[8], (__nv_bfloat16*)d_out, p);
}
```

```cpp
#include <cuda_runtime.h>
#include <cuda.h>
#include <cuda_bf16.h>
#include <stdint.h>
#include <stddef.h>

namespace {

constexpr int S_ = 2048, D_ = 1024, F_ = 3584;
constexpr int NCTA = 128, NGRID = 132, NTHREADS = 512;
#define NOMOD 0
constexpr int MOD_CTAS = NOMOD ? 0 : F_ / 32;

#define PRE 2
#define ST1 800
#define RT_G0 2
#define RT_ROT 1
#define RT_SLEEP 500
#define PF_MOD 8
#define MOD_START 10
#define MM 3
#define HOLD 5
#define KF 6
#define QA 3
#define R0 1
#define OA 3
#define Y_SLEEP 200
#define VK 1
#define KL 3
#define RS 2
#define RETRY 1
#define KV_SLEEP_A 64
#define KV_SLEEP 50
#define TL 3
#define B_SLEEP 32
#define PAIRED 1
#define BYSM 1

constexpr uint32_t SLOT = 16384, WQKV_BYTES = 24576;
constexpr int MOD_BUFS = 3, MOD_BUFS0 = MOD_BUFS + 2;
static_assert(MOD_START + MOD_BUFS0 <= 16, "first FFN round is requested during W1");
constexpr uint32_t OFF_RING = 0, OFF_W1 = 4 * SLOT;
constexpr uint64_t OA_SLOTS = 0x0AB210AB21098210ull, OW_SLOTS = 0x4376543765437654ull;
constexpr uint32_t OFF_RES = OFF_RING + 8 * SLOT;
constexpr uint32_t OFF_PK = 10 * SLOT;
constexpr uint32_t OFF_V = 11 * SLOT;
constexpr uint32_t OFF_ONES = OFF_V + 9216 + 8192;
constexpr uint32_t MOD_STEP = 9216, OFF_MOD = OFF_V + 2 * MOD_STEP;
constexpr __host__ __device__ uint32_t mod_off(uint32_t b) { return b < 2 ? OFF_PK + b * 8192 : OFF_V + b * MOD_STEP; }
constexpr __host__ __device__ uint32_t res_off(int h, int m) { return h & m ? OFF_RES : OFF_MOD + (h * 2 + m) * MOD_STEP; }
constexpr uint32_t OFF_XSEL = OFF_MOD + 8192;
constexpr uint32_t OFF_KVB = OFF_MOD + 2 * MOD_STEP + 8192;
constexpr uint32_t KVB_N = 1056;
constexpr uint32_t OFF_G = OFF_KVB + 4 * KVB_N + 1024;
constexpr uint32_t OFF_PART = OFF_G + 512;
constexpr uint32_t OFF_MISC = OFF_PART + 576;
constexpr uint32_t OFF_BAR = OFF_MISC + 32;
constexpr uint32_t SMEM_BYTES = OFF_BAR + 488;
constexpr uint32_t BAR_FULL = OFF_BAR, BAR_Y = BAR_FULL + 64, BAR_X = BAR_Y + 8, BAR_PEER = BAR_X + 8, BAR_GATE = BAR_PEER + 8, BAR_RT = BAR_GATE + 8,
                   BAR_FIX = BAR_RT,
                   BAR_MFULL = BAR_FIX + 32, BAR_LAND = BAR_FULL,
                   BAR_EMPTY = OFF_BAR + 28 * 8, BAR_OEMPTY = BAR_EMPTY + 64, BAR_RTD = BAR_OEMPTY + 40, BAR_DONE = BAR_RTD + 8,
                   BAR_OWN = BAR_DONE + 8, BAR_PA = BAR_OWN + 8, BAR_PUB = BAR_PA + 8, BAR_MEMPTY = BAR_PUB + 16,
                   BAR_IDX = BAR_MEMPTY + 8,
                   BAR_OFULL = OFF_BAR + 52 * 8;
static_assert(BAR_MFULL + MOD_BUFS0 * 8 <= BAR_EMPTY && BAR_MEMPTY + MOD_BUFS0 * 8 == BAR_OFULL, "barrier groups");
static_assert(SMEM_BYTES <= 232448, "smem");
static_assert(TL == 3 && PRE == 2, "schedule");

constexpr int NB_WG0 = 1, NB_ORDER_AB = 3, NB_ORDER_BO = 4, NB_STG = 5, NB_MODW = 6, NB_KEY = 7, NB_HOLD = 8;

struct Scratch {
  uint4 kv[2][8][3][128];
  float4 y[2][3][128];
  unsigned cnt[32][32];
  unsigned gslot[S_];
  unsigned rslot[8][NCTA];
  unsigned spare[128];
  unsigned block[NCTA];
  uint4 o[16][16][1024];
};
static_assert(offsetof(Scratch, gslot) == NCTA * 56 * 16, "clear size");
__device__ __align__(1024) Scratch g_scratch;

#define PROF(cond, i) do {} while (0)
#define PROF_C(cond, i) do {} while (0)

__device__ __forceinline__ void mbar_init(uint32_t bar, int cnt) { asm volatile("mbarrier.init.shared::cta.b64 [%0], %1;" ::"r"(bar), "r"(cnt)); }
__device__ __forceinline__ void mbar_expect_tx(uint32_t bar, uint32_t bytes) { asm volatile("mbarrier.arrive.expect_tx.shared::cta.b64 _, [%0], %1;" ::"r"(bar), "r"(bytes) : "memory"); }
__device__ __forceinline__ void mbar_arrive(uint32_t bar) { asm volatile("mbarrier.arrive.shared::cta.b64 _, [%0];" ::"r"(bar) : "memory"); }
__device__ __forceinline__ uint32_t peer_addr(uint32_t a) {
  uint32_t r;
  asm volatile("{\n.reg .u32 c;\nmov.u32 c, %%cluster_ctarank;\nxor.b32 c, c, 1;\nmapa.shared::cluster.u32 %0, %1, c;\n}" : "=r"(r) : "r"(a));
  return r;
}
__device__ __forceinline__ void mbar_arrive_peer(uint32_t bar) { asm volatile("mbarrier.arrive.shared::cluster.b64 _, [%0];" ::"r"(bar) : "memory"); }
__device__ __forceinline__ uint32_t mism(uint32_t a, uint32_t b, uint32_t p) {
  uint32_t r; asm("lop3.b32 %0, %1, %2, %3, 0x7E;" : "=r"(r) : "r"(a), "r"(b), "r"(p)); return r;
}
__device__ __forceinline__ bool elect() {
  uint32_t r;
  asm volatile("{\n.reg .pred p;\nelect.sync _|p, 0xffffffff;\nselp.u32 %0, 1, 0, p;\n}" : "=r"(r));
  return r;
}
__device__ __forceinline__ uint32_t fresh_tid() { uint32_t r; asm volatile("mov.u32 %0, %%tid.x;" : "=r"(r)); return r; }
__device__ __forceinline__ void mbar_arrive_warp(uint32_t bar) {
  asm volatile("{\n.reg .pred p;\nelect.sync _|p, 0xffffffff;\n@p mbarrier.arrive.shared::cta.b64 _, [%0];\n}" ::"r"(bar) : "memory");
}
__device__ __forceinline__ void mbar_wait(uint32_t bar, uint32_t parity) {
  asm volatile("{\n.reg .pred p;\nWAIT_L:\nmbarrier.try_wait.parity.shared::cta.b64 p, [%0], %1;\n@p bra DONE_L;\nbra WAIT_L;\nDONE_L:\n}"
               ::"r"(bar), "r"(parity) : "memory");
}
__device__ __forceinline__ uint32_t mbar_try(uint32_t bar, uint32_t parity) {
  uint32_t ok;
  asm volatile("{\n.reg .pred p;\nmbarrier.try_wait.parity.shared::cta.b64 p, [%1], %2;\nselp.u32 %0, 1, 0, p;\n}" : "=r"(ok) : "r"(bar), "r"(parity) : "memory");
  return ok;
}
__device__ __forceinline__ uint32_t mbar_test(uint32_t bar, uint32_t parity) {
  uint32_t ok;
  asm volatile("{\n.reg .pred p;\nmbarrier.test_wait.parity.shared::cta.b64 p, [%1], %2;\nselp.u32 %0, 1, 0, p;\n}" : "=r"(ok) : "r"(bar), "r"(parity) : "memory");
  return ok;
}
constexpr unsigned long long WATCHDOG_NS = 2000000000ull;
__device__ __forceinline__ unsigned long long gtime() { unsigned long long t; asm volatile("mov.u64 %0, %%globaltimer;" : "=l"(t)); return t; }
__device__ __forceinline__ uint32_t clock32() { uint32_t t; asm volatile("mov.u32 %0, %%clock;" : "=r"(t)); return t; }
__device__ __forceinline__ void mbar_wait_bounded(uint32_t bar, uint32_t parity) {
  unsigned long long t0 = 0;
  for (;;) {
    uint32_t ok;
    asm volatile("{\n.reg .pred p;\nmbarrier.try_wait.parity.shared::cta.b64 p, [%1], %2;\nselp.u32 %0, 1, 0, p;\n}" : "=r"(ok) : "r"(bar), "r"(parity) : "memory");
    if (ok) break;
    const unsigned long long t1 = gtime();
    if (t0 == 0) t0 = t1;
    if (t1 - t0 > WATCHDOG_NS) __trap();
  }
}
__device__ __forceinline__ void tma2d(uint32_t dst, const CUtensorMap* m, int c0, int c1, uint32_t bar) {
  asm volatile("cp.async.bulk.tensor.2d.shared::cluster.global.mbarrier::complete_tx::bytes [%0], [%1, {%3, %4}], [%2];"
               ::"r"(dst), "l"(m), "r"(bar), "r"(c0), "r"(c1) : "memory");
}
__device__ __forceinline__ void tma3d(uint32_t dst, const CUtensorMap* m, int c0, int c1, int c2, uint32_t bar) {
  asm volatile("cp.async.bulk.tensor.3d.shared::cluster.global.mbarrier::complete_tx::bytes [%0], [%1, {%3, %4, %5}], [%2];"
               ::"r"(dst), "l"(m), "r"(bar), "r"(c0), "r"(c1), "r"(c2) : "memory");
}
__device__ __forceinline__ void bulk_load(uint32_t dst, const void* src, uint32_t bytes, uint32_t bar) {
  asm volatile("cp.async.bulk.shared::cluster.global.mbarrier::complete_tx::bytes [%0], [%1], %2, [%3];" ::"r"(dst), "l"(src), "r"(bytes), "r"(bar) : "memory");
}
__device__ __forceinline__ void bulk_store(void* dst, uint32_t src, uint32_t bytes) {
  asm volatile("cp.async.bulk.global.shared::cta.bulk_group [%0], [%1], %2;" ::"l"(dst), "r"(src), "r"(bytes) : "memory");
}
__device__ __forceinline__ void st_async4(uint32_t dst, const uint32_t (&v)[4], uint32_t bar) {
  asm volatile("st.async.shared::cluster.mbarrier::complete_tx::bytes.v4.b32 [%0], {%1, %2, %3, %4}, [%5];" ::"r"(dst), "r"(v[0]), "r"(v[1]), "r"(v[2]), "r"(v[3]), "r"(bar) : "memory");
}
__device__ __forceinline__ void bulk_commit() { asm volatile("cp.async.bulk.commit_group;" ::: "memory"); }
__device__ __forceinline__ void bulk_prefetch(const void* p, uint32_t bytes) {
  asm volatile("cp.async.bulk.prefetch.L2.global [%0], %1;" ::"l"(p), "r"(bytes) : "memory");
}
__device__ __forceinline__ void tma2d_store(const CUtensorMap* m, uint32_t src, int c0, int c1) {
  asm volatile("cp.async.bulk.tensor.2d.global.shared::cta.bulk_group [%0, {%2, %3}], [%1];" ::"l"(m), "r"(src), "r"(c0), "r"(c1) : "memory");
}
__device__ __forceinline__ void wg_fence() { asm volatile("wgmma.fence.sync.aligned;" ::: "memory"); }
__device__ __forceinline__ void wg_commit() { asm volatile("wgmma.commit_group.sync.aligned;" ::: "memory"); }
template <int N> __device__ __forceinline__ void wg_wait() { asm volatile("wgmma.wait_group.sync.aligned %0;" ::"n"(N) : "memory"); }
__device__ __forceinline__ void fence_async_smem() { asm volatile("fence.proxy.async.shared::cta;" ::: "memory"); }
__device__ __forceinline__ void fence_async_global() { asm volatile("fence.proxy.async.global;" ::: "memory"); }
__device__ __forceinline__ void fence_release() { asm volatile("fence.release.gpu;" ::: "memory"); }
__device__ __forceinline__ void fence_acquire() { asm volatile("fence.acquire.gpu;" ::: "memory"); }
__device__ __forceinline__ void nb_sync(int id, int n) { asm volatile("bar.sync %0, %1;" ::"r"(id), "r"(n) : "memory"); }
__device__ __forceinline__ void nb_arrive(int id, int n) { asm volatile("bar.arrive %0, %1;" ::"r"(id), "r"(n) : "memory"); }
__device__ __forceinline__ void stsm4(uint32_t addr, uint32_t r0, uint32_t r1, uint32_t r2, uint32_t r3) {
  asm volatile("stmatrix.sync.aligned.m8n8.x4.shared.b16 [%0], {%1, %2, %3, %4};" ::"r"(addr), "r"(r0), "r"(r1), "r"(r2), "r"(r3) : "memory");
}
__device__ __forceinline__ void stsm4t(uint32_t addr, uint32_t r0, uint32_t r1, uint32_t r2, uint32_t r3) {
  asm volatile("stmatrix.sync.aligned.m8n8.x4.trans.shared.b16 [%0], {%1, %2, %3, %4};" ::"r"(addr), "r"(r0), "r"(r1), "r"(r2), "r"(r3) : "memory");
}
__device__ __forceinline__ void st_relaxed4(void* p, const uint32_t (&v)[4]) {
  asm volatile("st.relaxed.gpu.global.v4.u32 [%0], {%1, %2, %3, %4};" ::"l"(p), "r"(v[0]), "r"(v[1]), "r"(v[2]), "r"(v[3]) : "memory");
}
__device__ __forceinline__ void sts128(uint32_t addr, uint32_t a, uint32_t b, uint32_t c, uint32_t d) {
  asm volatile("st.shared.v4.b32 [%0], {%1, %2, %3, %4};" ::"r"(addr), "r"(a), "r"(b), "r"(c), "r"(d) : "memory");
}
__device__ __forceinline__ uint32_t pack2(float lo, float hi) {
  uint32_t r; asm("cvt.rn.bf16x2.f32 %0, %1, %2;" : "=r"(r) : "f"(hi), "f"(lo)); return r;
}
__device__ __forceinline__ float bf_lo(uint32_t v) { return __uint_as_float(v << 16); }
__device__ __forceinline__ float bf_hi(uint32_t v) { return __uint_as_float(v & 0xffff0000u); }
__device__ __forceinline__ float bf_round(float v) { return __bfloat162float(__float2bfloat16_rn(v)); }
__device__ __forceinline__ void ldsm4(uint32_t addr, uint32_t (&r)[4]) {
  asm volatile("ldmatrix.sync.aligned.m8n8.x4.shared.b16 {%0, %1, %2, %3}, [%4];" : "=r"(r[0]), "=r"(r[1]), "=r"(r[2]), "=r"(r[3]) : "r"(addr) : "memory");
}
__device__ __forceinline__ uint4 lds128(uint32_t addr) {
  uint4 v; asm volatile("ld.volatile.shared.v4.u32 {%0, %1, %2, %3}, [%4];" : "=r"(v.x), "=r"(v.y), "=r"(v.z), "=r"(v.w) : "r"(addr) : "memory"); return v;
}
__device__ __forceinline__ uint2 lds64(uint32_t addr) { uint2 v; asm volatile("ld.volatile.shared.v2.u32 {%0, %1}, [%2];" : "=r"(v.x), "=r"(v.y) : "r"(addr) : "memory"); return v; }
__device__ __forceinline__ uint32_t lds32(uint32_t addr) { uint32_t v; asm volatile("ld.volatile.shared.u32 %0, [%1];" : "=r"(v) : "r"(addr) : "memory"); return v; }
__device__ __forceinline__ uint32_t ld_generic(const void* p) { uint32_t v; asm volatile("ld.volatile.u32 %0, [%1];" : "=r"(v) : "l"(p) : "memory"); return v; }
__device__ __forceinline__ void sts32(uint32_t addr, uint32_t v) { asm volatile("st.shared.u32 [%0], %1;" ::"r"(addr), "r"(v) : "memory"); }
__device__ __forceinline__ uint32_t fma_bf2(uint32_t a, uint32_t b, uint32_t c) { uint32_t r; asm("fma.rn.bf16x2 %0, %1, %2, %3;" : "=r"(r) : "r"(a), "r"(b), "r"(c)); return r; }
__device__ __forceinline__ uint32_t mul_bf2(uint32_t a, uint32_t b) { uint32_t r; asm("mul.rn.bf16x2 %0, %1, %2;" : "=r"(r) : "r"(a), "r"(b)); return r; }
__device__ __forceinline__ unsigned ld_relaxed(const unsigned* p) { unsigned v; asm volatile("ld.relaxed.gpu.global.u32 %0, [%1];" : "=r"(v) : "l"(p) : "memory"); return v; }
__device__ __forceinline__ void st_relaxed(unsigned* p, unsigned v) { asm volatile("st.relaxed.gpu.global.u32 [%0], %1;" ::"l"(p), "r"(v) : "memory"); }
__device__ __forceinline__ uint4 ld_relaxed4(const void* p) {
  uint4 v; asm volatile("ld.relaxed.gpu.global.v4.u32 {%0, %1, %2, %3}, [%4];" : "=r"(v.x), "=r"(v.y), "=r"(v.z), "=r"(v.w) : "l"(p) : "memory"); return v;
}
__device__ __forceinline__ float4 ld_relaxed_f4(const void* p) {
  float4 v; asm volatile("ld.relaxed.gpu.global.v4.f32 {%0, %1, %2, %3}, [%4];" : "=f"(v.x), "=f"(v.y), "=f"(v.z), "=f"(v.w) : "l"(p) : "memory"); return v;
}
__device__ __forceinline__ void red_add4(void* p, float a, float b, float c, float d) {
  asm volatile("red.relaxed.gpu.global.add.v4.f32 [%0], {%1, %2, %3, %4};" ::"l"(p), "f"(a), "f"(b), "f"(c), "f"(d) : "memory");
}
__device__ __forceinline__ void red_add_bf(void* p, uint32_t a, uint32_t b, uint32_t c) {
  asm volatile("red.relaxed.gpu.global.add.noftz.v4.bf16x2 [%0], {%1, %2, %3, %4};" ::"l"(p), "r"(a), "r"(b), "r"(c), "r"(0x3F803F80u) : "memory");
}
__device__ __forceinline__ void red_add(unsigned* p, unsigned v) { asm volatile("red.relaxed.gpu.global.add.u32 [%0], %1;" ::"l"(p), "r"(v) : "memory"); }
__device__ __forceinline__ float rcp(float v) { float r; asm("rcp.approx.ftz.f32 %0, %1;" : "=f"(r) : "f"(v)); return r; }
__device__ __forceinline__ float sigmoidf_(float v) { return rcp(1.f + __expf(-v)); }
__device__ __forceinline__ uint32_t phi2(float a, float b, float l2e = 1.4426950408889634f) {
  float ea, eb;
  asm("ex2.approx.ftz.f32 %0, %1;" : "=f"(ea) : "f"(a * l2e));
  asm("ex2.approx.ftz.f32 %0, %1;" : "=f"(eb) : "f"(b * l2e));
  uint32_t t = pack2(a, b), e = pack2(ea, eb), r;
  asm("max.NaN.bf16x2 %0, %0, %1;" : "+r"(t) : "r"(0x35863586u));
  asm("min.bf16x2 %0, %0, %1;" : "+r"(e) : "r"(0x3F803F80u));
  asm("add.rn.bf16x2 %0, %1, %2;" : "=r"(r) : "r"(t), "r"(e));
  return r;
}
__device__ __forceinline__ uint64_t mkdesc(uint32_t addr, uint32_t lbo, uint32_t sbo, uint32_t sw) {
  return (uint64_t)(((addr & 0x3FFFF) >> 4) | ((lbo >> 4) << 16)) | ((uint64_t)((sbo >> 4) | (sw << 30)) << 32);
}

template <int TA, int TB>
__device__ __forceinline__ void mma128(float (&d)[64], uint64_t da, uint64_t db, int sc) {
  asm volatile("{\n.reg .pred p;\nsetp.ne.b32 p, %66, 0;\n"
    "wgmma.mma_async.sync.aligned.m64n128k16.f32.bf16.bf16 "
    "{%0,%1,%2,%3,%4,%5,%6,%7,%8,%9,%10,%11,%12,%13,%14,%15,%16,%17,%18,%19,%20,%21,%22,%23,"
    "%24,%25,%26,%27,%28,%29,%30,%31,%32,%33,%34,%35,%36,%37,%38,%39,%40,%41,%42,%43,%44,%45,%46,%47,"
    "%48,%49,%50,%51,%52,%53,%54,%55,%56,%57,%58,%59,%60,%61,%62,%63}, "
    "%64, %65, p, 1, 1, %67, %68;\n}\n"
    : "+f"(d[0]), "+f"(d[1]), "+f"(d[2]), "+f"(d[3]), "+f"(d[4]), "+f"(d[5]), "+f"(d[6]), "+f"(d[7]),
      "+f"(d[8]), "+f"(d[9]), "+f"(d[10]), "+f"(d[11]), "+f"(d[12]), "+f"(d[13]), "+f"(d[14]), "+f"(d[15]),
      "+f"(d[16]), "+f"(d[17]), "+f"(d[18]), "+f"(d[19]), "+f"(d[20]), "+f"(d[21]), "+f"(d[22]), "+f"(d[23]),
      "+f"(d[24]), "+f"(d[25]), "+f"(d[26]), "+f"(d[27]), "+f"(d[28]), "+f"(d[29]), "+f"(d[30]), "+f"(d[31]),
      "+f"(d[32]), "+f"(d[33]), "+f"(d[34]), "+f"(d[35]), "+f"(d[36]), "+f"(d[37]), "+f"(d[38]), "+f"(d[39]),
      "+f"(d[40]), "+f"(d[41]), "+f"(d[42]), "+f"(d[43]), "+f"(d[44]), "+f"(d[45]), "+f"(d[46]), "+f"(d[47]),
      "+f"(d[48]), "+f"(d[49]), "+f"(d[50]), "+f"(d[51]), "+f"(d[52]), "+f"(d[53]), "+f"(d[54]), "+f"(d[55]),
      "+f"(d[56]), "+f"(d[57]), "+f"(d[58]), "+f"(d[59]), "+f"(d[60]), "+f"(d[61]), "+f"(d[62]), "+f"(d[63])
    : "l"(da), "l"(db), "r"(sc), "n"(TA), "n"(TB));
}

__device__ __forceinline__ void mma_ktv(float (&d)[36], const uint32_t (&a)[4], uint64_t db, int sc) {
  asm volatile("{\n.reg .pred p;\nsetp.ne.b32 p, %41, 0;\n"
    "wgmma.mma_async.sync.aligned.m64n72k16.f32.bf16.bf16 "
    "{%0,%1,%2,%3,%4,%5,%6,%7,%8,%9,%10,%11,%12,%13,%14,%15,%16,%17,%18,%19,%20,%21,%22,%23,"
    "%24,%25,%26,%27,%28,%29,%30,%31,%32,%33,%34,%35}, "
    "{%36,%37,%38,%39}, %40, p, 1, 1, 0;\n}\n"
    : "+f"(d[0]), "+f"(d[1]), "+f"(d[2]), "+f"(d[3]), "+f"(d[4]), "+f"(d[5]), "+f"(d[6]), "+f"(d[7]),
      "+f"(d[8]), "+f"(d[9]), "+f"(d[10]), "+f"(d[11]), "+f"(d[12]), "+f"(d[13]), "+f"(d[14]), "+f"(d[15]),
      "+f"(d[16]), "+f"(d[17]), "+f"(d[18]), "+f"(d[19]), "+f"(d[20]), "+f"(d[21]), "+f"(d[22]), "+f"(d[23]),
      "+f"(d[24]), "+f"(d[25]), "+f"(d[26]), "+f"(d[27]), "+f"(d[28]), "+f"(d[29]), "+f"(d[30]), "+f"(d[31]),
      "+f"(d[32]), "+f"(d[33]), "+f"(d[34]), "+f"(d[35])
    : "r"(a[0]), "r"(a[1]), "r"(a[2]), "r"(a[3]), "l"(db), "r"(sc));
}

__device__ __forceinline__ void mma_qkvz(float (&d)[20], uint64_t da, uint64_t db, int sc) {
  asm volatile("{\n.reg .pred p;\nsetp.ne.b32 p, %22, 0;\n"
    "wgmma.mma_async.sync.aligned.m64n40k16.f32.bf16.bf16 "
    "{%0,%1,%2,%3,%4,%5,%6,%7,%8,%9,%10,%11,%12,%13,%14,%15,%16,%17,%18,%19}, "
    "%20, %21, p, 1, 1, 0, 1;\n}\n"
    : "+f"(d[0]), "+f"(d[1]), "+f"(d[2]), "+f"(d[3]), "+f"(d[4]), "+f"(d[5]), "+f"(d[6]), "+f"(d[7]),
      "+f"(d[8]), "+f"(d[9]), "+f"(d[10]), "+f"(d[11]), "+f"(d[12]), "+f"(d[13]), "+f"(d[14]), "+f"(d[15]),
      "+f"(d[16]), "+f"(d[17]), "+f"(d[18]), "+f"(d[19])
    : "l"(da), "l"(db), "r"(sc));
}

template <int N> __device__ __forceinline__ void pin(float (&d)[N]) {
#pragma unroll
  for (int i = 0; i < N; i++) asm volatile("" : "+f"(d[i])::"memory");
}

struct Params {
  CUtensorMap x, w, xr, gate, up, wo, out, down, xh;
};

__device__ __forceinline__ uint32_t dup_lo(uint32_t v) { uint32_t r; asm("{\n.reg .b16 l, h;\nmov.b32 {l, h}, %1;\nmov.b32 %0, {l, l};\n}" : "=r"(r) : "r"(v)); return r; }
__device__ __forceinline__ uint32_t dup_hi(uint32_t v) { uint32_t r; asm("{\n.reg .b16 l, h;\nmov.b32 {l, h}, %1;\nmov.b32 %0, {h, h};\n}" : "=r"(r) : "r"(v)); return r; }
__device__ __forceinline__ float butterfly8(float (&s)[8], int lane, int o) {
#pragma unroll
  for (int k = 1; k < 8; k <<= 1) {
    const bool up = lane & (o * k);
#pragma unroll
    for (int j = 0; j < 4 / k; j++) s[j] = (up ? s[2 * j + 1] : s[2 * j]) + __shfl_xor_sync(~0u, up ? s[2 * j] : s[2 * j + 1], o * k);
  }
  return s[0];
}
constexpr int OWN = 8, PEER = 9;
static_assert((OA_SLOTS >> OWN * 4 & 15) * SLOT == OFF_V && (OA_SLOTS >> PEER * 4 & 15) * SLOT == OFF_PK, "");
constexpr uint64_t OR_SLOTS = (OA_SLOTS & 0xFFFFFFFFu) | OA_SLOTS >> 40 << 32;
template <class F> __device__ __forceinline__ void verify_tiles(uint32_t sb, Scratch* gs, int tm, int tn, int w, int lane, F between) {
  const uint32_t par = lds32(sb + OFF_MISC + 24), fix = sb + BAR_FIX + w * 8;
  uint64_t slots = OR_SLOTS, full = 0x04321021043210ull;
#pragma unroll 1
  for (int i = 0; i < 14; i++, slots >>= 4, full >>= 4) {
    const uint32_t a = sb + OFF_RING + ((uint32_t)slots & 15) * SLOT + w * 1024, cw = a + lane * 32 + (lane >> 2) * 4;
    if (i == 4) mbar_wait(sb + BAR_EMPTY + 7 * 8, 1);
    if (i == 8) between();
    mbar_wait(sb + BAR_LAND + (i & 7) * 8, i >> 3);
    if (i >> 1 == 4) PROF(w == 0 && lane == 0, 33 + i);
    for (;;) {
      const uint32_t u0 = lds32(cw), u1 = lds32(cw + 4096), u2 = lds32(cw + 8192), u3 = lds32(cw + 12288);
      if (__all_sync(~0u, !(mism(mism(u0, u1, par), mism(u2, u3, par), 0) & 1))) break;
      const uint4* src = gs->o[tm][i < 8 + (tn & 6) ? i : i + 2] + w * 64;
      const uint32_t ph = !mbar_test(fix, 1);
      fence_async_smem();
      __syncwarp();
      if (elect()) {
        mbar_expect_tx(fix, 4096);
#pragma unroll 1
        for (int j = 0; j < 4; j++) bulk_load(a + j * 4096, src + j * 256, 1024, fix);
      }
      mbar_wait(fix, ph);
    }
    mbar_arrive_warp(sb + BAR_OFULL + ((uint32_t)full & 7) * 8);
    if (i == 8) PROF(w == 3 && lane == 0, 28);
  }
}
template <bool BY_SM> struct Tile {
  int sm, tm, tn, mu;
  bool spare;
  __device__ __forceinline__ Tile() {
    if (BY_SM) asm volatile("mov.u32 %0, %%smid;" : "=r"(sm));
    else sm = blockIdx.x + (blockIdx.x >= 120) * 4;
    const int tp = sm >> 1, pr = sm & 1;
    const int v = tp < 32 ? tp : tp < 60 ? (tp * 293 - 928) >> 8 : tp * 8 - 464, g = v & 7, i = v >> 3;
    tm = (v & 6) * 2 + (i & 3); tn = (v & 1) * 4 + (v >> 4 & 2) + pr;
    mu = i == 5 ? 112 : g * 14 + (i - (i > 5)) * 2 + pr;
    spare = (tp | 1) == 61;
  }
};

template <bool BY_SM> __global__ void __cluster_dims__(2, 1, 1) __launch_bounds__(NTHREADS, 1) fused_kernel(const __nv_bfloat16* __restrict__ px, Scratch* gs, const __nv_bfloat16* __restrict__ w_gate,
             const __nv_bfloat16* __restrict__ w_up, const __nv_bfloat16* __restrict__ w_r, const __nv_bfloat16* __restrict__ gate_w, __nv_bfloat16* __restrict__ pout,
             const __grid_constant__ Params p) {
  extern __shared__ __align__(1024) uint8_t smem[];
  const uint32_t sb = __shfl_sync(~0u, (uint32_t)__cvta_generic_to_shared(smem), 0);
  const int tid = threadIdx.x, lane = tid & 31;
  const int warp = __shfl_sync(~0u, tid >> 5, 0), wg = warp >> 2;
  const uint32_t t_start = clock32();
  const Tile<BY_SM> tile;
  const int tm = tile.tm, tn = tile.tn, mu = tile.mu, cta = tm * 8 + tn;
  const uint32_t zero = tile.sm >> 12;
  if (warp == 0) {
#pragma unroll
    for (int s = 0; s < PRE; s++)
      if (elect()) mbar_init(sb + BAR_FULL + s * 8, 1);
    asm volatile("fence.mbarrier_init.release.cluster;" ::: "memory");
    if (!tile.spare) {
#pragma unroll
      for (int s = 0; s < PRE; s++) {
        if (elect()) tma3d(sb + OFF_W1 + s * WQKV_BYTES, &p.w, tn * 64, s * 64, 0, sb + BAR_FULL + s * 8);
        if (elect()) tma2d(sb + OFF_RING + s * SLOT, &p.x, s * 64, tm * 128, sb + BAR_FULL + s * 8);
        PROF(lane == 0, 64 + s);
      }
      if (elect()) {
#pragma unroll
        for (int s = 0; s < PRE; s++) mbar_expect_tx(sb + BAR_FULL + s * 8, SLOT + WQKV_BYTES);
      }
    }
  }
  if (warp) {
    const int wi = warp == 15 ? 0 : warp;
    const int cnt = wi < 7 ? 1 : wi < 13 ? 4 : 5;
#pragma unroll
    for (int i = 0; i < 4; i++)
      if ((i >= PRE || wi) && elect()) mbar_init(sb + OFF_BAR + wi * 32 + i * 8, cnt);
    asm volatile("fence.mbarrier_init.release.cluster;" ::: "memory");
  }
  __syncthreads();
  if (tile.spare) {
    if (warp == 0) {
      const unsigned tag = (ld_relaxed(&gs->spare[tile.sm & 3]) + 1) & 0xFFF;
      const unsigned long long t0 = gtime();
      uint4 r4;
      do {
        __nanosleep(2048);
        if (gtime() - t0 > WATCHDOG_NS) __trap();
        r4 = ld_relaxed4(&gs->rslot[tile.sm & 3][lane * 4]);
      } while (!__all_sync(~0u, (((r4.x ^ tag) | (r4.y ^ tag) | (r4.z ^ tag) | (r4.w ^ tag)) & 0xFFF) == 0));
      if (tid == 0) st_relaxed(&gs->spare[tile.sm & 3], tag);
    }
    return;
  }

  auto patch_row = [&](int pw) {
    const unsigned key = lds32(sb + OFF_MISC + 16);
    const int sel = 0xFFFF - (int)(key & 0xFFFF) - tm * 128;
    if (pw == 0 && sel >= 0 && sel < 128) {
      const unsigned k16 = key >> 16;
      const float rs = bf_round(sigmoidf_(__uint_as_float(((k16 & 0x8000u) ? (k16 & 0x7FFFu) : (~k16 & 0xFFFFu)) << 16)));
      float v[12];
      const float4* yp = gs->y[lane >> 4][0] + tn * 16 + (lane & 15);
      for (;;) {
#pragma unroll
        for (int i = 0; i < 3; i++) {
          const float4 u = ld_relaxed_f4(yp + i * 128);
          v[4 * i] = u.x; v[4 * i + 1] = u.y; v[4 * i + 2] = u.z; v[4 * i + 3] = u.w;
        }
        const float n = v[3] + v[7] + v[11];
        if (__all_sync(~0u, n + __shfl_xor_sync(~0u, n, 16) == 3.f * MOD_CTAS)) break;
        __nanosleep(Y_SLEEP);
      }
#pragma unroll
      for (int i = 0; i < 10; i++) v[i] = bf_round(bf_round(v[i] + __shfl_xor_sync(~0u, v[i], 16)) * rs);
      PROF(lane == 0, 24);
      mbar_wait(sb + BAR_X, 0);
      if (lane < 16) {
        uint4* xp = (uint4*)(smem + res_off(lane >> 3, sel >> 6) + (sel & 63) * 128 + (((lane ^ sel) & 7) << 4));
        const uint4 xv = *xp;
        *xp = make_uint4(pack2(bf_lo(xv.x) + v[0], bf_hi(xv.x) + v[1]), pack2(bf_lo(xv.y) + v[2], bf_hi(xv.y) + v[4]),
                         pack2(bf_lo(xv.z) + v[5], bf_hi(xv.z) + v[6]), pack2(bf_lo(xv.w) + v[8], bf_hi(xv.w) + v[9]));
      }
      __syncwarp();
      mbar_arrive_warp(sb + BAR_Y);
    }
  };
  if (wg == 3) {
    asm volatile("setmaxnreg.dec.sync.aligned.u32 24;");
    if (warp == 12) {
      mbar_wait(sb + BAR_GATE, 0);
      uint64_t slots = OR_SLOTS, deps = 0x8CBA98A9877654ull;
      uint32_t seen;
#pragma unroll 1
      for (int i = 0; i < 14; i++, deps >>= 4, slots >>= 4) {
        const uint32_t slab = i < 8 + (tn & 6) ? i : i + 2;
        if (!(i & 7)) { mbar_wait(sb + BAR_PUB + (i & 8), 0); seen = 0; }
        if (!(seen >> (slab & 7) * 4 & 4))
          while (!((seen = __shfl_sync(~0u, ld_relaxed(gs->cnt[(i & 8) * 2 + tm]), 0)) >> (slab & 7) * 4 & 4)) __nanosleep(B_SLEEP);
        if (i == 8) mbar_wait(sb + BAR_OWN, 0);
        mbar_wait(sb + BAR_EMPTY + ((uint32_t)deps & 15) * 8, (i & 7) < 5);
        if (elect()) bulk_load(sb + OFF_RING + ((uint32_t)slots & 15) * SLOT, gs->o[tm][slab], SLOT, sb + BAR_LAND + (i & 7) * 8);
        if (elect()) mbar_expect_tx(sb + BAR_LAND + (i & 7) * 8, SLOT);
        PROF(lane == 0, 44 + i);
        if (i == 8) PROF(lane == 0, 43);
      }
    } else if (warp == 13) {
#pragma unroll 1
      for (int g = PRE; g < 32; g++) {
        const bool reuse = (g >> 2) == 4;
        const uint32_t s = g & 3, full = sb + BAR_FULL + (g & 7) * 8, c0 = tn * 64 + (g & 16) * 32, c1 = (g < 16 ? g : g - 4 & 15) * 64;
        if (g < 4) while ((int)(clock32() - t_start) < g * ST1) {}
        mbar_wait(sb + BAR_EMPTY + (g + 4 & 7) * 8, (g + 4 >> 3 & 1) ^ 1);
        if (!reuse && elect()) tma2d(sb + OFF_RING + s * SLOT, &p.x, c1, tm * 128, full);
        if (elect()) tma3d(sb + OFF_W1 + s * WQKV_BYTES, &p.w, c0, c1, 0, full);
        if (elect()) mbar_expect_tx(full, reuse ? WQKV_BYTES : SLOT + WQKV_BYTES);
        PROF(lane == 0, 64 + g);
        const uint32_t i = g - RT_G0;
        if (i < 4 && elect()) {
          mbar_expect_tx(sb + BAR_RT + i * 8, i ? 8192 : 8192 + 4096);
          tma2d(sb + OFF_PK + i * 8192 + (i == 3) * 1024, &p.xr, ((i + RT_ROT) & 3) * 256, cta * 16, sb + BAR_RT + i * 8);
          if (i == 0) { bulk_load(sb + OFF_KVB, w_r, 2048, sb + BAR_RT); bulk_load(sb + OFF_KVB + 2048, gate_w, 2048, sb + BAR_RT); }
        }
        const uint32_t c = g - MOD_START;
        if (c == MOD_BUFS) mbar_wait(sb + BAR_RTD, 0);
        if (c < MOD_BUFS0 && mu < MOD_CTAS && elect()) {
          PROF(true, 192 + c);
          const uint32_t mb = c < MOD_BUFS ? c + 2 : c - MOD_BUFS, mfull = sb + BAR_MFULL + mb * 8, mdst = sb + mod_off(mb);
          mbar_expect_tx(mfull, c ? 8192 : 8192 + 2048);
          tma3d(mdst, &p.gate, mu * 32, c * 16, 0, mfull); tma3d(mdst + 4096, &p.up, mu * 32, c * 16, 0, mfull);
        }
        const uint32_t pc = g - PF_MOD;
        if (pc < 16 && elect()) bulk_prefetch((cta & 64 ? w_up : w_gate) + (size_t)(pc * 64 + (cta & 63)) * F_, F_ * 2);
      }
      mbar_arrive_warp(sb + BAR_GATE);
      const uint32_t lowb = (1u << (tn & 6) * 4) - 1;
      uint64_t slabs = (uint64_t)((0xFEDCBA98u & lowb) | (0xFEDCBAu & ~lowb)) << 40 | (uint64_t)(8 + (tn ^ 1)) << 36 | (uint64_t)(8 + tn) << 32 | 0x76543210u;
      uint64_t deps = 0x8CBA98CBA9876554ull, ws = OW_SLOTS;
      uint32_t full = sb + BAR_OFULL, ph = 1;
#pragma unroll 1
      for (int g = 0; g < 16; g++, slabs >>= 4, deps >>= 4, ws >>= 4) {
        mbar_wait(sb + BAR_EMPTY + ((uint32_t)deps & 15) * 8, ph);
        if (elect()) tma3d(sb + OFF_RING + ((uint32_t)ws & 15) * SLOT, &p.wo, 0, ((uint32_t)slabs & 15) * 64, tn * 2, full);
        if (elect()) mbar_expect_tx(full, SLOT);
        PROF(lane == 0, 96 + g);
        if (g >> 1 == OWN / 2 && lane < 4) mbar_arrive(full);
        full += 8;
        if (full == sb + BAR_OFULL + 40) { full -= 40; ph ^= 1; }
      }
    } else if (warp == 14) {
      if (mu < MOD_CTAS) {
        uint32_t full = sb + BAR_MFULL + 16, dst = sb + OFF_MOD, ph = 0;
#pragma unroll 1
        for (int c = MOD_BUFS0; c < 24; c++) {
          mbar_wait(full + (BAR_MEMPTY - BAR_MFULL), ph);
          PROF(lane == 0, 192 + c);
          if (c < 16) {
            if (elect()) { tma3d(dst, &p.gate, mu * 32, c * 16, 0, full); tma3d(dst + 4096, &p.up, mu * 32, c * 16, 0, full); }
          } else if (elect()) tma3d(dst, &p.down, 0, mu * 32 + (c - 16) * 4, 0, full);
          if (elect()) mbar_expect_tx(full, 8192);
          full += 8; dst += MOD_STEP;
          if (full == sb + BAR_MFULL + MOD_BUFS0 * 8) { full -= MOD_BUFS * 8; dst = sb + OFF_MOD; ph ^= 1; }
        }
      }
      if (elect()) {
      mbar_wait(sb + BAR_IDX, 0);
      const bool paired = PAIRED && ld_relaxed(&gs->block[cta ^ 1]) == (blockIdx.x ^ 1);
      if (paired) mbar_expect_tx(sb + BAR_PEER, SLOT);
      mbar_expect_tx(sb + BAR_X, 32768);
      {
        if (mu < MOD_CTAS) {
          mbar_wait(sb + BAR_MEMPTY + 3 * 8, 0);
          mbar_wait(sb + BAR_MEMPTY + 4 * 8, 0);
          mbar_wait(sb + BAR_MEMPTY + 2 * 8, 1);
        } else mbar_wait(sb + BAR_GATE, 0);
#pragma unroll
        for (int i = 0; i < 4; i++) {
          if (i == 3) mbar_wait(sb + BAR_OEMPTY + 3 * 8, 0);
          tma2d(sb + res_off(i >> 1, i & 1), &p.xh, tn * 128 + (i >> 1) * 64, tm * 128 + (i & 1) * 64, sb + BAR_X);
        }
      }
      if (!paired) {
        mbar_wait(sb + BAR_OWN, 0);
        while (!(ld_relaxed(gs->cnt[16 + tm]) & 4u << (tn ^ 1) * 4)) __nanosleep(32);
        fence_acquire();
        fence_async_global();
        const uint32_t par = lds32(sb + OFF_MISC + 24);
        for (uint32_t ph = !mbar_test(sb + BAR_MFULL, 1), bad = 1; bad & 1; ph ^= 1) {
          fence_async_smem();
          mbar_expect_tx(sb + BAR_MFULL, SLOT);
          bulk_load(sb + OFF_PK, gs->o[tm][8 + (tn ^ 1)], SLOT, sb + BAR_MFULL);
          mbar_wait(sb + BAR_MFULL, ph);
          bad = 0;
#pragma unroll 1
          for (int i = 0; i < 512; i++) bad |= lds32(sb + OFF_PK + i * 32 + (i & 28)) ^ par;
        }
        mbar_arrive(sb + BAR_PEER);
      }
      }
    } else {
#pragma unroll 1
      for (int i = 2; i < 9; i++)
        if (elect()) asm volatile("prefetch.tensormap [%0];" ::"l"(&p.x + i) : "memory");
      mbar_wait_bounded(sb + BAR_DONE, 0);
    }
  } else if (wg == 2) {
    asm volatile("setmaxnreg.dec.sync.aligned.u32 40;");
    const int mw = warp & 3;
    if (mw == 0) {
      const unsigned tag = (ld_relaxed(&gs->rslot[tn][cta]) + 1) & 0xFFF;
#pragma unroll
      for (int i = 0; i < 2; i++)
        if (lane < 28) ((float4*)gs)[cta * 56 + i * 28 + lane] = make_float4(0.f, 0.f, 0.f, 0.f);
      if (lane == 29) gs->block[cta] = blockIdx.x;
      fence_release();
      nb_sync(NB_KEY, 160);
      const uint4 k4 = lds128(sb + OFF_MISC);
      if (lane < 8) st_relaxed(&gs->rslot[lane][cta], max(max(k4.x, k4.y), max(k4.z, k4.w)) | tag);
      if (lane < 16) st_relaxed(&gs->gslot[cta * 16 + lane], lds32(sb + OFF_G + lane * 4) | tag);
      PROF(lane == 0, 20);
      uint4 r4;
      do {
        __nanosleep(RT_SLEEP);
        r4 = ld_relaxed4(&gs->rslot[tn][lane * 4]);
      } while (!__all_sync(~0u, (((r4.x ^ tag) | (r4.y ^ tag) | (r4.z ^ tag) | (r4.w ^ tag)) & 0xFFF) == 0));
      const int c0 = 0xFFF0 - lane * 64;
      unsigned key = max(max((r4.x & 0xFFFF0000u) | (c0 + ((r4.x >> 12) & 15)), (r4.y & 0xFFFF0000u) | (c0 - 16 + ((r4.y >> 12) & 15))),
                         max((r4.z & 0xFFFF0000u) | (c0 - 32 + ((r4.z >> 12) & 15)), (r4.w & 0xFFFF0000u) | (c0 - 48 + ((r4.w >> 12) & 15))));
      key = __reduce_max_sync(~0u, key);
      if (elect()) {
        sts32(sb + OFF_MISC + 16, key);
        sts32(sb + OFF_MISC + 24, tag & 1);
        if (mu < MOD_CTAS) {
          const __nv_bfloat16* row = px + (size_t)(0xFFFF - (key & 0xFFFF)) * D_;
          bulk_load(sb + OFF_XSEL, row, 1024, sb + BAR_MFULL + 16);
          bulk_load(sb + OFF_XSEL + MOD_STEP, row + 512, 1024, sb + BAR_MFULL + 16);
        }
      }
      PROF(lane == 0, 21);
      do {
        r4 = ld_relaxed4(&gs->gslot[tm * 128 + lane * 4]);
      } while (!__all_sync(~0u, (((r4.x ^ tag) | (r4.y ^ tag) | (r4.z ^ tag) | (r4.w ^ tag)) & 0xFFF) == 0));
      sts128(sb + OFF_G + lane * 16, r4.x & 0xFFFF0000u, r4.y & 0xFFFF0000u, r4.z & 0xFFFF0000u, r4.w & 0xFFFF0000u);
      fence_acquire();
      __syncwarp();
    }
    PROF(tid == 256, 22);
    if (mu >= MOD_CTAS) {
      mbar_arrive_warp(sb + BAR_IDX);
    } else {
      const uint32_t wp = sb + (mw >> 1) * 4096 + (mw & 1) * 512 + lane * 16;
      uint32_t mp = sb + OFF_XSEL + (mw & 1) * 64 + (lane >> 2) * 8, mc = 128;
      float acc[8] = {0.f, 0.f, 0.f, 0.f, 0.f, 0.f, 0.f, 0.f};
      uint32_t b = 2, ph = 0;
#pragma unroll 1
      for (int c = 0; c < 24; c++) {
        mbar_wait(sb + BAR_MFULL + b * 8, ph);
        PROF_C(tid == 256, 216 + c);
        const uint32_t a = wp + mod_off(b);
        const uint2 m = lds64(mp);
        const uint4 w0 = lds128(a), w1 = lds128(a + 1024), w2 = lds128(a + 2048), w3 = lds128(a + 3072);
        mp += c == 7 ? MOD_STEP - 1024 + 128 : mc;
        const uint32_t m0 = dup_lo(m.x), m1 = dup_hi(m.x), m2 = dup_lo(m.y), m3 = dup_hi(m.y);
        uint4 q = make_uint4(mul_bf2(w0.x, m0), mul_bf2(w0.y, m0), mul_bf2(w0.z, m0), mul_bf2(w0.w, m0));
        q = make_uint4(fma_bf2(w1.x, m1, q.x), fma_bf2(w1.y, m1, q.y), fma_bf2(w1.z, m1, q.z), fma_bf2(w1.w, m1, q.w));
        q = make_uint4(fma_bf2(w2.x, m2, q.x), fma_bf2(w2.y, m2, q.y), fma_bf2(w2.z, m2, q.z), fma_bf2(w2.w, m2, q.w));
        mbar_arrive_warp(sb + BAR_MEMPTY + b * 8 + (w3.x & zero));
        q = make_uint4(fma_bf2(w3.x, m3, q.x), fma_bf2(w3.y, m3, q.y), fma_bf2(w3.z, m3, q.z), fma_bf2(w3.w, m3, q.w));
        if (++b == 5) b = c < 3 ? 0 : 2;
        if (b == 2) ph ^= 1;
        acc[0] += bf_lo(q.x); acc[1] += bf_hi(q.x); acc[2] += bf_lo(q.y); acc[3] += bf_hi(q.y);
        acc[4] += bf_lo(q.z); acc[5] += bf_hi(q.z); acc[6] += bf_lo(q.w); acc[7] += bf_hi(q.w);
        if (c == 15) {
          const uint32_t ft = fresh_tid(), fl = ft & 31;
          sts32(sb + OFF_PART + (ft & 96) * 4 + ((ft & 3) * 8 + (fl >> 2)) * 4, __float_as_uint(butterfly8(acc, fl, 4)));
          nb_sync(NB_MODW, 128);
          const float* part = (const float*)(smem + OFF_PART) + fl;
          const float gp = bf_round(part[0] + part[32]), up = bf_round(part[64] + part[96]);
          *(__nv_bfloat16*)(smem + OFF_PART + 512 + fl * 2) = __float2bfloat16_rn(bf_round(gp * sigmoidf_(gp)) * up);
          __syncwarp();
          mp = sb + OFF_PART + 512; mc = 8;
#pragma unroll
          for (int i = 0; i < 8; i++) acc[i] = 0.f;
          PROF(lane == 0 && mw == 0, 23);
        }
      }
      float4* yacc = gs->y[tn & 1][0] + (fresh_tid() & 127);
      red_add4(yacc, acc[0], acc[1], acc[2], 1.f);
      red_add4(yacc + 128, acc[3], acc[4], acc[5], 1.f);
      red_add4(yacc + 256, acc[6], acc[7], 0.f, 1.f);
      PROF(lane == 0 && mw == 0, 25);
    }
    mbar_wait(sb + BAR_GATE, 0);
    mbar_wait(sb + BAR_IDX, 0);
    verify_tiles(sb, gs, tm, tn, mw, lane, [&]() { patch_row(mw); });
  } else {
    asm volatile("setmaxnreg.inc.sync.aligned.u32 224;");
    const int w = warp & 3, wt = tid & 127;
    const int nb_self = NB_WG0 + wg;
    const uint64_t da0 = mkdesc(sb + OFF_RING, 16, 1024, 1), db0 = mkdesc(sb + OFF_RING, 8192, 1024, 1);

    if (wg == 1) {
      sts128(sb + OFF_ONES - (w >> 1) * 9216 + (w & 1) * 512 + lane * 16, 0x3F803F80u, 0x3F803F80u, 0x3F803F80u, 0x3F803F80u);
      sts32(sb + OFF_MISC + 20, 0x3FB8AA3Bu);
      fence_async_smem();
      float s[8] = {0.f, 0.f, 0.f, 0.f, 0.f, 0.f, 0.f, 0.f};
      uint32_t mask = 0xffff0000u;
#pragma unroll 1
      for (int i = 0; i < 4; i++) {
        const uint32_t u = (i + RT_ROT) & 3;
        mbar_wait(sb + BAR_RT + i * 8, 0);
        const uint4 wr = lds128(sb + OFF_KVB + u * 512 + lane * 16), gw = lds128(sb + OFF_KVB + 2048 + u * 512 + lane * 16);
        uint4 xv[4];
#pragma unroll
        for (int r = 0; r < 4; r++) xv[r] = lds128(sb + OFF_PK + i * 8192 + (i == 3) * 1024 + (w * 4 + r) * 512 + lane * 16);
        const float wf[16] = {bf_lo(wr.x), bf_hi(wr.x), bf_lo(wr.y), bf_hi(wr.y), bf_lo(wr.z), bf_hi(wr.z), bf_lo(wr.w), bf_hi(wr.w),
                              bf_lo(gw.x), bf_hi(gw.x), bf_lo(gw.y), bf_hi(gw.y), bf_lo(gw.z), bf_hi(gw.z), bf_lo(gw.w), bf_hi(gw.w)};
#pragma unroll
        for (int r = 0; r < 4; r++) {
          const uint4 xq = xv[r];
          const float xf[8] = {bf_lo(xq.x), __uint_as_float(xq.x & mask), bf_lo(xq.y), bf_hi(xq.y), bf_lo(xq.z), bf_hi(xq.z), bf_lo(xq.w), bf_hi(xq.w)};
#pragma unroll
          for (int j = 0; j < 8; j++) { s[2 * r] = fmaf(xf[j ^ 1], wf[j ^ 1], s[2 * r]); s[2 * r + 1] = fmaf(xf[j ^ 1], wf[8 + (j ^ 1)], s[2 * r + 1]); }
          mask = ((__float_as_uint(s[2 * r]) | __float_as_uint(s[2 * r + 1])) & zero) | 0xffff0000u;
        }
      }
      mbar_arrive_warp(sb + BAR_RTD + (__float_as_uint(s[6]) & zero));
      float v = butterfly8(s, lane, 1);
      PROF_C(wt == 0 && v != 12345.f, 19);
      v += __shfl_xor_sync(~0u, v, 8);
      v = bf_round(v + __shfl_xor_sync(~0u, v, 16));
      const unsigned rb = __float_as_uint(v) >> 16, row = w * 4 + ((lane & 7) >> 1);
      unsigned key = (lane & 1) ? 0u : ((((rb & 0x8000u) ? (~rb & 0xFFFFu) : (rb | 0x8000u)) << 16) | ((15 - row) << 12));
      key = __reduce_max_sync(~0u, key);
      if (lane == 0) sts32(sb + OFF_MISC + w * 4, key);
      if (lane < 8 && (lane & 1)) sts32(sb + OFF_G + row * 4, __float_as_uint(bf_round(sigmoidf_(v))));
      nb_arrive(NB_KEY, 160);
      nb_sync(NB_ORDER_AB, 256);
    }
    uint4* const kvacc = &gs->kv[wg][tn][0][wt];
    float aq[64];
    uint32_t su[9];
    {
      float ak[64], av[64], c[36];
      uint32_t pk[8][4];
      PROF_C(wt == 0, 1 + wg * 8);
#pragma unroll 1
      for (int g = 0; g < 16; g++) {
        const uint64_t dx = da0 + (g & 3) * (SLOT >> 4), dw = da0 + ((OFF_W1 >> 4) + (g & 3) * (WQKV_BYTES >> 4));
        mbar_wait(sb + BAR_FULL + (g & 7) * 8, g >> 3);
        if (g == 0) PROF_C(wt == 0, 2 + wg * 8);
        wg_fence();
#pragma unroll
        for (int kk = 0; kk < 4; kk++) mma128<1, 0>(ak, dw + (512 + kk * 128), dx + kk * 2, kk ? 1 : g);
        wg_commit();
        wg_wait<1>();
        if (g) mbar_arrive_warp(sb + BAR_EMPTY + (g - 1 & 7) * 8);
        wg_fence();
#pragma unroll
        for (int kk = 0; kk < 4; kk++) mma128<1, 0>(av, dw + (1024 + kk * 128), dx + kk * 2, kk ? 1 : g);
        wg_commit();
#pragma unroll
        for (int kk = 0; kk < 4; kk++) mma128<1, 0>(aq, dw + kk * 128, dx + kk * 2, kk ? 1 : g);
        wg_commit();
      }
      if (wg == 0) nb_arrive(NB_ORDER_AB, 256);
      mbar_wait(sb + BAR_RTD, 0);
      if (wg == 1) nb_sync(NB_STG, 256);
      wg_wait<2>();
      pin(ak);
      PROF_C(wt == 0, 3 + wg * 8);
      const uint32_t va = sb + OFF_V + (w * 16 + (lane & 15)) * 128;
      uint32_t lk[8];
#pragma unroll
      for (int u = 0; u < KL; u++) lk[u] = 0x3FB8AA3Bu;
#pragma unroll
      for (int u = 0; u < 8; u++) {
#pragma unroll
        for (int i = 0; i < 4; i++) pk[u][i] = phi2(ak[8 * u + 2 * i], ak[8 * u + 2 * i + 1], __uint_as_float(lk[u]));
        if (u == VK) { wg_wait<1>(); pin(av); }
        if (u == MM) { wg_wait<0>(); mbar_arrive_warp(sb + BAR_EMPTY + 7 * 8); }
        const uint32_t z = mism(pk[u][0], pk[u][1], 0) | mism(pk[u][2], pk[u][3], 0);
#pragma unroll
        for (int t = u < VK ? 8 : (u - VK) * 8 / (8 - VK); t < (u - VK + 1) * 8 / (8 - VK); t++) {
          const float* v = &av[8 * t];
          stsm4(va + (t >> 2) * 9216 + ((((lane >> 4) + 2 * (t & 3)) ^ (lane & 7)) << 4) + (z & zero), pack2(v[0], v[1]), pack2(v[2], v[3]), pack2(v[4], v[5]), pack2(v[6], v[7]));
        }
        if (u + KL < 8) lk[u + KL] = lds32(sb + OFF_MISC + 20 + (u < VK ? z & zero : 0));
      }
      fence_async_smem();
      nb_sync(nb_self, 128);
      PROF_C(wt == 0, 8 + wg * 8);
      const uint64_t dv = mkdesc(sb + OFF_V, 16, 1024, 1);
      wg_fence();
#pragma unroll
      for (int kk = 0; kk < 8; kk++) mma_ktv(c, pk[kk], dv + ((kk >> 2) * 576 + (kk & 3) * 2), kk ? 1 : 0);
      wg_commit();
      if (wg == 1) nb_arrive(NB_ORDER_BO, 256);
      mbar_wait(sb + BAR_IDX, 0);
      wg_wait<0>();
      pin(c); pin(aq);
      PROF_C(wt == 0, 4 + wg * 8);
#pragma unroll
      for (int i = 0; i < 8; i++) {
        const int j = (i & 3) * 4 + (i >> 2) * 2;
        su[i] = w >= 2 ? pack2(c[16 + j], c[17 + j]) : pack2(c[j], c[j + 1]);
      }
      su[8] = pack2(c[32], c[34]);
#pragma unroll
      for (int u = 0; u < 3; u++)
        if (u < R0 || wg) red_add_bf(kvacc + u * 128, su[3 * u], su[3 * u + 1], su[3 * u + 2]);
    }
    const uint32_t par = lds32(sb + OFF_MISC + 24);
    {
      const bool paired = PAIRED && ld_relaxed(&gs->block[cta ^ 1]) == (blockIdx.x ^ 1);
      uint4 kv[3];
      int tries = wg ? 0 : RETRY + 1;
      const uint8_t* gl = smem + OFF_MISC + 20;
      asm volatile("" : "+l"(gl));
      const uint32_t l2e = ld_generic(gl);
    auto stage_kv = [&]() {
      const uint32_t kb = sb + OFF_KVB + w * 256, ka = kb + (lane & 3) * KVB_N + (lane >> 2) * 16;
      sts128(ka, kv[0].x, kv[0].y, kv[0].z, kv[1].x);
      sts128(ka + 128, kv[1].y, kv[1].z, kv[2].x, kv[2].y);
      sts32(kb + 4 * KVB_N + lane * 4, dup_lo(kv[2].z));
      sts32(kb + 4 * KVB_N + 128 + lane * 4, dup_hi(kv[2].z));
      return __all_sync(~0u, (kv[0].w & kv[1].w & kv[2].w) == 0x41804180u && (kv[0].w | kv[1].w | kv[2].w) == 0x41804180u);
    };
      const uint32_t qa = sb + OFF_PK + ((lane >> 4) * 8 + (lane & 7)) * 128 + (((2 * w + ((lane >> 3) & 1)) ^ (lane & 7)) << 4);
      uint32_t lq[8];
#pragma unroll
      for (int u = 0; u < QA; u++) lq[u] = l2e;
#pragma unroll
      for (int u = 0; u < 8; u++) {
        uint32_t r[4];
#pragma unroll
        for (int i = 0; i < 4; i++) r[i] = phi2(aq[8 * u + 2 * i], aq[8 * u + 2 * i + 1], __uint_as_float(lq[u]));
        stsm4t(qa + u * 2048, r[0], r[1], r[2], r[3]);
        if (u + 1 == KF && wg) {
          const uint4* src = kvacc + (r[3] & zero);
#pragma unroll
          for (int i = 0; i < 3; i++) kv[i] = ld_relaxed4(src + i * 128);
        }
        const int ru = u / RS + R0;
        if (u % RS == RS - 1 && ru < 3 && !wg) red_add_bf(kvacc + ru * 128, su[3 * ru], su[3 * ru + 1], su[3 * ru + 2]);
        if (u + QA < 8) lq[u + QA] = lds32(sb + OFF_MISC + 20);
      }
      PROF_C(wt == 0, 34 + wg * 2);
      bool have = wg && stage_kv();
      for (; !have; tries++) {
        if (tries > RETRY)
          while (ld_relaxed((const unsigned*)&(kvacc - lane)[256 + 31].w) != 0x41804180u) __nanosleep(wg ? KV_SLEEP : KV_SLEEP_A);
#pragma unroll
        for (int i = 0; i < 3; i++) kv[i] = ld_relaxed4(kvacc + i * 128);
        have = stage_kv();
      }
      PROF_C(wt == 0, 5 + wg * 8);
      fence_async_smem();
      nb_sync(nb_self, 128);
      float o[2][2][20];
      const uint64_t dq = mkdesc(sb + OFF_PK, 16, 1024, 1), dz = mkdesc(sb + OFF_KVB, 128, KVB_N, 0);
      wg_fence();
#pragma unroll
      for (int m = 0; m < 2; m++) {
#pragma unroll
        for (int h = 0; h < 2; h++)
#pragma unroll
          for (int kk = 0; kk < 2; kk++) mma_qkvz(o[m][h], dq + (m * 512 + h * 4 + kk * 2), dz + (h * 32 + kk * 16), kk);
        wg_commit();
      }
      if (wg && elect()) red_add(gs->cnt[16 + tm], 1u << tn * 4);
      uint32_t tag[2][4];
#pragma unroll
      for (int i = 0; i < 8; i++) tag[i >> 2][i & 3] = (lane >> 3) == (i & 3) && ((lane ^ (lane >> 3)) & 1) == (i >> 2);
      uint32_t gr[8];
      const uint8_t* ga = smem + OFF_G + (w * 16 + (lane >> 2)) * 4;
      asm volatile("" : "+l"(ga));
#pragma unroll
      for (int i = 0; i < OA; i++) gr[i] = ld_generic(ga + (i >> 2) * 256 + (i & 1) * 32);
      const uint32_t oo = w * 1024 + (lane >> 2) * 64 + (((lane ^ (lane >> 3)) & 3) << 4);
      uint8_t* const og = (uint8_t*)gs->o[tm][wg * 8 + tn] + oo;
      uint32_t ob[8][4];
#pragma unroll
      for (int m = 0; m < 2; m++) {
        if (m == 0) wg_wait<1>(); else wg_wait<0>();
        pin(o[m][0]); pin(o[m][1]);
        if (m && wg) mbar_arrive_warp(sb + BAR_PUB + 8);
        if (m && !wg) nb_arrive(NB_STG, 256);
        if (m && wg) nb_arrive(NB_HOLD, 256);
        if (m && wg && paired && elect()) mbar_arrive_peer(peer_addr(sb + BAR_PA));
        if (m == 0) PROF_C(wt == 0, 6 + wg * 8);
#pragma unroll
        for (int u = 0; u < 4; u++) {
          const int h = u >> 1, i = u & 1;
          const float* on = o[m][h];
          const float sc = __uint_as_float(gr[m * 4 + u]) * rcp(on[16 + 2 * i] + 1e-6f);
          const uint32_t sc2 = pack2(sc, sc);
#pragma unroll
          for (int j = 0; j < 4; j++) {
            const uint32_t v = mul_bf2(pack2(on[4 * j + 2 * i], on[4 * j + 2 * i + 1]), sc2);
            asm("lop3.b32 %0, %1, %2, %3, 0xB8;" : "=r"(ob[m * 4 + u][j]) : "r"(v), "r"(tag[i][j]), "r"(par));
          }
          st_relaxed4(og + (h * 8192 + m * 4096 + i * 512), ob[m * 4 + u]);
          if (wg) sts128(sb + OFF_V + oo + (h * 8192 + m * 4096 + i * 512), ob[m * 4 + u][0], ob[m * 4 + u][1], ob[m * 4 + u][2], ob[m * 4 + u][3]);
          const int n = m * 4 + u + OA;
          if (n < 8) gr[n] = ld_generic(ga + (n >> 2) * 256 + (n & 1) * 32);
        }
      }
      if (!wg) {
        if (elect()) red_add(gs->cnt[tm], 1u << tn * 4);
        mbar_arrive_warp(sb + BAR_PUB);
      }
      PROF(wt == 0, 17 + wg);
      if (wg) {
        fence_async_smem();
        __syncwarp();
        mbar_arrive_warp(sb + BAR_OWN);
        PROF(wt == 0, 15);
        if (paired) {
          const uint32_t pb = peer_addr(sb);
          mbar_wait(sb + BAR_PA, 0);
#pragma unroll
          for (int u = 0, z = 0; u < 8; u++) {
            if (u) z = lds32(sb + OFF_ONES) & zero;
            st_async4(pb + OFF_PK + oo + ((u >> 1 & 1) * 8192 + (u >> 2) * 4096 + (u & 1) * 512) + z, ob[u], pb + BAR_PEER);
          }
        }
      }
    }
    if (wg == 0) {
      float acc[2][64];
      nb_sync(NB_ORDER_BO, 256);
      PROF_C(wt == 0, 26);
      uint32_t xr[2][8][4], q[2][2];
      const uint32_t ta = sb + (uint32_t)(w * 16 + (lane & 15)) * 128;
      const uint64_t do0 = mkdesc(sb + OFF_RING, 16, 512, 2);
      uint64_t xs = OA_SLOTS, ws = OW_SLOTS;
#pragma unroll 1
      for (int g = 0; g < 13 - TL; g++, xs >>= 4, ws >>= 4) {
        const uint32_t r = g * 52 >> 8, s = g - r * 5;
        const uint64_t da = do0 + ((uint32_t)xs & 15) * (SLOT >> 4), db = db0 + ((uint32_t)ws & 15) * (SLOT >> 4);
        if (g == OWN) mbar_wait(sb + BAR_OWN, 0);
        if (g == PEER) { PROF(wt == 0, 39); mbar_wait(sb + BAR_PEER, 0); PROF(wt == 0, 40); fence_async_smem(); }
        if (g == HOLD) nb_sync(NB_HOLD, 256);
        mbar_wait(sb + BAR_OFULL + s * 8, r & 1);
        wg_fence();
#pragma unroll
        for (int kk = 0; kk < 4; kk++)
#pragma unroll
          for (int m = 0; m < 2; m++) mma128<0, 1>(acc[m], da + (m * 256 + (kk >> 1) * 512 + (kk & 1) * 2), db + kk * 128, kk ? 1 : g);
        wg_commit();
        wg_wait<1>();
        if (g) mbar_arrive_warp(sb + BAR_OEMPTY + (s ? s - 1 : 4) * 8);
      }
      PROF(wt == 0, 29);
      mbar_wait(sb + BAR_X, 0);
      PROF(wt == 0, 30);
      const int selw = ((0xFFFF - (int)(lds32(sb + OFF_MISC + 16) & 0xFFFF)) >> 4) - tm * 8 - w;
#pragma unroll
      for (int u = 0; u < 4; u++) {
        const int m = u >> 1, g = 13 - TL + u;
        const float g1 = 1.f - __uint_as_float(lds32(sb + OFF_G + (m * 64 + w * 16 + (u & 1) * 8 + (lane >> 2)) * 4));
        q[m][u & 1] = pack2(g1, g1);
#pragma unroll
        for (int j = 0; j < 4; j++) ldsm4(ta + res_off(u & 1, m) + ((((lane >> 4) + 2 * j) ^ (lane & 7)) << 4), xr[m][(u & 1) * 4 + j]);
        if (u == 3) break;
        mbar_wait(sb + BAR_OFULL + g % 5 * 8, g / 5 & 1);
        wg_fence();
#pragma unroll
        for (int kk = 0; kk < 4; kk++)
#pragma unroll
          for (int mm = 0; mm < 2; mm++)
            mma128<0, 1>(acc[mm], do0 + ((OA_SLOTS >> g * 4 & 15) * (SLOT >> 4) + mm * 256 + (kk >> 1) * 512 + (kk & 1) * 2), db0 + ((OW_SLOTS >> g * 4 & 15) * (SLOT >> 4) + kk * 128), 1);
        wg_commit();
        wg_wait<1>();
        if (g <= 11) mbar_arrive_warp(sb + BAR_OEMPTY + (g + 4) % 5 * 8);
      }
#pragma unroll
      for (int m = 0; m < 2; m++) {
#pragma unroll
        for (int g = 16 - TL; g < 16; g++) {
          if (m == 0) { mbar_wait(sb + BAR_OFULL + g % 5 * 8, g / 5 & 1); wg_fence(); }
#pragma unroll
          for (int kk = 0; kk < 4; kk++)
            mma128<0, 1>(acc[m], do0 + ((OA_SLOTS >> g * 4 & 15) * (SLOT >> 4) + m * 256 + (kk >> 1) * 512 + (kk & 1) * 2), db0 + ((OW_SLOTS >> g * 4 & 15) * (SLOT >> 4) + kk * 128), 1);
        }
        wg_commit();
      }
      mbar_arrive_warp(sb + BAR_DONE);
      const uint32_t tb = sb + w * 2048 + (lane >> 3) * 128 + (((lane ^ (lane >> 3)) & 7) << 4), tx = lane & 4 ? 64 : -64;
      uint8_t* og = (uint8_t*)pout + (size_t)(tm * 128 + w * 16 + (lane >> 3)) * 2048 + tn * 256 + (lane & 7) * 16;
      asm volatile("" : "+l"(og)::"memory");
#pragma unroll
      for (int m = 0; m < 2; m++) {
        if (selw == 4 * m) {
          mbar_wait(sb + BAR_Y, 0);
#pragma unroll
          for (int j = 0; j < 8; j++) ldsm4(ta + res_off(j >> 2, m) + ((((lane >> 4) + 2 * (j & 3)) ^ (lane & 7)) << 4), xr[m][j]);
        }
        if (m == 0) wg_wait<1>(); else wg_wait<0>();
        if (m) PROF(wt == 0, 31);
#pragma unroll
        for (int h = 0; h < 2; h++) {
#pragma unroll
          for (int j = 4 * h; j < 4 * h + 4; j++) {
            const float* v = &acc[m][8 * j];
            stsm4(ta + res_off(h, m) + ((((lane >> 4) + 2 * (j & 3)) ^ (lane & 7)) << 4),
                  fma_bf2(xr[m][j][0], q[m][0], pack2(v[0], v[1])), fma_bf2(xr[m][j][1], q[m][1], pack2(v[2], v[3])),
                  fma_bf2(xr[m][j][2], q[m][0], pack2(v[4], v[5])), fma_bf2(xr[m][j][3], q[m][1], pack2(v[6], v[7])));
          }
          if (m) {
            __syncwarp();
            uint4 t[4];
#pragma unroll
            for (int j = 0; j < 4; j++) t[j] = lds128(tb + res_off(h, m) + j * 512 - (j & 1) * tx);
#pragma unroll
            for (int j = 0; j < 4; j++) *(uint4*)(og + (m * 64 + j * 4) * 2048 + h * 128) = t[j];
          } else {
            fence_async_smem();
            __syncwarp();
            if (elect()) tma2d_store(&p.out, sb + res_off(h, m) + w * 2048, tn * 128 + h * 64, tm * 128 + m * 64 + w * 16);
          }
          if (!m && h && elect()) bulk_commit();
          if (m && h && elect()) asm volatile("cp.async.bulk.wait_group.read 0;" ::: "memory");
        }
        if (!m) PROF(wt == 0, 33);
      }
      PROF(wt == 0, 32);
    }
  }
}

typedef CUresult (*EncodeFn)(CUtensorMap*, CUtensorMapDataType, cuuint32_t, void*, const cuuint64_t*, const cuuint64_t*, const cuuint32_t*,
                             const cuuint32_t*, CUtensorMapInterleave, CUtensorMapSwizzle, CUtensorMapL2promotion, CUtensorMapFloatOOBfill);

void encode(EncodeFn fn, CUtensorMap* m, const void* ptr, int rank, const cuuint64_t* dims, const cuuint64_t* strides, const cuuint32_t* box,
            CUtensorMapSwizzle sw, CUtensorMapDataType dt = CU_TENSOR_MAP_DATA_TYPE_BFLOAT16) {
  const cuuint32_t es[3] = {1, 1, 1};
  fn(m, dt, rank, const_cast<void*>(ptr), dims, strides, box, es, CU_TENSOR_MAP_INTERLEAVE_NONE, sw,
     CU_TENSOR_MAP_L2_PROMOTION_L2_128B, CU_TENSOR_MAP_FLOAT_OOB_FILL_NONE);
}

}

extern "C" void kernel_launch(void* const* d_in, const int* in_sizes, int n_in, void* d_out, int out_size) {
  (void)in_sizes; (void)n_in; (void)out_size;
  EncodeFn fn = nullptr;
  cudaDriverEntryPointQueryResult qr;
  cudaGetDriverEntryPoint("cuTensorMapEncodeTiled", (void**)&fn, cudaEnableDefault, &qr);

  Params p;
  {
    const cuuint64_t dims[2] = {D_, S_}, str[1] = {D_ * 2};
    const cuuint32_t box[2] = {64, 128}, box_st[2] = {64, 16}, box_r[2] = {256, 16}, box_h[2] = {64, 64};
    encode(fn, &p.xh, d_in[0], 2, dims, str, box_h, CU_TENSOR_MAP_SWIZZLE_128B);
    encode(fn, &p.xr, d_in[0], 2, dims, str, box_r, CU_TENSOR_MAP_SWIZZLE_NONE);
    encode(fn, &p.x, d_in[0], 2, dims, str, box, CU_TENSOR_MAP_SWIZZLE_128B);
    encode(fn, &p.out, d_out, 2, dims, str, box_st, CU_TENSOR_MAP_SWIZZLE_128B);
  }
  {
    const cuuint64_t dims[3] = {D_, D_, 3}, str[2] = {3 * D_ * 2, D_ * 2};
    const cuuint32_t box[3] = {64, 64, 3};
    encode(fn, &p.w, d_in[1], 3, dims, str, box, CU_TENSOR_MAP_SWIZZLE_128B);
  }
  {
    const cuuint64_t dims[3] = {64, D_, D_ / 64}, str[2] = {D_ * 2, 128};
    const cuuint32_t box[3] = {64, 64, 2};
    encode(fn, &p.wo, d_in[2], 3, dims, str, box, CU_TENSOR_MAP_SWIZZLE_128B);
  }
  {
    const cuuint64_t dims[3] = {F_, D_ / 4, 4}, str[2] = {F_ * 8, F_ * 2};
    const cuuint32_t box[3] = {32, 16, 4};
    encode(fn, &p.gate, d_in[5], 3, dims, str, box, CU_TENSOR_MAP_SWIZZLE_NONE);
    encode(fn, &p.up, d_in[6], 3, dims, str, box, CU_TENSOR_MAP_SWIZZLE_NONE);
  }
  {
    const cuuint64_t dims[3] = {D_ / 4, F_, 2}, str[2] = {D_ * 2, D_};
    const cuuint32_t box[3] = {256, 4, 2};
    encode(fn, &p.down, d_in[7], 3, dims, str, box, CU_TENSOR_MAP_SWIZZLE_NONE, CU_TENSOR_MAP_DATA_TYPE_UINT32);
  }
  void* gs = nullptr;
  cudaGetSymbolAddress(&gs, g_scratch);
  typedef const __nv_bfloat16* bp;
  int dev = 0, sms = 0;
  cudaGetDevice(&dev);
  cudaDeviceGetAttribute(&sms, cudaDevAttrMultiProcessorCount, dev);
  const bool by_sm = BYSM && sms == NGRID;
  const auto kernel = by_sm ? fused_kernel<true> : fused_kernel<false>;
  cudaFuncSetAttribute(kernel, cudaFuncAttributeMaxDynamicSharedMemorySize, SMEM_BYTES);
  kernel<<<by_sm ? NGRID : NCTA, NTHREADS, SMEM_BYTES, cudaStreamPerThread>>>((bp)d_in[0], (Scratch*)gs, (bp)d_in[5], (bp)d_in[6], (bp)d_in[4], (bp)d_in[8], (__nv_bfloat16*)d_out, p);
}
```

```cpp
#include <cuda_runtime.h>
#include <cuda.h>
#include <cuda_bf16.h>
#include <stdint.h>
#include <stddef.h>

namespace {

constexpr int S_ = 2048, D_ = 1024, F_ = 3584;
constexpr int NCTA = 128, NGRID = 132, NTHREADS = 512;
#define NOMOD 0
constexpr int MOD_CTAS = NOMOD ? 0 : F_ / 32;

#define PRE 2
#define ST1 800
#define RT_G0 2
#define RT_ROT 1
#define RT_SLEEP 500
#define PF_MOD 8
#define PF_W 5
#define MOD_START 10
#define MM 3
#define HOLD 5
#define KF 6
#define QA 3
#define R0 1
#define OA 3
#define Y_SLEEP 200
#define VK 1
#define KL 3
#define RS 2
#define RETRY 1
#define KV_SLEEP_A 64
#define KV_SLEEP 50
#define TL 3
#define B_SLEEP 32
#define PAIRED 1
#define BYSM 1

constexpr uint32_t SLOT = 16384, WQKV_BYTES = 24576;
constexpr int MOD_BUFS = 3, MOD_BUFS0 = MOD_BUFS + 2;
static_assert(MOD_START + MOD_BUFS0 <= 16, "first FFN round is requested during wave A");
constexpr uint32_t OFF_RING = 0, OFF_W1 = 4 * SLOT;
constexpr uint64_t OA_SLOTS = 0x0AB210AB21098210ull, OW_SLOTS = 0x4376543765437654ull;
constexpr uint32_t OFF_RES = OFF_RING + 8 * SLOT;
constexpr uint32_t OFF_PK = 10 * SLOT;
constexpr uint32_t OFF_V = 11 * SLOT;
constexpr uint32_t OFF_ONES = OFF_V + 9216 + 8192;
constexpr uint32_t MOD_STEP = 9216, OFF_MOD = OFF_V + 2 * MOD_STEP;
constexpr __host__ __device__ uint32_t mod_off(uint32_t b) { return b < 2 ? OFF_PK + b * 8192 : OFF_V + b * MOD_STEP; }
constexpr __host__ __device__ uint32_t res_off(int h, int m) { return h & m ? OFF_RES : OFF_MOD + (h * 2 + m) * MOD_STEP; }
constexpr uint32_t OFF_XSEL = OFF_MOD + 8192;
constexpr uint32_t OFF_KVB = OFF_MOD + 2 * MOD_STEP + 8192;
constexpr uint32_t KVB_N = 1056;
constexpr uint32_t OFF_G = OFF_KVB + 4 * KVB_N + 1024;
constexpr uint32_t OFF_PART = OFF_G + 512;
constexpr uint32_t OFF_MISC = OFF_PART + 576;
constexpr uint32_t OFF_BAR = OFF_MISC + 32;
constexpr uint32_t SMEM_BYTES = OFF_BAR + 480;
constexpr uint32_t BAR_FULL = OFF_BAR, BAR_Y = BAR_FULL + 64, BAR_X = BAR_Y + 8, BAR_PEER = BAR_X + 8, BAR_GATE = BAR_PEER + 8, BAR_RT = BAR_GATE + 8,
                   BAR_FIX = BAR_RT,
                   BAR_MFULL = BAR_FIX + 32, BAR_LAND = BAR_FULL,
                   BAR_EMPTY = OFF_BAR + 28 * 8, BAR_OEMPTY = BAR_EMPTY + 64, BAR_RTD = BAR_OEMPTY + 40, BAR_DONE = BAR_RTD + 8,
                   BAR_OWN = BAR_DONE + 8, BAR_PA = BAR_OWN + 8, BAR_PUB = BAR_PA + 8, BAR_MEMPTY = BAR_PUB + 16,
                   BAR_IDX = BAR_MEMPTY + 8,
                   BAR_OFULL = OFF_BAR + 52 * 8;
static_assert(BAR_MFULL + MOD_BUFS0 * 8 <= BAR_EMPTY && BAR_MEMPTY + MOD_BUFS0 * 8 == BAR_OFULL, "barrier groups");
static_assert(SMEM_BYTES <= 232448, "smem");
static_assert(TL == 3 && PRE == 2, "schedule");

constexpr int NB_WG0 = 1, NB_ORDER_AB = 3, NB_ORDER_BO = 4, NB_STG = 5, NB_MODW = 6, NB_KEY = 7, NB_HOLD = 8;

struct Scratch {
  uint4 kv[2][8][3][128];
  float4 y[2][3][128];
  unsigned cnt[32][32];
  unsigned gslot[S_];
  unsigned rslot[8][NCTA];
  unsigned spare[128];
  unsigned block[NCTA];
  uint4 o[16][16][1024];
};
static_assert(offsetof(Scratch, gslot) == NCTA * 56 * 16, "clear size");
__device__ __align__(1024) Scratch g_scratch;

#define PROF(cond, i) do {} while (0)
#define PROF_C(cond, i) do {} while (0)

__device__ __forceinline__ void mbar_init(uint32_t bar, int cnt) { asm volatile("mbarrier.init.shared::cta.b64 [%0], %1;" ::"r"(bar), "r"(cnt)); }
__device__ __forceinline__ void mbar_expect_tx(uint32_t bar, uint32_t bytes) { asm volatile("mbarrier.arrive.expect_tx.shared::cta.b64 _, [%0], %1;" ::"r"(bar), "r"(bytes) : "memory"); }
__device__ __forceinline__ void mbar_arrive(uint32_t bar) { asm volatile("mbarrier.arrive.shared::cta.b64 _, [%0];" ::"r"(bar) : "memory"); }
__device__ __forceinline__ uint32_t peer_addr(uint32_t a) {
  uint32_t r;
  asm volatile("{\n.reg .u32 c;\nmov.u32 c, %%cluster_ctarank;\nxor.b32 c, c, 1;\nmapa.shared::cluster.u32 %0, %1, c;\n}" : "=r"(r) : "r"(a));
  return r;
}
__device__ __forceinline__ void mbar_arrive_peer(uint32_t bar) { asm volatile("mbarrier.arrive.shared::cluster.b64 _, [%0];" ::"r"(bar) : "memory"); }
__device__ __forceinline__ uint32_t mism(uint32_t a, uint32_t b, uint32_t p) {
  uint32_t r; asm("lop3.b32 %0, %1, %2, %3, 0x7E;" : "=r"(r) : "r"(a), "r"(b), "r"(p)); return r;
}
__device__ __forceinline__ bool elect() {
  uint32_t r;
  asm volatile("{\n.reg .pred p;\nelect.sync _|p, 0xffffffff;\nselp.u32 %0, 1, 0, p;\n}" : "=r"(r));
  return r;
}
__device__ __forceinline__ uint32_t fresh_tid() { uint32_t r; asm volatile("mov.u32 %0, %%tid.x;" : "=r"(r)); return r; }
__device__ __forceinline__ void mbar_arrive_warp(uint32_t bar) {
  asm volatile("{\n.reg .pred p;\nelect.sync _|p, 0xffffffff;\n@p mbarrier.arrive.shared::cta.b64 _, [%0];\n}" ::"r"(bar) : "memory");
}
__device__ __forceinline__ void mbar_wait(uint32_t bar, uint32_t parity) {
  asm volatile("{\n.reg .pred p;\nWAIT_L:\nmbarrier.try_wait.parity.shared::cta.b64 p, [%0], %1;\n@p bra DONE_L;\nbra WAIT_L;\nDONE_L:\n}"
               ::"r"(bar), "r"(parity) : "memory");
}
__device__ __forceinline__ uint32_t mbar_test(uint32_t bar, uint32_t parity) {
  uint32_t ok;
  asm volatile("{\n.reg .pred p;\nmbarrier.test_wait.parity.shared::cta.b64 p, [%1], %2;\nselp.u32 %0, 1, 0, p;\n}" : "=r"(ok) : "r"(bar), "r"(parity) : "memory");
  return ok;
}
constexpr unsigned long long WATCHDOG_NS = 2000000000ull;
__device__ __forceinline__ unsigned long long gtime() { unsigned long long t; asm volatile("mov.u64 %0, %%globaltimer;" : "=l"(t)); return t; }
__device__ __forceinline__ uint32_t clock32() { uint32_t t; asm volatile("mov.u32 %0, %%clock;" : "=r"(t)); return t; }
__device__ __forceinline__ void mbar_wait_bounded(uint32_t bar, uint32_t parity) {
  unsigned long long t0 = 0;
  for (;;) {
    uint32_t ok;
    asm volatile("{\n.reg .pred p;\nmbarrier.try_wait.parity.shared::cta.b64 p, [%1], %2;\nselp.u32 %0, 1, 0, p;\n}" : "=r"(ok) : "r"(bar), "r"(parity) : "memory");
    if (ok) break;
    const unsigned long long t1 = gtime();
    if (t0 == 0) t0 = t1;
    if (t1 - t0 > WATCHDOG_NS) __trap();
  }
}
__device__ __forceinline__ void tma2d(uint32_t dst, const CUtensorMap* m, int c0, int c1, uint32_t bar) {
  asm volatile("cp.async.bulk.tensor.2d.shared::cluster.global.mbarrier::complete_tx::bytes [%0], [%1, {%3, %4}], [%2];"
               ::"r"(dst), "l"(m), "r"(bar), "r"(c0), "r"(c1) : "memory");
}
__device__ __forceinline__ void tma3d(uint32_t dst, const CUtensorMap* m, int c0, int c1, int c2, uint32_t bar) {
  asm volatile("cp.async.bulk.tensor.3d.shared::cluster.global.mbarrier::complete_tx::bytes [%0], [%1, {%3, %4, %5}], [%2];"
               ::"r"(dst), "l"(m), "r"(bar), "r"(c0), "r"(c1), "r"(c2) : "memory");
}
__device__ __forceinline__ void bulk_load(uint32_t dst, const void* src, uint32_t bytes, uint32_t bar) {
  asm volatile("cp.async.bulk.shared::cluster.global.mbarrier::complete_tx::bytes [%0], [%1], %2, [%3];" ::"r"(dst), "l"(src), "r"(bytes), "r"(bar) : "memory");
}
__device__ __forceinline__ void st_async4(uint32_t dst, const uint32_t (&v)[4], uint32_t bar) {
  asm volatile("st.async.shared::cluster.mbarrier::complete_tx::bytes.v4.b32 [%0], {%1, %2, %3, %4}, [%5];" ::"r"(dst), "r"(v[0]), "r"(v[1]), "r"(v[2]), "r"(v[3]), "r"(bar) : "memory");
}
__device__ __forceinline__ void bulk_commit() { asm volatile("cp.async.bulk.commit_group;" ::: "memory"); }
__device__ __forceinline__ void bulk_prefetch(const void* p, uint32_t bytes) {
  asm volatile("cp.async.bulk.prefetch.L2.global [%0], %1;" ::"l"(p), "r"(bytes) : "memory");
}
__device__ __forceinline__ void tma2d_store(const CUtensorMap* m, uint32_t src, int c0, int c1) {
  asm volatile("cp.async.bulk.tensor.2d.global.shared::cta.bulk_group [%0, {%2, %3}], [%1];" ::"l"(m), "r"(src), "r"(c0), "r"(c1) : "memory");
}
__device__ __forceinline__ void wg_fence() { asm volatile("wgmma.fence.sync.aligned;" ::: "memory"); }
__device__ __forceinline__ void wg_commit() { asm volatile("wgmma.commit_group.sync.aligned;" ::: "memory"); }
template <int N> __device__ __forceinline__ void wg_wait() { asm volatile("wgmma.wait_group.sync.aligned %0;" ::"n"(N) : "memory"); }
__device__ __forceinline__ void fence_async_smem() { asm volatile("fence.proxy.async.shared::cta;" ::: "memory"); }
__device__ __forceinline__ void fence_release() { asm volatile("fence.release.gpu;" ::: "memory"); }
__device__ __forceinline__ void fence_acquire() { asm volatile("fence.acquire.gpu;" ::: "memory"); }
__device__ __forceinline__ void nb_sync(int id, int n) { asm volatile("bar.sync %0, %1;" ::"r"(id), "r"(n) : "memory"); }
__device__ __forceinline__ void nb_arrive(int id, int n) { asm volatile("bar.arrive %0, %1;" ::"r"(id), "r"(n) : "memory"); }
__device__ __forceinline__ void stsm4(uint32_t addr, uint32_t r0, uint32_t r1, uint32_t r2, uint32_t r3) {
  asm volatile("stmatrix.sync.aligned.m8n8.x4.shared.b16 [%0], {%1, %2, %3, %4};" ::"r"(addr), "r"(r0), "r"(r1), "r"(r2), "r"(r3) : "memory");
}
__device__ __forceinline__ void stsm4t(uint32_t addr, uint32_t r0, uint32_t r1, uint32_t r2, uint32_t r3) {
  asm volatile("stmatrix.sync.aligned.m8n8.x4.trans.shared.b16 [%0], {%1, %2, %3, %4};" ::"r"(addr), "r"(r0), "r"(r1), "r"(r2), "r"(r3) : "memory");
}
__device__ __forceinline__ void st_relaxed4(void* p, const uint32_t (&v)[4]) {
  asm volatile("st.relaxed.gpu.global.v4.u32 [%0], {%1, %2, %3, %4};" ::"l"(p), "r"(v[0]), "r"(v[1]), "r"(v[2]), "r"(v[3]) : "memory");
}
__device__ __forceinline__ void sts128(uint32_t addr, uint32_t a, uint32_t b, uint32_t c, uint32_t d) {
  asm volatile("st.shared.v4.b32 [%0], {%1, %2, %3, %4};" ::"r"(addr), "r"(a), "r"(b), "r"(c), "r"(d) : "memory");
}
__device__ __forceinline__ uint32_t pack2(float lo, float hi) {
  uint32_t r; asm("cvt.rn.bf16x2.f32 %0, %1, %2;" : "=r"(r) : "f"(hi), "f"(lo)); return r;
}
__device__ __forceinline__ float bf_lo(uint32_t v) { return __uint_as_float(v << 16); }
__device__ __forceinline__ float bf_hi(uint32_t v) { return __uint_as_float(v & 0xffff0000u); }
__device__ __forceinline__ float bf_round(float v) { return __bfloat162float(__float2bfloat16_rn(v)); }
__device__ __forceinline__ void ldsm4(uint32_t addr, uint32_t (&r)[4]) {
  asm volatile("ldmatrix.sync.aligned.m8n8.x4.shared.b16 {%0, %1, %2, %3}, [%4];" : "=r"(r[0]), "=r"(r[1]), "=r"(r[2]), "=r"(r[3]) : "r"(addr) : "memory");
}
__device__ __forceinline__ uint4 lds128(uint32_t addr) {
  uint4 v; asm volatile("ld.volatile.shared.v4.u32 {%0, %1, %2, %3}, [%4];" : "=r"(v.x), "=r"(v.y), "=r"(v.z), "=r"(v.w) : "r"(addr) : "memory"); return v;
}
__device__ __forceinline__ uint2 lds64(uint32_t addr) { uint2 v; asm volatile("ld.volatile.shared.v2.u32 {%0, %1}, [%2];" : "=r"(v.x), "=r"(v.y) : "r"(addr) : "memory"); return v; }
__device__ __forceinline__ uint32_t lds32(uint32_t addr) { uint32_t v; asm volatile("ld.volatile.shared.u32 %0, [%1];" : "=r"(v) : "r"(addr) : "memory"); return v; }
__device__ __forceinline__ uint32_t ld_generic(const void* p) { uint32_t v; asm volatile("ld.volatile.u32 %0, [%1];" : "=r"(v) : "l"(p) : "memory"); return v; }
__device__ __forceinline__ void sts32(uint32_t addr, uint32_t v) { asm volatile("st.shared.u32 [%0], %1;" ::"r"(addr), "r"(v) : "memory"); }
__device__ __forceinline__ uint32_t fma_bf2(uint32_t a, uint32_t b, uint32_t c) { uint32_t r; asm("fma.rn.bf16x2 %0, %1, %2, %3;" : "=r"(r) : "r"(a), "r"(b), "r"(c)); return r; }
__device__ __forceinline__ uint32_t mul_bf2(uint32_t a, uint32_t b) { uint32_t r; asm("mul.rn.bf16x2 %0, %1, %2;" : "=r"(r) : "r"(a), "r"(b)); return r; }
__device__ __forceinline__ unsigned ld_relaxed(const unsigned* p) { unsigned v; asm volatile("ld.relaxed.gpu.global.u32 %0, [%1];" : "=r"(v) : "l"(p) : "memory"); return v; }
__device__ __forceinline__ void st_relaxed(unsigned* p, unsigned v) { asm volatile("st.relaxed.gpu.global.u32 [%0], %1;" ::"l"(p), "r"(v) : "memory"); }
__device__ __forceinline__ uint4 ld_relaxed4(const void* p) {
  uint4 v; asm volatile("ld.relaxed.gpu.global.v4.u32 {%0, %1, %2, %3}, [%4];" : "=r"(v.x), "=r"(v.y), "=r"(v.z), "=r"(v.w) : "l"(p) : "memory"); return v;
}
__device__ __forceinline__ float4 ld_relaxed_f4(const void* p) {
  float4 v; asm volatile("ld.relaxed.gpu.global.v4.f32 {%0, %1, %2, %3}, [%4];" : "=f"(v.x), "=f"(v.y), "=f"(v.z), "=f"(v.w) : "l"(p) : "memory"); return v;
}
__device__ __forceinline__ void red_add4(void* p, float a, float b, float c, float d) {
  asm volatile("red.relaxed.gpu.global.add.v4.f32 [%0], {%1, %2, %3, %4};" ::"l"(p), "f"(a), "f"(b), "f"(c), "f"(d) : "memory");
}
__device__ __forceinline__ void red_add_bf(void* p, uint32_t a, uint32_t b, uint32_t c) {
  asm volatile("red.relaxed.gpu.global.add.noftz.v4.bf16x2 [%0], {%1, %2, %3, %4};" ::"l"(p), "r"(a), "r"(b), "r"(c), "r"(0x3F803F80u) : "memory");
}
__device__ __forceinline__ void red_add(unsigned* p, unsigned v) { asm volatile("red.relaxed.gpu.global.add.u32 [%0], %1;" ::"l"(p), "r"(v) : "memory"); }
__device__ __forceinline__ float rcp(float v) { float r; asm("rcp.approx.ftz.f32 %0, %1;" : "=f"(r) : "f"(v)); return r; }
__device__ __forceinline__ float sigmoidf_(float v) { return rcp(1.f + __expf(-v)); }
__device__ __forceinline__ uint32_t phi2(float a, float b, float l2e = 1.4426950408889634f) {
  float ea, eb;
  asm("ex2.approx.ftz.f32 %0, %1;" : "=f"(ea) : "f"(a * l2e));
  asm("ex2.approx.ftz.f32 %0, %1;" : "=f"(eb) : "f"(b * l2e));
  uint32_t t = pack2(a, b), e = pack2(ea, eb), r;
  asm("max.NaN.bf16x2 %0, %0, %1;" : "+r"(t) : "r"(0x35863586u));
  asm("min.bf16x2 %0, %0, %1;" : "+r"(e) : "r"(0x3F803F80u));
  asm("add.rn.bf16x2 %0, %1, %2;" : "=r"(r) : "r"(t), "r"(e));
  return r;
}
__device__ __forceinline__ uint64_t mkdesc(uint32_t addr, uint32_t lbo, uint32_t sbo, uint32_t sw) {
  return (uint64_t)(((addr & 0x3FFFF) >> 4) | ((lbo >> 4) << 16)) | ((uint64_t)((sbo >> 4) | (sw << 30)) << 32);
}

template <int TA, int TB>
__device__ __forceinline__ void mma128(float (&d)[64], uint64_t da, uint64_t db, int sc) {
  asm volatile("{\n.reg .pred p;\nsetp.ne.b32 p, %66, 0;\n"
    "wgmma.mma_async.sync.aligned.m64n128k16.f32.bf16.bf16 "
    "{%0,%1,%2,%3,%4,%5,%6,%7,%8,%9,%10,%11,%12,%13,%14,%15,%16,%17,%18,%19,%20,%21,%22,%23,"
    "%24,%25,%26,%27,%28,%29,%30,%31,%32,%33,%34,%35,%36,%37,%38,%39,%40,%41,%42,%43,%44,%45,%46,%47,"
    "%48,%49,%50,%51,%52,%53,%54,%55,%56,%57,%58,%59,%60,%61,%62,%63}, "
    "%64, %65, p, 1, 1, %67, %68;\n}\n"
    : "+f"(d[0]), "+f"(d[1]), "+f"(d[2]), "+f"(d[3]), "+f"(d[4]), "+f"(d[5]), "+f"(d[6]), "+f"(d[7]),
      "+f"(d[8]), "+f"(d[9]), "+f"(d[10]), "+f"(d[11]), "+f"(d[12]), "+f"(d[13]), "+f"(d[14]), "+f"(d[15]),
      "+f"(d[16]), "+f"(d[17]), "+f"(d[18]), "+f"(d[19]), "+f"(d[20]), "+f"(d[21]), "+f"(d[22]), "+f"(d[23]),
      "+f"(d[24]), "+f"(d[25]), "+f"(d[26]), "+f"(d[27]), "+f"(d[28]), "+f"(d[29]), "+f"(d[30]), "+f"(d[31]),
      "+f"(d[32]), "+f"(d[33]), "+f"(d[34]), "+f"(d[35]), "+f"(d[36]), "+f"(d[37]), "+f"(d[38]), "+f"(d[39]),
      "+f"(d[40]), "+f"(d[41]), "+f"(d[42]), "+f"(d[43]), "+f"(d[44]), "+f"(d[45]), "+f"(d[46]), "+f"(d[47]),
      "+f"(d[48]), "+f"(d[49]), "+f"(d[50]), "+f"(d[51]), "+f"(d[52]), "+f"(d[53]), "+f"(d[54]), "+f"(d[55]),
      "+f"(d[56]), "+f"(d[57]), "+f"(d[58]), "+f"(d[59]), "+f"(d[60]), "+f"(d[61]), "+f"(d[62]), "+f"(d[63])
    : "l"(da), "l"(db), "r"(sc), "n"(TA), "n"(TB));
}

__device__ __forceinline__ void mma_ktv(float (&d)[36], const uint32_t (&a)[4], uint64_t db, int sc) {
  asm volatile("{\n.reg .pred p;\nsetp.ne.b32 p, %41, 0;\n"
    "wgmma.mma_async.sync.aligned.m64n72k16.f32.bf16.bf16 "
    "{%0,%1,%2,%3,%4,%5,%6,%7,%8,%9,%10,%11,%12,%13,%14,%15,%16,%17,%18,%19,%20,%21,%22,%23,"
    "%24,%25,%26,%27,%28,%29,%30,%31,%32,%33,%34,%35}, "
    "{%36,%37,%38,%39}, %40, p, 1, 1, 0;\n}\n"
    : "+f"(d[0]), "+f"(d[1]), "+f"(d[2]), "+f"(d[3]), "+f"(d[4]), "+f"(d[5]), "+f"(d[6]), "+f"(d[7]),
      "+f"(d[8]), "+f"(d[9]), "+f"(d[10]), "+f"(d[11]), "+f"(d[12]), "+f"(d[13]), "+f"(d[14]), "+f"(d[15]),
      "+f"(d[16]), "+f"(d[17]), "+f"(d[18]), "+f"(d[19]), "+f"(d[20]), "+f"(d[21]), "+f"(d[22]), "+f"(d[23]),
      "+f"(d[24]), "+f"(d[25]), "+f"(d[26]), "+f"(d[27]), "+f"(d[28]), "+f"(d[29]), "+f"(d[30]), "+f"(d[31]),
      "+f"(d[32]), "+f"(d[33]), "+f"(d[34]), "+f"(d[35])
    : "r"(a[0]), "r"(a[1]), "r"(a[2]), "r"(a[3]), "l"(db), "r"(sc));
}

__device__ __forceinline__ void mma_qkvz(float (&d)[20], uint64_t da, uint64_t db, int sc) {
  asm volatile("{\n.reg .pred p;\nsetp.ne.b32 p, %22, 0;\n"
    "wgmma.mma_async.sync.aligned.m64n40k16.f32.bf16.bf16 "
    "{%0,%1,%2,%3,%4,%5,%6,%7,%8,%9,%10,%11,%12,%13,%14,%15,%16,%17,%18,%19}, "
    "%20, %21, p, 1, 1, 0, 1;\n}\n"
    : "+f"(d[0]), "+f"(d[1]), "+f"(d[2]), "+f"(d[3]), "+f"(d[4]), "+f"(d[5]), "+f"(d[6]), "+f"(d[7]),
      "+f"(d[8]), "+f"(d[9]), "+f"(d[10]), "+f"(d[11]), "+f"(d[12]), "+f"(d[13]), "+f"(d[14]), "+f"(d[15]),
      "+f"(d[16]), "+f"(d[17]), "+f"(d[18]), "+f"(d[19])
    : "l"(da), "l"(db), "r"(sc));
}

template <int N> __device__ __forceinline__ void pin(float (&d)[N]) {
#pragma unroll
  for (int i = 0; i < N; i++) asm volatile("" : "+f"(d[i])::"memory");
}

struct Params {
  CUtensorMap x, w, xr, gate, up, wo, out, down, xh;
};

__device__ __forceinline__ uint32_t dup_lo(uint32_t v) { uint32_t r; asm("{\n.reg .b16 l, h;\nmov.b32 {l, h}, %1;\nmov.b32 %0, {l, l};\n}" : "=r"(r) : "r"(v)); return r; }
__device__ __forceinline__ uint32_t dup_hi(uint32_t v) { uint32_t r; asm("{\n.reg .b16 l, h;\nmov.b32 {l, h}, %1;\nmov.b32 %0, {h, h};\n}" : "=r"(r) : "r"(v)); return r; }
__device__ __forceinline__ float butterfly8(float (&s)[8], int lane, int o) {
#pragma unroll
  for (int k = 1; k < 8; k <<= 1) {
    const bool up = lane & (o * k);
#pragma unroll
    for (int j = 0; j < 4 / k; j++) s[j] = (up ? s[2 * j + 1] : s[2 * j]) + __shfl_xor_sync(~0u, up ? s[2 * j] : s[2 * j + 1], o * k);
  }
  return s[0];
}
constexpr int OWN = 8, PEER = 9;
static_assert((OA_SLOTS >> OWN * 4 & 15) * SLOT == OFF_V && (OA_SLOTS >> PEER * 4 & 15) * SLOT == OFF_PK, "");
constexpr uint64_t OR_SLOTS = (OA_SLOTS & 0xFFFFFFFFu) | OA_SLOTS >> 40 << 32;
template <class F> __device__ __forceinline__ void verify_tiles(uint32_t sb, Scratch* gs, int tm, int tn, int w, int lane, F between) {
  const uint32_t par = lds32(sb + OFF_MISC + 24), fix = sb + BAR_FIX + w * 8;
  uint64_t slots = OR_SLOTS, full = 0x04321021043210ull;
#pragma unroll 1
  for (int i = 0; i < 14; i++, slots >>= 4, full >>= 4) {
    const uint32_t a = sb + OFF_RING + ((uint32_t)slots & 15) * SLOT + w * 1024, cw = a + lane * 32 + (lane >> 2) * 4;
    if (i == 4) mbar_wait(sb + BAR_EMPTY + 7 * 8, 1);
    if (i == 8) between();
    mbar_wait(sb + BAR_LAND + (i & 7) * 8, i >> 3);
    if (i >> 1 == 4) PROF(w == 0 && lane == 0, 33 + i);
    for (;;) {
      const uint32_t u0 = lds32(cw), u1 = lds32(cw + 4096), u2 = lds32(cw + 8192), u3 = lds32(cw + 12288);
      if (__all_sync(~0u, !(mism(mism(u0, u1, par), mism(u2, u3, par), 0) & 1))) break;
      const uint4* src = gs->o[tm][i < 8 + (tn & 6) ? i : i + 2] + w * 64;
      const uint32_t ph = !mbar_test(fix, 1);
      fence_async_smem();
      __syncwarp();
      if (elect()) {
        mbar_expect_tx(fix, 4096);
#pragma unroll 1
        for (int j = 0; j < 4; j++) bulk_load(a + j * 4096, src + j * 256, 1024, fix);
      }
      mbar_wait(fix, ph);
    }
    mbar_arrive_warp(sb + BAR_OFULL + ((uint32_t)full & 7) * 8);
    if (i == 8) PROF(w == 3 && lane == 0, 28);
  }
}
template <bool BY_SM> struct Tile {
  int sm, tm, tn, mu;
  bool spare;
  __device__ __forceinline__ Tile() {
    if (BY_SM) asm volatile("mov.u32 %0, %%smid;" : "=r"(sm));
    else sm = blockIdx.x + (blockIdx.x >= 120) * 4;
    const int tp = sm >> 1, pr = sm & 1;
    const int v = tp < 32 ? tp : tp < 60 ? (tp * 293 - 928) >> 8 : tp * 8 - 464, g = v & 7, i = v >> 3;
    tm = (v & 6) * 2 + (i & 3); tn = (v & 1) * 4 + (v >> 4 & 2) + pr;
    mu = i == 5 ? 112 : g * 14 + (i - (i > 5)) * 2 + pr;
    spare = (tp | 1) == 61;
  }
};

template <bool BY_SM> __global__ void __cluster_dims__(2, 1, 1) __launch_bounds__(NTHREADS, 1) fused_kernel(const __nv_bfloat16* __restrict__ px, Scratch* gs, const __nv_bfloat16* __restrict__ w_gate,
             const __nv_bfloat16* __restrict__ w_up, const __nv_bfloat16* __restrict__ w_r, const __nv_bfloat16* __restrict__ gate_w, __nv_bfloat16* __restrict__ pout,
             const __grid_constant__ Params p) {
  extern __shared__ __align__(1024) uint8_t smem[];
  const uint32_t sb = __shfl_sync(~0u, (uint32_t)__cvta_generic_to_shared(smem), 0);
  const int tid = threadIdx.x, lane = tid & 31;
  const int warp = __shfl_sync(~0u, tid >> 5, 0), wg = warp >> 2;
  const uint32_t t_start = clock32();
  const Tile<BY_SM> tile;
  const int tm = tile.tm, tn = tile.tn, mu = tile.mu, cta = tm * 8 + tn;
  const uint32_t zero = tile.sm >> 12;
  if (warp == 0) {
#pragma unroll
    for (int s = 0; s < PRE; s++)
      if (elect()) mbar_init(sb + BAR_FULL + s * 8, 1);
    asm volatile("fence.mbarrier_init.release.cluster;" ::: "memory");
    if (!tile.spare) {
#pragma unroll
      for (int s = 0; s < PRE; s++) {
        if (elect()) tma3d(sb + OFF_W1 + s * WQKV_BYTES, &p.w, tn * 64, s * 64, 0, sb + BAR_FULL + s * 8);
        if (elect()) tma2d(sb + OFF_RING + s * SLOT, &p.x, s * 64, tm * 128, sb + BAR_FULL + s * 8);
        PROF(lane == 0, 64 + s);
      }
      if (elect()) {
#pragma unroll
        for (int s = 0; s < PRE; s++) mbar_expect_tx(sb + BAR_FULL + s * 8, SLOT + WQKV_BYTES);
      }
    }
  }
  if (warp) {
    const int wi = warp == 15 ? 0 : warp;
    const int cnt = wi < 7 ? 1 : wi < 13 ? 4 : 5;
#pragma unroll
    for (int i = 0; i < 4; i++)
      if ((i >= PRE || wi) && elect()) mbar_init(sb + OFF_BAR + wi * 32 + i * 8, cnt);
    asm volatile("fence.mbarrier_init.release.cluster;" ::: "memory");
  }
  __syncthreads();
  if (tile.spare) {
    if (warp == 0) {
      const unsigned tag = (ld_relaxed(&gs->spare[tile.sm & 3]) + 1) & 0xFFF;
      const unsigned long long t0 = gtime();
      uint4 r4;
      do {
        __nanosleep(2048);
        if (gtime() - t0 > WATCHDOG_NS) __trap();
        r4 = ld_relaxed4(&gs->rslot[tile.sm & 3][lane * 4]);
      } while (!__all_sync(~0u, (((r4.x ^ tag) | (r4.y ^ tag) | (r4.z ^ tag) | (r4.w ^ tag)) & 0xFFF) == 0));
      if (tid == 0) st_relaxed(&gs->spare[tile.sm & 3], tag);
    }
    return;
  }

  auto patch_row = [&](int pw) {
    const unsigned key = lds32(sb + OFF_MISC + 16);
    const int sel = 0xFFFF - (int)(key & 0xFFFF) - tm * 128;
    if (pw == 0 && sel >= 0 && sel < 128) {
      const unsigned k16 = key >> 16;
      const float rs = bf_round(sigmoidf_(__uint_as_float(((k16 & 0x8000u) ? (k16 & 0x7FFFu) : (~k16 & 0xFFFFu)) << 16)));
      float v[12];
      const float4* yp = gs->y[lane >> 4][0] + tn * 16 + (lane & 15);
      for (;;) {
#pragma unroll
        for (int i = 0; i < 3; i++) {
          const float4 u = ld_relaxed_f4(yp + i * 128);
          v[4 * i] = u.x; v[4 * i + 1] = u.y; v[4 * i + 2] = u.z; v[4 * i + 3] = u.w;
        }
        const float n = v[3] + v[7] + v[11];
        if (__all_sync(~0u, n + __shfl_xor_sync(~0u, n, 16) == 3.f * MOD_CTAS)) break;
        __nanosleep(Y_SLEEP);
      }
#pragma unroll
      for (int i = 0; i < 10; i++) v[i] = bf_round(bf_round(v[i] + __shfl_xor_sync(~0u, v[i], 16)) * rs);
      PROF(lane == 0, 24);
      mbar_wait(sb + BAR_X, 0);
      if (lane < 16) {
        uint4* xp = (uint4*)(smem + res_off(lane >> 3, sel >> 6) + (sel & 63) * 128 + (((lane ^ sel) & 7) << 4));
        const uint4 xv = *xp;
        *xp = make_uint4(pack2(bf_lo(xv.x) + v[0], bf_hi(xv.x) + v[1]), pack2(bf_lo(xv.y) + v[2], bf_hi(xv.y) + v[4]),
                         pack2(bf_lo(xv.z) + v[5], bf_hi(xv.z) + v[6]), pack2(bf_lo(xv.w) + v[8], bf_hi(xv.w) + v[9]));
      }
      __syncwarp();
      mbar_arrive_warp(sb + BAR_Y);
    }
  };
  if (wg == 3) {
    asm volatile("setmaxnreg.dec.sync.aligned.u32 24;");
    if (warp == 12) {
      mbar_wait(sb + BAR_GATE, 0);
      uint64_t slots = OR_SLOTS, deps = 0x8CBA98A9877654ull;
      uint32_t seen;
#pragma unroll 1
      for (int i = 0; i < 14; i++, deps >>= 4, slots >>= 4) {
        const uint32_t slab = i < 8 + (tn & 6) ? i : i + 2;
        if (!(i & 7)) { mbar_wait(sb + BAR_PUB + (i & 8), 0); seen = 0; }
        if (!(seen >> (slab & 7) * 4 & 4))
          while (!((seen = __shfl_sync(~0u, ld_relaxed(gs->cnt[(i & 8) * 2 + tm]), 0)) >> (slab & 7) * 4 & 4)) __nanosleep(B_SLEEP);
        if (i == 8) mbar_wait(sb + BAR_OWN, 0);
        mbar_wait(sb + BAR_EMPTY + ((uint32_t)deps & 15) * 8, (i & 7) < 5);
        if (elect()) bulk_load(sb + OFF_RING + ((uint32_t)slots & 15) * SLOT, gs->o[tm][slab], SLOT, sb + BAR_LAND + (i & 7) * 8);
        if (elect()) mbar_expect_tx(sb + BAR_LAND + (i & 7) * 8, SLOT);
        PROF(lane == 0, 44 + i);
        if (i == 8) PROF(lane == 0, 43);
      }
    } else if (warp == 13) {
#pragma unroll 1
      for (int g = PRE; g < 32; g++) {
        const bool reuse = (g >> 2) == 4;
        const uint32_t s = g & 3, full = sb + BAR_FULL + (g & 7) * 8, c0 = tn * 64 + (g & 16) * 32, c1 = (g < 16 ? g : g - 4 & 15) * 64;
        if (g < 4) while ((int)(clock32() - t_start) < g * ST1) {}
        mbar_wait(sb + BAR_EMPTY + (g + 4 & 7) * 8, (g + 4 >> 3 & 1) ^ 1);
        if (!reuse && elect()) tma2d(sb + OFF_RING + s * SLOT, &p.x, c1, tm * 128, full);
        if (elect()) tma3d(sb + OFF_W1 + s * WQKV_BYTES, &p.w, c0, c1, 0, full);
        if (elect()) mbar_expect_tx(full, reuse ? WQKV_BYTES : SLOT + WQKV_BYTES);
        PROF(lane == 0, 64 + g);
        const uint32_t i = g - RT_G0;
        if (i < 4 && elect()) {
          mbar_expect_tx(sb + BAR_RT + i * 8, i ? 8192 : 8192 + 4096);
          tma2d(sb + OFF_PK + i * 8192 + (i == 3) * 1024, &p.xr, ((i + RT_ROT) & 3) * 256, cta * 16, sb + BAR_RT + i * 8);
          if (i == 0) { bulk_load(sb + OFF_KVB, w_r, 2048, sb + BAR_RT); bulk_load(sb + OFF_KVB + 2048, gate_w, 2048, sb + BAR_RT); }
        }
        const uint32_t c = g - MOD_START;
        if (c == MOD_BUFS) mbar_wait(sb + BAR_RTD, 0);
        if (c < MOD_BUFS0 && mu < MOD_CTAS && elect()) {
          PROF(true, 192 + c);
          const uint32_t mb = c < MOD_BUFS ? c + 2 : c - MOD_BUFS, mfull = sb + BAR_MFULL + mb * 8, mdst = sb + mod_off(mb);
          mbar_expect_tx(mfull, c ? 8192 : 8192 + 2048);
          tma3d(mdst, &p.gate, mu * 32, c * 16, 0, mfull); tma3d(mdst + 4096, &p.up, mu * 32, c * 16, 0, mfull);
        }
        if (g == PF_W && tm >= PF_W + 3 && elect())
          asm volatile("cp.async.bulk.prefetch.tensor.3d.L2.global [%0, {%1, %2, %3}];" ::"l"(&p.w), "r"(tn * 64), "r"(tm * 64), "r"(0) : "memory");
        const uint32_t pc = g - PF_MOD;
        if (pc < 16 && elect()) bulk_prefetch((cta & 64 ? w_up : w_gate) + (size_t)(pc * 64 + (cta & 63)) * F_, F_ * 2);
      }
      mbar_arrive_warp(sb + BAR_GATE);
      const uint32_t lowb = (1u << (tn & 6) * 4) - 1;
      uint64_t slabs = (uint64_t)((0xFEDCBA98u & lowb) | (0xFEDCBAu & ~lowb)) << 40 | (uint64_t)(8 + (tn ^ 1)) << 36 | (uint64_t)(8 + tn) << 32 | 0x76543210u;
      uint64_t deps = 0x8CBA98CBA9876554ull, ws = OW_SLOTS;
      uint32_t full = sb + BAR_OFULL, ph = 1;
#pragma unroll 1
      for (int g = 0; g < 16; g++, slabs >>= 4, deps >>= 4, ws >>= 4) {
        mbar_wait(sb + BAR_EMPTY + ((uint32_t)deps & 15) * 8, ph);
        if (elect()) tma3d(sb + OFF_RING + ((uint32_t)ws & 15) * SLOT, &p.wo, 0, ((uint32_t)slabs & 15) * 64, tn * 2, full);
        if (elect()) mbar_expect_tx(full, SLOT);
        PROF(lane == 0, 96 + g);
        if (g >> 1 == OWN / 2 && lane < 4) mbar_arrive(full);
        full += 8;
        if (full == sb + BAR_OFULL + 40) { full -= 40; ph ^= 1; }
      }
    } else if (warp == 14) {
      if (mu < MOD_CTAS) {
        uint32_t full = sb + BAR_MFULL + 16, dst = sb + OFF_MOD, ph = 0;
#pragma unroll 1
        for (int c = MOD_BUFS0; c < 24; c++) {
          mbar_wait(full + (BAR_MEMPTY - BAR_MFULL), ph);
          PROF(lane == 0, 192 + c);
          if (c < 16) {
            if (elect()) { tma3d(dst, &p.gate, mu * 32, c * 16, 0, full); tma3d(dst + 4096, &p.up, mu * 32, c * 16, 0, full); }
          } else if (elect()) tma3d(dst, &p.down, 0, mu * 32 + (c - 16) * 4, 0, full);
          if (elect()) mbar_expect_tx(full, 8192);
          full += 8; dst += MOD_STEP;
          if (full == sb + BAR_MFULL + MOD_BUFS0 * 8) { full -= MOD_BUFS * 8; dst = sb + OFF_MOD; ph ^= 1; }
        }
      }
      if (elect()) {
        mbar_wait(sb + BAR_IDX, 0);
        const bool paired = PAIRED && ld_relaxed(&gs->block[cta ^ 1]) == (blockIdx.x ^ 1);
        if (paired) mbar_expect_tx(sb + BAR_PEER, SLOT);
        mbar_expect_tx(sb + BAR_X, 32768);
        if (mu < MOD_CTAS) {
          mbar_wait(sb + BAR_MEMPTY + 3 * 8, 0);
          mbar_wait(sb + BAR_MEMPTY + 4 * 8, 0);
          mbar_wait(sb + BAR_MEMPTY + 2 * 8, 1);
        } else mbar_wait(sb + BAR_GATE, 0);
#pragma unroll
        for (int i = 0; i < 4; i++) {
          if (i == 3) mbar_wait(sb + BAR_OEMPTY + 3 * 8, 0);
          tma2d(sb + res_off(i >> 1, i & 1), &p.xh, tn * 128 + (i >> 1) * 64, tm * 128 + (i & 1) * 64, sb + BAR_X);
        }
        if (!paired) {
          mbar_wait(sb + BAR_OWN, 0);
          while (!(ld_relaxed(gs->cnt[16 + tm]) & 4u << (tn ^ 1) * 4)) __nanosleep(32);
          const uint32_t par = lds32(sb + OFF_MISC + 24);
          for (uint32_t ph = !mbar_test(sb + BAR_MFULL, 1), bad = 1; bad & 1; ph ^= 1) {
            fence_async_smem();
            mbar_expect_tx(sb + BAR_MFULL, SLOT);
            bulk_load(sb + OFF_PK, gs->o[tm][8 + (tn ^ 1)], SLOT, sb + BAR_MFULL);
            mbar_wait(sb + BAR_MFULL, ph);
            bad = 0;
#pragma unroll 1
            for (int i = 0; i < 512; i++) bad |= lds32(sb + OFF_PK + i * 32 + (i & 28)) ^ par;
          }
          mbar_arrive(sb + BAR_PEER);
        }
      }
    } else {
#pragma unroll 1
      for (int i = 2; i < 9; i++)
        if (elect()) asm volatile("prefetch.tensormap [%0];" ::"l"(&p.x + i) : "memory");
      mbar_wait_bounded(sb + BAR_DONE, 0);
    }
  } else if (wg == 2) {
    asm volatile("setmaxnreg.dec.sync.aligned.u32 40;");
    const int mw = warp & 3;
    if (mw == 0) {
      const unsigned tag = (ld_relaxed(&gs->rslot[tn][cta]) + 1) & 0xFFF;
#pragma unroll
      for (int i = 0; i < 2; i++)
        if (lane < 28) ((float4*)gs)[cta * 56 + i * 28 + lane] = make_float4(0.f, 0.f, 0.f, 0.f);
      if (lane == 29) gs->block[cta] = blockIdx.x;
      fence_release();
      nb_sync(NB_KEY, 160);
      const uint4 k4 = lds128(sb + OFF_MISC);
      if (lane < 8) st_relaxed(&gs->rslot[lane][cta], max(max(k4.x, k4.y), max(k4.z, k4.w)) | tag);
      if (lane < 16) st_relaxed(&gs->gslot[cta * 16 + lane], lds32(sb + OFF_G + lane * 4) | tag);
      PROF(lane == 0, 20);
      uint4 r4;
      do {
        __nanosleep(RT_SLEEP);
        r4 = ld_relaxed4(&gs->rslot[tn][lane * 4]);
      } while (!__all_sync(~0u, (((r4.x ^ tag) | (r4.y ^ tag) | (r4.z ^ tag) | (r4.w ^ tag)) & 0xFFF) == 0));
      const int c0 = 0xFFF0 - lane * 64;
      unsigned key = max(max((r4.x & 0xFFFF0000u) | (c0 + ((r4.x >> 12) & 15)), (r4.y & 0xFFFF0000u) | (c0 - 16 + ((r4.y >> 12) & 15))),
                         max((r4.z & 0xFFFF0000u) | (c0 - 32 + ((r4.z >> 12) & 15)), (r4.w & 0xFFFF0000u) | (c0 - 48 + ((r4.w >> 12) & 15))));
      key = __reduce_max_sync(~0u, key);
      if (elect()) {
        sts32(sb + OFF_MISC + 16, key);
        sts32(sb + OFF_MISC + 24, tag & 1);
        if (mu < MOD_CTAS) {
          const __nv_bfloat16* row = px + (size_t)(0xFFFF - (key & 0xFFFF)) * D_;
          bulk_load(sb + OFF_XSEL, row, 1024, sb + BAR_MFULL + 16);
          bulk_load(sb + OFF_XSEL + MOD_STEP, row + 512, 1024, sb + BAR_MFULL + 16);
        }
      }
      PROF(lane == 0, 21);
      do {
        r4 = ld_relaxed4(&gs->gslot[tm * 128 + lane * 4]);
      } while (!__all_sync(~0u, (((r4.x ^ tag) | (r4.y ^ tag) | (r4.z ^ tag) | (r4.w ^ tag)) & 0xFFF) == 0));
      sts128(sb + OFF_G + lane * 16, r4.x & 0xFFFF0000u, r4.y & 0xFFFF0000u, r4.z & 0xFFFF0000u, r4.w & 0xFFFF0000u);
      fence_acquire();
      __syncwarp();
    }
    PROF(tid == 256, 22);
    if (mu >= MOD_CTAS) {
      mbar_arrive_warp(sb + BAR_IDX);
    } else {
      const uint32_t wp = sb + (mw >> 1) * 4096 + (mw & 1) * 512 + lane * 16;
      uint32_t mp = sb + OFF_XSEL + (mw & 1) * 64 + (lane >> 2) * 8, mc = 128;
      float acc[8] = {0.f, 0.f, 0.f, 0.f, 0.f, 0.f, 0.f, 0.f};
      uint32_t b = 2, ph = 0;
#pragma unroll 1
      for (int c = 0; c < 24; c++) {
        mbar_wait(sb + BAR_MFULL + b * 8, ph);
        PROF_C(tid == 256, 216 + c);
        const uint32_t a = wp + mod_off(b);
        const uint2 m = lds64(mp);
        const uint4 w0 = lds128(a), w1 = lds128(a + 1024), w2 = lds128(a + 2048), w3 = lds128(a + 3072);
        mp += c == 7 ? MOD_STEP - 1024 + 128 : mc;
        const uint32_t m0 = dup_lo(m.x), m1 = dup_hi(m.x), m2 = dup_lo(m.y), m3 = dup_hi(m.y);
        uint4 q = make_uint4(mul_bf2(w0.x, m0), mul_bf2(w0.y, m0), mul_bf2(w0.z, m0), mul_bf2(w0.w, m0));
        q = make_uint4(fma_bf2(w1.x, m1, q.x), fma_bf2(w1.y, m1, q.y), fma_bf2(w1.z, m1, q.z), fma_bf2(w1.w, m1, q.w));
        q = make_uint4(fma_bf2(w2.x, m2, q.x), fma_bf2(w2.y, m2, q.y), fma_bf2(w2.z, m2, q.z), fma_bf2(w2.w, m2, q.w));
        mbar_arrive_warp(sb + BAR_MEMPTY + b * 8 + (w3.x & zero));
        q = make_uint4(fma_bf2(w3.x, m3, q.x), fma_bf2(w3.y, m3, q.y), fma_bf2(w3.z, m3, q.z), fma_bf2(w3.w, m3, q.w));
        if (++b == 5) b = c < 3 ? 0 : 2;
        if (b == 2) ph ^= 1;
        acc[0] += bf_lo(q.x); acc[1] += bf_hi(q.x); acc[2] += bf_lo(q.y); acc[3] += bf_hi(q.y);
        acc[4] += bf_lo(q.z); acc[5] += bf_hi(q.z); acc[6] += bf_lo(q.w); acc[7] += bf_hi(q.w);
        if (c == 15) {
          const uint32_t ft = fresh_tid(), fl = ft & 31;
          sts32(sb + OFF_PART + (ft & 96) * 4 + ((ft & 3) * 8 + (fl >> 2)) * 4, __float_as_uint(butterfly8(acc, fl, 4)));
          nb_sync(NB_MODW, 128);
          const float* part = (const float*)(smem + OFF_PART) + fl;
          const float gp = bf_round(part[0] + part[32]), up = bf_round(part[64] + part[96]);
          *(__nv_bfloat16*)(smem + OFF_PART + 512 + fl * 2) = __float2bfloat16_rn(bf_round(gp * sigmoidf_(gp)) * up);
          __syncwarp();
          mp = sb + OFF_PART + 512; mc = 8;
#pragma unroll
          for (int i = 0; i < 8; i++) acc[i] = 0.f;
          PROF(lane == 0 && mw == 0, 23);
        }
      }
      float4* yacc = gs->y[tn & 1][0] + (fresh_tid() & 127);
      red_add4(yacc, acc[0], acc[1], acc[2], 1.f);
      red_add4(yacc + 128, acc[3], acc[4], acc[5], 1.f);
      red_add4(yacc + 256, acc[6], acc[7], 0.f, 1.f);
      PROF(lane == 0 && mw == 0, 25);
    }
    mbar_wait(sb + BAR_GATE, 0);
    mbar_wait(sb + BAR_IDX, 0);
    verify_tiles(sb, gs, tm, tn, mw, lane, [&]() { patch_row(mw); });
  } else {
    asm volatile("setmaxnreg.inc.sync.aligned.u32 224;");
    const int w = warp & 3, wt = tid & 127;
    const int nb_self = NB_WG0 + wg;
    const uint64_t da0 = mkdesc(sb + OFF_RING, 16, 1024, 1), db0 = mkdesc(sb + OFF_RING, 8192, 1024, 1);

    if (wg == 1) {
      sts128(sb + OFF_ONES - (w >> 1) * 9216 + (w & 1) * 512 + lane * 16, 0x3F803F80u, 0x3F803F80u, 0x3F803F80u, 0x3F803F80u);
      sts32(sb + OFF_MISC + 20, 0x3FB8AA3Bu);
      fence_async_smem();
      float s[8] = {0.f, 0.f, 0.f, 0.f, 0.f, 0.f, 0.f, 0.f};
      uint32_t mask = 0xffff0000u;
#pragma unroll 1
      for (int i = 0; i < 4; i++) {
        const uint32_t u = (i + RT_ROT) & 3;
        mbar_wait(sb + BAR_RT + i * 8, 0);
        const uint4 wr = lds128(sb + OFF_KVB + u * 512 + lane * 16), gw = lds128(sb + OFF_KVB + 2048 + u * 512 + lane * 16);
        uint4 xv[4];
#pragma unroll
        for (int r = 0; r < 4; r++) xv[r] = lds128(sb + OFF_PK + i * 8192 + (i == 3) * 1024 + (w * 4 + r) * 512 + lane * 16);
        const float wf[16] = {bf_lo(wr.x), bf_hi(wr.x), bf_lo(wr.y), bf_hi(wr.y), bf_lo(wr.z), bf_hi(wr.z), bf_lo(wr.w), bf_hi(wr.w),
                              bf_lo(gw.x), bf_hi(gw.x), bf_lo(gw.y), bf_hi(gw.y), bf_lo(gw.z), bf_hi(gw.z), bf_lo(gw.w), bf_hi(gw.w)};
#pragma unroll
        for (int r = 0; r < 4; r++) {
          const uint4 xq = xv[r];
          const float xf[8] = {bf_lo(xq.x), __uint_as_float(xq.x & mask), bf_lo(xq.y), bf_hi(xq.y), bf_lo(xq.z), bf_hi(xq.z), bf_lo(xq.w), bf_hi(xq.w)};
#pragma unroll
          for (int j = 0; j < 8; j++) { s[2 * r] = fmaf(xf[j ^ 1], wf[j ^ 1], s[2 * r]); s[2 * r + 1] = fmaf(xf[j ^ 1], wf[8 + (j ^ 1)], s[2 * r + 1]); }
          mask = ((__float_as_uint(s[2 * r]) | __float_as_uint(s[2 * r + 1])) & zero) | 0xffff0000u;
        }
      }
      mbar_arrive_warp(sb + BAR_RTD + (__float_as_uint(s[6]) & zero));
      float v = butterfly8(s, lane, 1);
      PROF_C(wt == 0 && v != 12345.f, 19);
      v += __shfl_xor_sync(~0u, v, 8);
      v = bf_round(v + __shfl_xor_sync(~0u, v, 16));
      const unsigned rb = __float_as_uint(v) >> 16, row = w * 4 + ((lane & 7) >> 1);
      unsigned key = (lane & 1) ? 0u : ((((rb & 0x8000u) ? (~rb & 0xFFFFu) : (rb | 0x8000u)) << 16) | ((15 - row) << 12));
      key = __reduce_max_sync(~0u, key);
      if (lane == 0) sts32(sb + OFF_MISC + w * 4, key);
      if (lane < 8 && (lane & 1)) sts32(sb + OFF_G + row * 4, __float_as_uint(bf_round(sigmoidf_(v))));
      nb_arrive(NB_KEY, 160);
      nb_sync(NB_ORDER_AB, 256);
    }
    uint4* const kvacc = &gs->kv[wg][tn][0][wt];
    float aq[64];
    uint32_t su[9];
    {
      float ak[64], av[64], c[36];
      uint32_t pk[8][4];
      PROF_C(wt == 0, 1 + wg * 8);
#pragma unroll 1
      for (int g = 0; g < 16; g++) {
        const uint64_t dx = da0 + (g & 3) * (SLOT >> 4), dw = da0 + ((OFF_W1 >> 4) + (g & 3) * (WQKV_BYTES >> 4));
        mbar_wait(sb + BAR_FULL + (g & 7) * 8, g >> 3);
        if (g == 0) PROF_C(wt == 0, 2 + wg * 8);
        wg_fence();
#pragma unroll
        for (int kk = 0; kk < 4; kk++) mma128<1, 0>(ak, dw + (512 + kk * 128), dx + kk * 2, kk ? 1 : g);
        wg_commit();
        wg_wait<1>();
        if (g) mbar_arrive_warp(sb + BAR_EMPTY + (g - 1 & 7) * 8);
        wg_fence();
#pragma unroll
        for (int kk = 0; kk < 4; kk++) mma128<1, 0>(av, dw + (1024 + kk * 128), dx + kk * 2, kk ? 1 : g);
        wg_commit();
#pragma unroll
        for (int kk = 0; kk < 4; kk++) mma128<1, 0>(aq, dw + kk * 128, dx + kk * 2, kk ? 1 : g);
        wg_commit();
      }
      if (wg == 0) nb_arrive(NB_ORDER_AB, 256);
      mbar_wait(sb + BAR_RTD, 0);
      if (wg == 1) nb_sync(NB_STG, 256);
      wg_wait<2>();
      pin(ak);
      PROF_C(wt == 0, 3 + wg * 8);
      const uint32_t va = sb + OFF_V + (w * 16 + (lane & 15)) * 128;
      uint32_t lk[8];
#pragma unroll
      for (int u = 0; u < KL; u++) lk[u] = 0x3FB8AA3Bu;
#pragma unroll
      for (int u = 0; u < 8; u++) {
#pragma unroll
        for (int i = 0; i < 4; i++) pk[u][i] = phi2(ak[8 * u + 2 * i], ak[8 * u + 2 * i + 1], __uint_as_float(lk[u]));
        if (u == VK) { wg_wait<1>(); pin(av); }
        if (u == MM) { wg_wait<0>(); mbar_arrive_warp(sb + BAR_EMPTY + 7 * 8); }
        const uint32_t z = mism(pk[u][0], pk[u][1], 0) | mism(pk[u][2], pk[u][3], 0);
#pragma unroll
        for (int t = u < VK ? 8 : (u - VK) * 8 / (8 - VK); t < (u - VK + 1) * 8 / (8 - VK); t++) {
          const float* v = &av[8 * t];
          stsm4(va + (t >> 2) * 9216 + ((((lane >> 4) + 2 * (t & 3)) ^ (lane & 7)) << 4) + (z & zero), pack2(v[0], v[1]), pack2(v[2], v[3]), pack2(v[4], v[5]), pack2(v[6], v[7]));
        }
        if (u + KL < 8) lk[u + KL] = lds32(sb + OFF_MISC + 20 + (u < VK ? z & zero : 0));
      }
      fence_async_smem();
      nb_sync(nb_self, 128);
      PROF_C(wt == 0, 8 + wg * 8);
      const uint64_t dv = mkdesc(sb + OFF_V, 16, 1024, 1);
      wg_fence();
#pragma unroll
      for (int kk = 0; kk < 8; kk++) mma_ktv(c, pk[kk], dv + ((kk >> 2) * 576 + (kk & 3) * 2), kk ? 1 : 0);
      wg_commit();
      if (wg == 1) nb_arrive(NB_ORDER_BO, 256);
      mbar_wait(sb + BAR_IDX, 0);
      wg_wait<0>();
      pin(c); pin(aq);
      PROF_C(wt == 0, 4 + wg * 8);
#pragma unroll
      for (int i = 0; i < 8; i++) {
        const int j = (i & 3) * 4 + (i >> 2) * 2;
        su[i] = w >= 2 ? pack2(c[16 + j], c[17 + j]) : pack2(c[j], c[j + 1]);
      }
      su[8] = pack2(c[32], c[34]);
#pragma unroll
      for (int u = 0; u < 3; u++)
        if (u < R0 || wg) red_add_bf(kvacc + u * 128, su[3 * u], su[3 * u + 1], su[3 * u + 2]);
    }
    const uint32_t par = lds32(sb + OFF_MISC + 24);
    {
      const bool paired = PAIRED && ld_relaxed(&gs->block[cta ^ 1]) == (blockIdx.x ^ 1);
      uint4 kv[3];
      int tries = wg ? 0 : RETRY + 1;
      const uint8_t* gl = smem + OFF_MISC + 20;
      asm volatile("" : "+l"(gl));
      const uint32_t l2e = ld_generic(gl);
      auto stage_kv = [&]() {
        const uint32_t kb = sb + OFF_KVB + w * 256, ka = kb + (lane & 3) * KVB_N + (lane >> 2) * 16;
        sts128(ka, kv[0].x, kv[0].y, kv[0].z, kv[1].x);
        sts128(ka + 128, kv[1].y, kv[1].z, kv[2].x, kv[2].y);
        sts32(kb + 4 * KVB_N + lane * 4, dup_lo(kv[2].z));
        sts32(kb + 4 * KVB_N + 128 + lane * 4, dup_hi(kv[2].z));
        return __all_sync(~0u, (kv[0].w & kv[1].w & kv[2].w) == 0x41804180u && (kv[0].w | kv[1].w | kv[2].w) == 0x41804180u);
      };
      const uint32_t qa = sb + OFF_PK + ((lane >> 4) * 8 + (lane & 7)) * 128 + (((2 * w + ((lane >> 3) & 1)) ^ (lane & 7)) << 4);
      uint32_t lq[8];
#pragma unroll
      for (int u = 0; u < QA; u++) lq[u] = l2e;
#pragma unroll
      for (int u = 0; u < 8; u++) {
        uint32_t r[4];
#pragma unroll
        for (int i = 0; i < 4; i++) r[i] = phi2(aq[8 * u + 2 * i], aq[8 * u + 2 * i + 1], __uint_as_float(lq[u]));
        stsm4t(qa + u * 2048, r[0], r[1], r[2], r[3]);
        if (u + 1 == KF && wg) {
          const uint4* src = kvacc + (r[3] & zero);
#pragma unroll
          for (int i = 0; i < 3; i++) kv[i] = ld_relaxed4(src + i * 128);
        }
        const int ru = u / RS + R0;
        if (u % RS == RS - 1 && ru < 3 && !wg) red_add_bf(kvacc + ru * 128, su[3 * ru], su[3 * ru + 1], su[3 * ru + 2]);
        if (u + QA < 8) lq[u + QA] = lds32(sb + OFF_MISC + 20);
      }
      PROF_C(wt == 0, 34 + wg * 2);
      bool have = wg && stage_kv();
      for (; !have; tries++) {
        if (tries > RETRY)
          while (ld_relaxed((const unsigned*)&(kvacc - lane)[256 + 31].w) != 0x41804180u) __nanosleep(wg ? KV_SLEEP : KV_SLEEP_A);
#pragma unroll
        for (int i = 0; i < 3; i++) kv[i] = ld_relaxed4(kvacc + i * 128);
        have = stage_kv();
      }
      PROF_C(wt == 0, 5 + wg * 8);
      fence_async_smem();
      nb_sync(nb_self, 128);
      float o[2][2][20];
      const uint64_t dq = mkdesc(sb + OFF_PK, 16, 1024, 1), dz = mkdesc(sb + OFF_KVB, 128, KVB_N, 0);
      wg_fence();
#pragma unroll
      for (int m = 0; m < 2; m++) {
#pragma unroll
        for (int h = 0; h < 2; h++)
#pragma unroll
          for (int kk = 0; kk < 2; kk++) mma_qkvz(o[m][h], dq + (m * 512 + h * 4 + kk * 2), dz + (h * 32 + kk * 16), kk);
        wg_commit();
      }
      if (wg && elect()) red_add(gs->cnt[16 + tm], 1u << tn * 4);
      uint32_t tag[2][4];
#pragma unroll
      for (int i = 0; i < 8; i++) tag[i >> 2][i & 3] = (lane >> 3) == (i & 3) && ((lane ^ (lane >> 3)) & 1) == (i >> 2);
      uint32_t gr[8];
      const uint8_t* ga = smem + OFF_G + (w * 16 + (lane >> 2)) * 4;
      asm volatile("" : "+l"(ga));
#pragma unroll
      for (int i = 0; i < OA; i++) gr[i] = ld_generic(ga + (i >> 2) * 256 + (i & 1) * 32);
      const uint32_t oo = w * 1024 + (lane >> 2) * 64 + (((lane ^ (lane >> 3)) & 3) << 4);
      uint8_t* const og = (uint8_t*)gs->o[tm][wg * 8 + tn] + oo;
      uint32_t ob[8][4];
#pragma unroll
      for (int m = 0; m < 2; m++) {
        if (m == 0) wg_wait<1>(); else wg_wait<0>();
        pin(o[m][0]); pin(o[m][1]);
        if (m && wg) mbar_arrive_warp(sb + BAR_PUB + 8);
        if (m && !wg) nb_arrive(NB_STG, 256);
        if (m && wg) nb_arrive(NB_HOLD, 256);
        if (m && wg && paired && elect()) mbar_arrive_peer(peer_addr(sb + BAR_PA));
        if (m == 0) PROF_C(wt == 0, 6 + wg * 8);
#pragma unroll
        for (int u = 0; u < 4; u++) {
          const int h = u >> 1, i = u & 1;
          const float* on = o[m][h];
          const float sc = __uint_as_float(gr[m * 4 + u]) * rcp(on[16 + 2 * i] + 1e-6f);
          const uint32_t sc2 = pack2(sc, sc);
#pragma unroll
          for (int j = 0; j < 4; j++) {
            const uint32_t v = mul_bf2(pack2(on[4 * j + 2 * i], on[4 * j + 2 * i + 1]), sc2);
            asm("lop3.b32 %0, %1, %2, %3, 0xB8;" : "=r"(ob[m * 4 + u][j]) : "r"(v), "r"(tag[i][j]), "r"(par));
          }
          st_relaxed4(og + (h * 8192 + m * 4096 + i * 512), ob[m * 4 + u]);
          if (wg) sts128(sb + OFF_V + oo + (h * 8192 + m * 4096 + i * 512), ob[m * 4 + u][0], ob[m * 4 + u][1], ob[m * 4 + u][2], ob[m * 4 + u][3]);
          const int n = m * 4 + u + OA;
          if (n < 8) gr[n] = ld_generic(ga + (n >> 2) * 256 + (n & 1) * 32);
        }
      }
      if (!wg) {
        if (elect()) red_add(gs->cnt[tm], 1u << tn * 4);
        mbar_arrive_warp(sb + BAR_PUB);
      }
      PROF(wt == 0, 17 + wg);
      if (wg) {
        fence_async_smem();
        __syncwarp();
        mbar_arrive_warp(sb + BAR_OWN);
        PROF(wt == 0, 15);
        if (paired) {
          const uint32_t pb = peer_addr(sb);
          mbar_wait(sb + BAR_PA, 0);
#pragma unroll
          for (int u = 0, z = 0; u < 8; u++) {
            if (u) z = lds32(sb + OFF_ONES) & zero;
            st_async4(pb + OFF_PK + oo + ((u >> 1 & 1) * 8192 + (u >> 2) * 4096 + (u & 1) * 512) + z, ob[u], pb + BAR_PEER);
          }
        }
      }
    }
    if (wg == 0) {
      float acc[2][64];
      nb_sync(NB_ORDER_BO, 256);
      PROF_C(wt == 0, 26);
      uint32_t xr[2][8][4], q[2][2];
      const uint32_t ta = sb + (uint32_t)(w * 16 + (lane & 15)) * 128;
      const uint64_t do0 = mkdesc(sb + OFF_RING, 16, 512, 2);
      uint64_t xs = OA_SLOTS, ws = OW_SLOTS;
#pragma unroll 1
      for (int g = 0; g < 13 - TL; g++, xs >>= 4, ws >>= 4) {
        const uint32_t r = g * 52 >> 8, s = g - r * 5;
        const uint64_t da = do0 + ((uint32_t)xs & 15) * (SLOT >> 4), db = db0 + ((uint32_t)ws & 15) * (SLOT >> 4);
        if (g == OWN) mbar_wait(sb + BAR_OWN, 0);
        if (g == PEER) { PROF(wt == 0, 39); mbar_wait(sb + BAR_PEER, 0); PROF(wt == 0, 40); fence_async_smem(); }
        if (g == HOLD) nb_sync(NB_HOLD, 256);
        mbar_wait(sb + BAR_OFULL + s * 8, r & 1);
        wg_fence();
#pragma unroll
        for (int kk = 0; kk < 4; kk++)
#pragma unroll
          for (int m = 0; m < 2; m++) mma128<0, 1>(acc[m], da + (m * 256 + (kk >> 1) * 512 + (kk & 1) * 2), db + kk * 128, kk ? 1 : g);
        wg_commit();
        wg_wait<1>();
        if (g) mbar_arrive_warp(sb + BAR_OEMPTY + (s ? s - 1 : 4) * 8);
      }
      PROF(wt == 0, 29);
      mbar_wait(sb + BAR_X, 0);
      PROF(wt == 0, 30);
      const int selw = ((0xFFFF - (int)(lds32(sb + OFF_MISC + 16) & 0xFFFF)) >> 4) - tm * 8 - w;
#pragma unroll
      for (int u = 0; u < 4; u++) {
        const int m = u >> 1, g = 13 - TL + u;
        const float g1 = 1.f - __uint_as_float(lds32(sb + OFF_G + (m * 64 + w * 16 + (u & 1) * 8 + (lane >> 2)) * 4));
        q[m][u & 1] = pack2(g1, g1);
#pragma unroll
        for (int j = 0; j < 4; j++) ldsm4(ta + res_off(u & 1, m) + ((((lane >> 4) + 2 * j) ^ (lane & 7)) << 4), xr[m][(u & 1) * 4 + j]);
        if (u == 3) break;
        mbar_wait(sb + BAR_OFULL + g % 5 * 8, g / 5 & 1);
        wg_fence();
#pragma unroll
        for (int kk = 0; kk < 4; kk++)
#pragma unroll
          for (int mm = 0; mm < 2; mm++)
            mma128<0, 1>(acc[mm], do0 + ((OA_SLOTS >> g * 4 & 15) * (SLOT >> 4) + mm * 256 + (kk >> 1) * 512 + (kk & 1) * 2), db0 + ((OW_SLOTS >> g * 4 & 15) * (SLOT >> 4) + kk * 128), 1);
        wg_commit();
        wg_wait<1>();
        if (g <= 11) mbar_arrive_warp(sb + BAR_OEMPTY + (g + 4) % 5 * 8);
      }
#pragma unroll
      for (int m = 0; m < 2; m++) {
#pragma unroll
        for (int g = 16 - TL; g < 16; g++) {
          if (m == 0) { mbar_wait(sb + BAR_OFULL + g % 5 * 8, g / 5 & 1); wg_fence(); }
#pragma unroll
          for (int kk = 0; kk < 4; kk++)
            mma128<0, 1>(acc[m], do0 + ((OA_SLOTS >> g * 4 & 15) * (SLOT >> 4) + m * 256 + (kk >> 1) * 512 + (kk & 1) * 2), db0 + ((OW_SLOTS >> g * 4 & 15) * (SLOT >> 4) + kk * 128), 1);
        }
        wg_commit();
      }
      mbar_arrive_warp(sb + BAR_DONE);
      const uint32_t tb = sb + w * 2048 + (lane >> 3) * 128 + (((lane ^ (lane >> 3)) & 7) << 4), tx = lane & 4 ? 64 : -64;
      uint8_t* og = (uint8_t*)pout + (size_t)(tm * 128 + w * 16 + (lane >> 3)) * 2048 + tn * 256 + (lane & 7) * 16;
      asm volatile("" : "+l"(og)::"memory");
#pragma unroll
      for (int m = 0; m < 2; m++) {
        if (selw == 4 * m) {
          mbar_wait(sb + BAR_Y, 0);
#pragma unroll
          for (int j = 0; j < 8; j++) ldsm4(ta + res_off(j >> 2, m) + ((((lane >> 4) + 2 * (j & 3)) ^ (lane & 7)) << 4), xr[m][j]);
        }
        if (m == 0) wg_wait<1>(); else wg_wait<0>();
        if (m) PROF(wt == 0, 31);
#pragma unroll
        for (int h = 0; h < 2; h++) {
#pragma unroll
          for (int j = 4 * h; j < 4 * h + 4; j++) {
            const float* v = &acc[m][8 * j];
            stsm4(ta + res_off(h, m) + ((((lane >> 4) + 2 * (j & 3)) ^ (lane & 7)) << 4),
                  fma_bf2(xr[m][j][0], q[m][0], pack2(v[0], v[1])), fma_bf2(xr[m][j][1], q[m][1], pack2(v[2], v[3])),
                  fma_bf2(xr[m][j][2], q[m][0], pack2(v[4], v[5])), fma_bf2(xr[m][j][3], q[m][1], pack2(v[6], v[7])));
          }
          if (m) {
            __syncwarp();
            uint4 t[4];
#pragma unroll
            for (int j = 0; j < 4; j++) t[j] = lds128(tb + res_off(h, m) + j * 512 - (j & 1) * tx);
#pragma unroll
            for (int j = 0; j < 4; j++) *(uint4*)(og + (m * 64 + j * 4) * 2048 + h * 128) = t[j];
          } else {
            fence_async_smem();
            __syncwarp();
            if (elect()) tma2d_store(&p.out, sb + res_off(h, m) + w * 2048, tn * 128 + h * 64, tm * 128 + m * 64 + w * 16);
          }
          if (!m && h && elect()) bulk_commit();
          if (m && h && elect()) asm volatile("cp.async.bulk.wait_group.read 0;" ::: "memory");
        }
        if (!m) PROF(wt == 0, 33);
      }
      PROF(wt == 0, 32);
    }
  }
}

typedef CUresult (*EncodeFn)(CUtensorMap*, CUtensorMapDataType, cuuint32_t, void*, const cuuint64_t*, const cuuint64_t*, const cuuint32_t*,
                             const cuuint32_t*, CUtensorMapInterleave, CUtensorMapSwizzle, CUtensorMapL2promotion, CUtensorMapFloatOOBfill);

void encode(EncodeFn fn, CUtensorMap* m, const void* ptr, int rank, const cuuint64_t* dims, const cuuint64_t* strides, const cuuint32_t* box,
            CUtensorMapSwizzle sw, CUtensorMapDataType dt = CU_TENSOR_MAP_DATA_TYPE_BFLOAT16) {
  const cuuint32_t es[3] = {1, 1, 1};
  fn(m, dt, rank, const_cast<void*>(ptr), dims, strides, box, es, CU_TENSOR_MAP_INTERLEAVE_NONE, sw,
     CU_TENSOR_MAP_L2_PROMOTION_L2_128B, CU_TENSOR_MAP_FLOAT_OOB_FILL_NONE);
}

}

extern "C" void kernel_launch(void* const* d_in, const int* in_sizes, int n_in, void* d_out, int out_size) {
  (void)in_sizes; (void)n_in; (void)out_size;
  EncodeFn fn = nullptr;
  cudaDriverEntryPointQueryResult qr;
  cudaGetDriverEntryPoint("cuTensorMapEncodeTiled", (void**)&fn, cudaEnableDefault, &qr);

  Params p;
  {
    const cuuint64_t dims[2] = {D_, S_}, str[1] = {D_ * 2};
    const cuuint32_t box[2] = {64, 128}, box_st[2] = {64, 16}, box_r[2] = {256, 16}, box_h[2] = {64, 64};
    encode(fn, &p.xh, d_in[0], 2, dims, str, box_h, CU_TENSOR_MAP_SWIZZLE_128B);
    encode(fn, &p.xr, d_in[0], 2, dims, str, box_r, CU_TENSOR_MAP_SWIZZLE_NONE);
    encode(fn, &p.x, d_in[0], 2, dims, str, box, CU_TENSOR_MAP_SWIZZLE_128B);
    encode(fn, &p.out, d_out, 2, dims, str, box_st, CU_TENSOR_MAP_SWIZZLE_128B);
  }
  {
    const cuuint64_t dims[3] = {D_, D_, 3}, str[2] = {3 * D_ * 2, D_ * 2};
    const cuuint32_t box[3] = {64, 64, 3};
    encode(fn, &p.w, d_in[1], 3, dims, str, box, CU_TENSOR_MAP_SWIZZLE_128B);
  }
  {
    const cuuint64_t dims[3] = {64, D_, D_ / 64}, str[2] = {D_ * 2, 128};
    const cuuint32_t box[3] = {64, 64, 2};
    encode(fn, &p.wo, d_in[2], 3, dims, str, box, CU_TENSOR_MAP_SWIZZLE_128B);
  }
  {
    const cuuint64_t dims[3] = {F_, D_ / 4, 4}, str[2] = {F_ * 8, F_ * 2};
    const cuuint32_t box[3] = {32, 16, 4};
    encode(fn, &p.gate, d_in[5], 3, dims, str, box, CU_TENSOR_MAP_SWIZZLE_NONE);
    encode(fn, &p.up, d_in[6], 3, dims, str, box, CU_TENSOR_MAP_SWIZZLE_NONE);
  }
  {
    const cuuint64_t dims[3] = {D_ / 4, F_, 2}, str[2] = {D_ * 2, D_};
    const cuuint32_t box[3] = {256, 4, 2};
    encode(fn, &p.down, d_in[7], 3, dims, str, box, CU_TENSOR_MAP_SWIZZLE_NONE, CU_TENSOR_MAP_DATA_TYPE_UINT32);
  }
  void* gs = nullptr;
  cudaGetSymbolAddress(&gs, g_scratch);
  typedef const __nv_bfloat16* bp;
  int dev = 0, sms = 0;
  cudaGetDevice(&dev);
  cudaDeviceGetAttribute(&sms, cudaDevAttrMultiProcessorCount, dev);
  const bool by_sm = BYSM && sms == NGRID;
  const auto kernel = by_sm ? fused_kernel<true> : fused_kernel<false>;
  cudaFuncSetAttribute(kernel, cudaFuncAttributeMaxDynamicSharedMemorySize, SMEM_BYTES);
  kernel<<<by_sm ? NGRID : NCTA, NTHREADS, SMEM_BYTES, cudaStreamPerThread>>>((bp)d_in[0], (Scratch*)gs, (bp)d_in[5], (bp)d_in[6], (bp)d_in[4], (bp)d_in[8], (__nv_bfloat16*)d_out, p);
}
```
